```python
import torch

def _softmax(x, axis=-1):
    return torch.softmax(x, dim=axis)
def _gelu(x):
    return torch.nn.functional.gelu(x, approximate="tanh")
def _silu(x):
    return torch.nn.functional.silu(x)
def _sigmoid(x):
    return torch.sigmoid(x)
def _layernorm(x, axis=-1, eps=1e-5):
    m = x.mean(dim=axis, keepdim=True)
    v = x.var(dim=axis, keepdim=True, unbiased=False)
    return (x - m) / torch.sqrt(v + eps)
def _scatter_add(tgt, idx, src, axis=0):
    return tgt.clone().index_add_(axis, idx, src)
def _segment_sum(src, seg, n):
    out = torch.zeros((n,) + src.shape[1:], dtype=src.dtype)
    return out.index_add_(0, seg, src)
def _pad(x, pw):
    flat = tuple(v for pair in reversed(pw) for v in pair)
    return torch.nn.functional.pad(x, flat)

kernel_name = 'parallel_sum__mha_block__moe_arch_mod__prompt'

def setup_inputs():

    _w = (lambda a: (lambda t: t.to(torch.bfloat16) if t.is_floating_point() else t)(torch.as_tensor(a)))
    def _A_setup():
        B, S, D, H = 1, 2048, 512, 32
        return {
            "x": _w((lambda *s: torch.randn(*s, dtype=torch.bfloat16) * 0.05)(B, S, D)),
            "wqkv": _w((lambda *s: torch.randn(*s, dtype=torch.bfloat16) * 0.2)(D, 3 * D)),
            "wo": _w((lambda *s: torch.randn(*s, dtype=torch.bfloat16) * 0.1)(D, D)),
        }
    _A_in = _A_setup()

    def _B_setup():
        B, S, D, F, C = 1, 2048, 512, 1792, 2
        return {
            "x": _w((lambda *s: torch.randn(*s, dtype=torch.bfloat16) * 0.05)(B, S, D)),
            "w_r": _w((lambda *s: torch.randn(*s, dtype=torch.bfloat16) * 0.1)(D)),
            "w_gate": _w((lambda *s: torch.randn(*s, dtype=torch.bfloat16) * 0.1)(D, F)),
            "w_up": _w((lambda *s: torch.randn(*s, dtype=torch.bfloat16) * 0.1)(D, F)),
            "w_down": _w((lambda *s: torch.randn(*s, dtype=torch.bfloat16) * 0.1)(F, D)),
        }
    _B_in = _B_setup()

    return {
        "A_x": _A_in["x"],
        "A_wqkv": _A_in["wqkv"],
        "A_wo": _A_in["wo"],
        "B_x": _B_in["x"],
        "B_w_r": _B_in["w_r"],
        "B_w_gate": _B_in["w_gate"],
        "B_w_up": _B_in["w_up"],
        "B_w_down": _B_in["w_down"],
    }

def reference(A_x, A_wqkv, A_wo, B_x, B_w_r, B_w_gate, B_w_up, B_w_down):
    def _A_ref(x, wqkv, wo):
        B, S, D = x.shape
        H = 32
        Dh = D // H
        qkv = (lambda x, *d: x.permute(*d))((x @ wqkv).reshape(B, S, 3, H, Dh), 2, 0, 3, 1, 4)
        q, k, v = qkv[0], qkv[1], qkv[2]
        scores = torch.einsum("bhqd,bhkd->bhqk", q, k) * (Dh ** -0.5)
        p = _softmax(scores, axis=-1)
        o = torch.einsum("bhqk,bhkd->bhqd", p, v)
        return (lambda x, *d: x.permute(*d))(o, 0, 2, 1, 3).reshape(B, S, D) @ wo

    def _B_ref(x, w_r, w_gate, w_up, w_down):
        B, S, D = x.shape
        C = 2
        r = x @ w_r
        idx = torch.argsort(-r, axis=-1)[:, :C]
        idx_e = (lambda x, n, axis: torch.repeat_interleave(x, n, dim=axis))(idx.reshape(B, C, 1), D, axis=2)
        x_sel = (lambda x, i, axis: torch.take_along_dim(x, i, dim=axis))(x, idx_e, axis=1)
        g = _silu(x_sel @ w_gate)
        u = x_sel @ w_up
        y = (g * u) @ w_down
        r_sel = _sigmoid((lambda x, i, axis: torch.take_along_dim(x, i, dim=axis))(r, idx, axis=1))
        y = y * r_sel.reshape(B, C, 1)
        b_off = (torch.arange(B) * S).reshape(B, 1)
        flat_idx = (idx + b_off).reshape(B * C)
        zero = (x * 0.0).reshape(B * S, D)
        upd = _scatter_add(zero, flat_idx, y.reshape(B * C, D), axis=0)
        return x + upd.reshape(B, S, D)

    x = A_x
    xn = _layernorm(x, axis=-1)
    return x + _A_ref(xn, A_wqkv, A_wo) + _B_ref(xn, B_w_r, B_w_gate, B_w_up, B_w_down)
```

```cpp
#include <cuda_runtime.h>
#include <cuda_bf16.h>
#include <cuda.h>
#include <stdint.h>
#include <type_traits>

namespace {

constexpr int S_LEN = 2048;
constexpr int DM = 512;
constexpr int NH = 32;
constexpr int FF = 1792;

__device__ __align__(1024) __nv_bfloat16 g_xn[S_LEN * DM];
__device__ float g_r[S_LEN];
__device__ __align__(1024) uint4 g_q[NH * 128 * 32];
__device__ __align__(1024) uint4 g_k[NH * 4096];
__device__ __align__(1024) uint4 g_v[NH * 4096];
__device__ __align__(1024) __nv_bfloat16 g_o[S_LEN * DM];
__device__ float g_ypart[4 * 2 * DM];
__device__ int g_sel[2];
__device__ float g_gate[2];

__device__ __forceinline__ uint32_t smem_u32(const void* p) { return (uint32_t)__cvta_generic_to_shared(p); }
__device__ __forceinline__ void pdl_wait() { asm volatile("griddepcontrol.wait;" ::: "memory"); }
__device__ __forceinline__ void pdl_launch() { asm volatile("griddepcontrol.launch_dependents;" ::: "memory"); }
__device__ __forceinline__ void mbar_init(uint32_t bar, uint32_t cnt) {
    asm volatile("mbarrier.init.shared::cta.b64 [%0], %1;" :: "r"(bar), "r"(cnt) : "memory");
}
__device__ __forceinline__ void mbar_expect_tx(uint32_t bar, uint32_t bytes) {
    asm volatile("mbarrier.arrive.expect_tx.shared::cta.b64 _, [%0], %1;" :: "r"(bar), "r"(bytes) : "memory");
}
__device__ __forceinline__ void mbar_arrive(uint32_t bar) {
    asm volatile("mbarrier.arrive.shared::cta.b64 _, [%0];" :: "r"(bar) : "memory");
}
__device__ __forceinline__ bool mbar_try(uint32_t bar, uint32_t parity) {
    uint32_t ok;
    asm volatile("{\n.reg .pred p;\nmbarrier.try_wait.parity.shared::cta.b64 p, [%1], %2;\nselp.u32 %0, 1, 0, p;\n}"
                 : "=r"(ok) : "r"(bar), "r"(parity) : "memory");
    return ok != 0;
}
__device__ __forceinline__ void mbar_wait(uint32_t bar, uint32_t parity) {
    uint32_t n = 0;
    while (!mbar_try(bar, parity)) { if (++n > (1u << 22)) __trap(); }
}
__device__ __forceinline__ void fence_barrier_init() { asm volatile("fence.mbarrier_init.release.cluster;" ::: "memory"); }
__device__ __forceinline__ void fence_proxy_async() { asm volatile("fence.proxy.async.shared::cta;" ::: "memory"); }
__device__ __forceinline__ void tma2d(uint32_t dst, const CUtensorMap* map, uint32_t bar, int c0, int c1) {
    asm volatile("cp.async.bulk.tensor.2d.shared::cluster.global.mbarrier::complete_tx::bytes [%0], [%1, {%3, %4}], [%2];"
                 :: "r"(dst), "l"((uint64_t)map), "r"(bar), "r"(c0), "r"(c1) : "memory");
}
__device__ __forceinline__ void bulk_g2s(uint32_t dst, const void* src, uint32_t bytes, uint32_t bar) {
    asm volatile("cp.async.bulk.shared::cluster.global.mbarrier::complete_tx::bytes [%0], [%1], %2, [%3];"
                 :: "r"(dst), "l"((uint64_t)src), "r"(bytes), "r"(bar) : "memory");
}
__device__ __forceinline__ uint64_t mkdesc(uint32_t addr, uint32_t lbo, uint32_t sbo, uint32_t swz) {
    return (uint64_t)((addr & 0x3FFFF) >> 4) | ((uint64_t)(lbo >> 4) << 16) | ((uint64_t)(sbo >> 4) << 32) | ((uint64_t)swz << 62);
}
#define WG_FENCE() asm volatile("wgmma.fence.sync.aligned;" ::: "memory")
#define WG_COMMIT() asm volatile("wgmma.commit_group.sync.aligned;" ::: "memory")
#define WG_WAIT(n) asm volatile("wgmma.wait_group.sync.aligned %0;" :: "n"(n) : "memory")

__device__ __forceinline__ float ex2(float x) { float y; asm("ex2.approx.ftz.f32 %0, %1;" : "=f"(y) : "f"(x)); return y; }
__device__ __forceinline__ uint32_t packbf(float lo, float hi) {
    uint32_t r; asm("cvt.rn.bf16x2.f32 %0, %1, %2;" : "=r"(r) : "f"(hi), "f"(lo)); return r;
}
__device__ __forceinline__ float bf_lo(uint32_t v) { return __uint_as_float(v << 16); }
__device__ __forceinline__ float bf_hi(uint32_t v) { return __uint_as_float(v & 0xffff0000u); }
__device__ __forceinline__ float bfr(float x) { return __bfloat162float(__float2bfloat16_rn(x)); }

__global__ void __launch_bounds__(256) ln_kernel(const __nv_bfloat16* __restrict__ x, const __nv_bfloat16* __restrict__ wr) {
    pdl_launch();
    const int warp = threadIdx.x >> 5, lane = threadIdx.x & 31;
    const int row = blockIdx.x * 8 + warp;
    const uint4* xr = reinterpret_cast<const uint4*>(x + (size_t)row * DM);
    uint4 a = xr[lane], b = xr[32 + lane];
    const uint4* wp = reinterpret_cast<const uint4*>(wr);
    uint4 wa = wp[lane], wb = wp[32 + lane];
    uint32_t u[8] = {a.x, a.y, a.z, a.w, b.x, b.y, b.z, b.w};
    uint32_t w[8] = {wa.x, wa.y, wa.z, wa.w, wb.x, wb.y, wb.z, wb.w};
    float f[16];
    float sum = 0.f;
#pragma unroll
    for (int i = 0; i < 8; i++) { f[2 * i] = bf_lo(u[i]); f[2 * i + 1] = bf_hi(u[i]); sum += f[2 * i] + f[2 * i + 1]; }
#pragma unroll
    for (int o = 16; o > 0; o >>= 1) sum += __shfl_xor_sync(~0u, sum, o);
    const float mean = sum * (1.f / DM);
    float sq = 0.f;
#pragma unroll
    for (int i = 0; i < 16; i++) { float d = f[i] - mean; sq = fmaf(d, d, sq); }
#pragma unroll
    for (int o = 16; o > 0; o >>= 1) sq += __shfl_xor_sync(~0u, sq, o);
    const float mb = bfr(mean);
    const float vb = bfr(sq * (1.f / DM));
    const float den = bfr(sqrtf(bfr(vb + 1e-5f)));
    const float rinv = 1.f / den;
    uint32_t o[8];
    float r = 0.f;
#pragma unroll
    for (int i = 0; i < 8; i++) {
        float d0 = bfr(f[2 * i] - mb), d1 = bfr(f[2 * i + 1] - mb);
        o[i] = packbf(d0 * rinv, d1 * rinv);
        r = fmaf(bf_lo(o[i]), bf_lo(w[i]), r);
        r = fmaf(bf_hi(o[i]), bf_hi(w[i]), r);
    }
#pragma unroll
    for (int of = 16; of > 0; of >>= 1) r += __shfl_xor_sync(~0u, r, of);
    uint4* xo = reinterpret_cast<uint4*>(g_xn + (size_t)row * DM);
    xo[lane] = make_uint4(o[0], o[1], o[2], o[3]);
    xo[32 + lane] = make_uint4(o[4], o[5], o[6], o[7]);
    if (lane == 0) g_r[row] = r;
}

constexpr int K1_ST = 5;
constexpr int K1_STAGE = 16384 + 24576;
constexpr int K1_SMEM = K1_ST * K1_STAGE + 1024 + 128;

__device__ __forceinline__ void wgmma_n192(float (&d)[96], uint64_t da, uint64_t db, int scale_d) {
    asm volatile("{\n.reg .pred p;\nsetp.ne.b32 p, %98, 0;\n"
        "wgmma.mma_async.sync.aligned.m64n192k16.f32.bf16.bf16 "
        "{%0,%1,%2,%3,%4,%5,%6,%7,%8,%9,%10,%11,%12,%13,%14,%15,%16,%17,%18,%19,%20,%21,%22,%23,"
        "%24,%25,%26,%27,%28,%29,%30,%31,%32,%33,%34,%35,%36,%37,%38,%39,%40,%41,%42,%43,%44,%45,%46,%47,"
        "%48,%49,%50,%51,%52,%53,%54,%55,%56,%57,%58,%59,%60,%61,%62,%63,%64,%65,%66,%67,%68,%69,%70,%71,"
        "%72,%73,%74,%75,%76,%77,%78,%79,%80,%81,%82,%83,%84,%85,%86,%87,%88,%89,%90,%91,%92,%93,%94,%95}, "
        "%96, %97, p, 1, 1, 0, 1;\n}"
        : "+f"(d[0]), "+f"(d[1]), "+f"(d[2]), "+f"(d[3]), "+f"(d[4]), "+f"(d[5]), "+f"(d[6]), "+f"(d[7]),
          "+f"(d[8]), "+f"(d[9]), "+f"(d[10]), "+f"(d[11]), "+f"(d[12]), "+f"(d[13]), "+f"(d[14]), "+f"(d[15]),
          "+f"(d[16]), "+f"(d[17]), "+f"(d[18]), "+f"(d[19]), "+f"(d[20]), "+f"(d[21]), "+f"(d[22]), "+f"(d[23]),
          "+f"(d[24]), "+f"(d[25]), "+f"(d[26]), "+f"(d[27]), "+f"(d[28]), "+f"(d[29]), "+f"(d[30]), "+f"(d[31]),
          "+f"(d[32]), "+f"(d[33]), "+f"(d[34]), "+f"(d[35]), "+f"(d[36]), "+f"(d[37]), "+f"(d[38]), "+f"(d[39]),
          "+f"(d[40]), "+f"(d[41]), "+f"(d[42]), "+f"(d[43]), "+f"(d[44]), "+f"(d[45]), "+f"(d[46]), "+f"(d[47]),
          "+f"(d[48]), "+f"(d[49]), "+f"(d[50]), "+f"(d[51]), "+f"(d[52]), "+f"(d[53]), "+f"(d[54]), "+f"(d[55]),
          "+f"(d[56]), "+f"(d[57]), "+f"(d[58]), "+f"(d[59]), "+f"(d[60]), "+f"(d[61]), "+f"(d[62]), "+f"(d[63]),
          "+f"(d[64]), "+f"(d[65]), "+f"(d[66]), "+f"(d[67]), "+f"(d[68]), "+f"(d[69]), "+f"(d[70]), "+f"(d[71]),
          "+f"(d[72]), "+f"(d[73]), "+f"(d[74]), "+f"(d[75]), "+f"(d[76]), "+f"(d[77]), "+f"(d[78]), "+f"(d[79]),
          "+f"(d[80]), "+f"(d[81]), "+f"(d[82]), "+f"(d[83]), "+f"(d[84]), "+f"(d[85]), "+f"(d[86]), "+f"(d[87]),
          "+f"(d[88]), "+f"(d[89]), "+f"(d[90]), "+f"(d[91]), "+f"(d[92]), "+f"(d[93]), "+f"(d[94]), "+f"(d[95])
        : "l"(da), "l"(db), "r"(scale_d));
}

__global__ void __launch_bounds__(288, 1) qkv_kernel(const __grid_constant__ CUtensorMap mapA, const __grid_constant__ CUtensorMap mapB) {
    extern __shared__ uint8_t smem_raw[];
    const uint32_t sbase = (smem_u32(smem_raw) + 1023u) & ~1023u;
    const uint32_t bars = sbase + K1_ST * K1_STAGE;
    const int warp = threadIdx.x >> 5, lane = threadIdx.x & 31;
    const int nb = blockIdx.x & 7, mb = blockIdx.x >> 3;
    if (threadIdx.x == 0) {
        for (int s = 0; s < K1_ST; s++) { mbar_init(bars + 8 * s, 1); mbar_init(bars + 8 * (K1_ST + s), 2); }
        fence_barrier_init();
    }
    __syncthreads();
    if (warp == 8) {
        if (lane == 0) {
            for (int c = 0; c < K1_ST; c++) {
                const uint32_t st = sbase + c * K1_STAGE;
                mbar_expect_tx(bars + 8 * c, K1_STAGE);
                for (int j = 0; j < 3; j++) tma2d(st + 16384 + j * 8192, &mapB, bars + 8 * c, nb * 192 + j * 64, c * 64);
            }
            pdl_wait();
            pdl_launch();
            for (int c = 0; c < K1_ST; c++) tma2d(sbase + c * K1_STAGE, &mapA, bars + 8 * c, c * 64, mb * 128);
            for (int c = K1_ST; c < 8; c++) {
                const int s = c - K1_ST;
                const uint32_t st = sbase + s * K1_STAGE;
                mbar_wait(bars + 8 * (K1_ST + s), 0);
                mbar_expect_tx(bars + 8 * s, K1_STAGE);
                tma2d(st, &mapA, bars + 8 * s, c * 64, mb * 128);
                for (int j = 0; j < 3; j++) tma2d(st + 16384 + j * 8192, &mapB, bars + 8 * s, nb * 192 + j * 64, c * 64);
            }
        }
        return;
    }
    const int wg = warp >> 2;
    float acc[96];
#pragma unroll
    for (int i = 0; i < 96; i++) acc[i] = 0.f;
#pragma unroll 1
    for (int c = 0; c < 8; c++) {
        const int s = c < K1_ST ? c : c - K1_ST;
        const uint32_t st = sbase + s * K1_STAGE;
        mbar_wait(bars + 8 * s, c < K1_ST ? 0 : 1);
        const uint64_t da = mkdesc(st + wg * 8192, 16, 1024, 1);
        const uint64_t db = mkdesc(st + 16384, 8192, 1024, 1);
        WG_FENCE();
#pragma unroll
        for (int k = 0; k < 4; k++) wgmma_n192(acc, da + k * 2, db + k * 128, (c | k) != 0);
        WG_COMMIT();
        if (c + K1_ST < 8 + 1) {
            WG_WAIT(1);
            if (c >= 1 && (threadIdx.x & 127) == 0) mbar_arrive(bars + 8 * (K1_ST + c - 1));
        }
    }
    WG_WAIT(0);
    const int g = lane >> 2, t = lane & 3;
    const int mt = mb * 8 + warp;
    const float qs = 0.25f * 1.4426950408889634f;
#pragma unroll
    for (int hh = 0; hh < 12; hh++) {
        const int gh = nb * 12 + hh;
        const float* a = &acc[hh * 8];
        if (gh < 32) {
            uint4 v;
            v.x = packbf(a[0] * qs, a[1] * qs); v.y = packbf(a[2] * qs, a[3] * qs);
            v.z = packbf(a[4] * qs, a[5] * qs); v.w = packbf(a[6] * qs, a[7] * qs);
            g_q[(gh * 128 + mt) * 32 + lane] = v;
        } else {
            uint32_t* dst = reinterpret_cast<uint32_t*>(gh < 64 ? g_k + (gh - 32) * 4096 : g_v + (gh - 64) * 4096);
            const int off = (mt * 16 + g) * 4 + t;
            dst[off] = packbf(a[0], a[1]);
            dst[off + 32] = packbf(a[2], a[3]);
            dst[8192 + off] = packbf(a[4], a[5]);
            dst[8192 + off + 32] = packbf(a[6], a[7]);
        }
    }
}

constexpr float SHIFT = 90.0f;
constexpr int K2_SMEM = 163840 + 1024 + 128;

__device__ __forceinline__ uint32_t polyexp(float lo, float hi) {
    uint32_t w, g, q, h;
    asm("cvt.pack.sat.s16.s32 %0, %1, %2;" : "=r"(w) : "r"(__float_as_uint(hi)), "r"(__float_as_uint(lo)));
    g = w & 0x007F007Fu;
    asm("fma.rn.f16x2 %0, %1, %2, %3;" : "=r"(q) : "r"(g), "r"(0xf940f940u), "r"(0x35513551u));
    asm("mul.rn.f16x2 %0, %1, %2;" : "=r"(h) : "r"(q), "r"(g));
    return w - h;
}
__device__ __forceinline__ void qk64(float (&s)[32], const uint32_t (&q)[4], uint64_t db) {
    asm volatile("wgmma.mma_async.sync.aligned.m64n64k16.f32.bf16.bf16 "
        "{%0,%1,%2,%3,%4,%5,%6,%7,%8,%9,%10,%11,%12,%13,%14,%15,%16,%17,%18,%19,%20,%21,%22,%23,%24,%25,%26,%27,%28,%29,%30,%31}, "
        "{%32,%33,%34,%35}, %36, 0, 1, 1, 0;"
        : "=f"(s[0]), "=f"(s[1]), "=f"(s[2]), "=f"(s[3]), "=f"(s[4]), "=f"(s[5]), "=f"(s[6]), "=f"(s[7]),
          "=f"(s[8]), "=f"(s[9]), "=f"(s[10]), "=f"(s[11]), "=f"(s[12]), "=f"(s[13]), "=f"(s[14]), "=f"(s[15]),
          "=f"(s[16]), "=f"(s[17]), "=f"(s[18]), "=f"(s[19]), "=f"(s[20]), "=f"(s[21]), "=f"(s[22]), "=f"(s[23]),
          "=f"(s[24]), "=f"(s[25]), "=f"(s[26]), "=f"(s[27]), "=f"(s[28]), "=f"(s[29]), "=f"(s[30]), "=f"(s[31])
        : "r"(q[0]), "r"(q[1]), "r"(q[2]), "r"(q[3]), "l"(db));
}
__device__ __forceinline__ void pv24(float (&o)[12], uint32_t a0, uint32_t a1, uint32_t a2, uint32_t a3, uint64_t db) {
    asm volatile("wgmma.mma_async.sync.aligned.m64n24k16.f32.bf16.bf16 "
        "{%0,%1,%2,%3,%4,%5,%6,%7,%8,%9,%10,%11}, {%12,%13,%14,%15}, %16, 1, 1, 1, 1;"
        : "+f"(o[0]), "+f"(o[1]), "+f"(o[2]), "+f"(o[3]), "+f"(o[4]), "+f"(o[5]), "+f"(o[6]), "+f"(o[7]),
          "+f"(o[8]), "+f"(o[9]), "+f"(o[10]), "+f"(o[11])
        : "r"(a0), "r"(a1), "r"(a2), "r"(a3), "l"(db));
}

__device__ __forceinline__ void attn_safe(float (&o)[12], const uint32_t (&q)[4], uint64_t kdesc0, uint64_t vdesc0) {
    float s[32];
    float m0 = -INFINITY, m1 = -INFINITY;
#pragma unroll
    for (int i = 0; i < 12; i++) o[i] = 0.f;
#pragma unroll 1
    for (int j = 0; j < 32; j++) {
        WG_FENCE();
        qk64(s, q, kdesc0 + (uint64_t)(j * 64));
        WG_COMMIT(); WG_WAIT(0);
        float n0 = m0, n1 = m1;
#pragma unroll
        for (int i = 0; i < 8; i++) { n0 = fmaxf(n0, fmaxf(s[4 * i], s[4 * i + 1])); n1 = fmaxf(n1, fmaxf(s[4 * i + 2], s[4 * i + 3])); }
        n0 = fmaxf(n0, __shfl_xor_sync(~0u, n0, 1)); n0 = fmaxf(n0, __shfl_xor_sync(~0u, n0, 2));
        n1 = fmaxf(n1, __shfl_xor_sync(~0u, n1, 1)); n1 = fmaxf(n1, __shfl_xor_sync(~0u, n1, 2));
        const float c0 = ex2(m0 - n0), c1 = ex2(m1 - n1);
        m0 = n0; m1 = n1;
#pragma unroll
        for (int i = 0; i < 3; i++) { o[4 * i] *= c0; o[4 * i + 1] *= c0; o[4 * i + 2] *= c1; o[4 * i + 3] *= c1; }
        uint32_t p[16];
#pragma unroll
        for (int i = 0; i < 8; i++) {
            p[2 * i] = packbf(ex2(s[4 * i] - m0), ex2(s[4 * i + 1] - m0));
            p[2 * i + 1] = packbf(ex2(s[4 * i + 2] - m1), ex2(s[4 * i + 3] - m1));
        }
        WG_FENCE();
#pragma unroll
        for (int kk = 0; kk < 4; kk++) pv24(o, p[4 * kk], p[4 * kk + 1], p[4 * kk + 2], p[4 * kk + 3], vdesc0 + (uint64_t)(j * 64 + kk * 16));
        WG_COMMIT(); WG_WAIT(0);
    }
}

__device__ void ffn_block(int c, uint8_t* smem, const __nv_bfloat16* __restrict__ wg, const __nv_bfloat16* __restrict__ wu,
                          const __nv_bfloat16* __restrict__ wd) {
    const int tid = threadIdx.x, warp = tid >> 5, lane = tid & 31;
    float* sx = reinterpret_cast<float*>(smem);
    float* sh = sx + 1024;
    float* red = sh + 1024;
    __shared__ float tv[32]; __shared__ int ti[32];
    __shared__ int ssel[2];
    float b1 = -INFINITY, b2 = -INFINITY; int i1 = 0x7fffffff, i2 = 0x7fffffff;
    auto push = [&](float v, int i) {
        if (v > b1 || (v == b1 && i < i1)) { b2 = b1; i2 = i1; b1 = v; i1 = i; }
        else if (v > b2 || (v == b2 && i < i2)) { b2 = v; i2 = i; }
    };
    for (int i = tid; i < S_LEN; i += 512) push(g_r[i], i);
#pragma unroll
    for (int o = 16; o > 0; o >>= 1) {
        float v1 = __shfl_xor_sync(~0u, b1, o), v2 = __shfl_xor_sync(~0u, b2, o);
        int j1 = __shfl_xor_sync(~0u, i1, o), j2 = __shfl_xor_sync(~0u, i2, o);
        push(v1, j1); push(v2, j2);
    }
    if (lane == 0) { tv[2 * warp] = b1; ti[2 * warp] = i1; tv[2 * warp + 1] = b2; ti[2 * warp + 1] = i2; }
    __syncthreads();
    if (warp == 0) {
        b1 = tv[lane]; i1 = ti[lane]; b2 = -INFINITY; i2 = 0x7fffffff;
#pragma unroll
        for (int o = 16; o > 0; o >>= 1) {
            float v1 = __shfl_xor_sync(~0u, b1, o), v2 = __shfl_xor_sync(~0u, b2, o);
            int j1 = __shfl_xor_sync(~0u, i1, o), j2 = __shfl_xor_sync(~0u, i2, o);
            push(v1, j1); push(v2, j2);
        }
        if (lane == 0) {
            i1 = min(max(i1, 0), S_LEN - 1); i2 = min(max(i2, 0), S_LEN - 1);
            ssel[0] = i1; ssel[1] = i2;
            if (c == 0) {
                g_sel[0] = i1; g_sel[1] = i2;
                g_gate[0] = bfr(1.f / (1.f + __expf(-bfr(b1))));
                g_gate[1] = bfr(1.f / (1.f + __expf(-bfr(b2))));
            }
        }
    }
    __syncthreads();
    for (int i = tid; i < 1024; i += 512) sx[i] = __bfloat162float(g_xn[(size_t)ssel[i >> 9] * DM + (i & 511)]);
    __syncthreads();
    {
        const int ch = tid % 56, kg = tid / 56;
        float ag[2][8], au[2][8];
#pragma unroll
        for (int j = 0; j < 8; j++) { ag[0][j] = ag[1][j] = au[0][j] = au[1][j] = 0.f; }
        if (kg < 9) {
            const uint4* pg = reinterpret_cast<const uint4*>(wg + c * 448 + ch * 8);
            const uint4* pu = reinterpret_cast<const uint4*>(wu + c * 448 + ch * 8);
#pragma unroll 4
            for (int k = kg; k < DM; k += 9) {
                const uint4 vg = __ldg(pg + (size_t)k * (FF / 8)), vu = __ldg(pu + (size_t)k * (FF / 8));
                const float x0 = sx[k], x1 = sx[512 + k];
                const uint32_t gw[4] = {vg.x, vg.y, vg.z, vg.w}, uw[4] = {vu.x, vu.y, vu.z, vu.w};
#pragma unroll
                for (int j = 0; j < 4; j++) {
                    const float g0 = bf_lo(gw[j]), g1 = bf_hi(gw[j]), u0 = bf_lo(uw[j]), u1 = bf_hi(uw[j]);
                    ag[0][2 * j] = fmaf(x0, g0, ag[0][2 * j]); ag[0][2 * j + 1] = fmaf(x0, g1, ag[0][2 * j + 1]);
                    ag[1][2 * j] = fmaf(x1, g0, ag[1][2 * j]); ag[1][2 * j + 1] = fmaf(x1, g1, ag[1][2 * j + 1]);
                    au[0][2 * j] = fmaf(x0, u0, au[0][2 * j]); au[0][2 * j + 1] = fmaf(x0, u1, au[0][2 * j + 1]);
                    au[1][2 * j] = fmaf(x1, u0, au[1][2 * j]); au[1][2 * j + 1] = fmaf(x1, u1, au[1][2 * j + 1]);
                }
            }
#pragma unroll
            for (int j = 0; j < 8; j++) {
                red[(kg * 4 + 0) * 448 + ch * 8 + j] = ag[0][j]; red[(kg * 4 + 1) * 448 + ch * 8 + j] = ag[1][j];
                red[(kg * 4 + 2) * 448 + ch * 8 + j] = au[0][j]; red[(kg * 4 + 3) * 448 + ch * 8 + j] = au[1][j];
            }
        }
        __syncthreads();
        for (int i = tid; i < 896; i += 512) {
            const int tok = i / 448, col = i % 448;
            float gs = 0.f, us = 0.f;
#pragma unroll
            for (int q = 0; q < 9; q++) { gs += red[(q * 4 + tok) * 448 + col]; us += red[(q * 4 + 2 + tok) * 448 + col]; }
            gs = bfr(gs); us = bfr(us);
            const float sg = bfr(gs / (1.f + __expf(-gs)));
            sh[tok * 448 + col] = bfr(sg * us);
        }
        __syncthreads();
    }
    {
        const int ch = tid & 63, kg = tid >> 6;
        float a[2][8];
#pragma unroll
        for (int j = 0; j < 8; j++) a[0][j] = a[1][j] = 0.f;
        const uint4* pd = reinterpret_cast<const uint4*>(wd + (size_t)c * 448 * DM + ch * 8);
#pragma unroll 8
        for (int k = kg; k < 448; k += 8) {
            const uint4 v = __ldg(pd + (size_t)k * (DM / 8));
            const float h0 = sh[k], h1 = sh[448 + k];
            const uint32_t w[4] = {v.x, v.y, v.z, v.w};
#pragma unroll
            for (int j = 0; j < 4; j++) {
                const float w0 = bf_lo(w[j]), w1 = bf_hi(w[j]);
                a[0][2 * j] = fmaf(h0, w0, a[0][2 * j]); a[0][2 * j + 1] = fmaf(h0, w1, a[0][2 * j + 1]);
                a[1][2 * j] = fmaf(h1, w0, a[1][2 * j]); a[1][2 * j + 1] = fmaf(h1, w1, a[1][2 * j + 1]);
            }
        }
#pragma unroll
        for (int j = 0; j < 8; j++) { red[(kg * 2 + 0) * 512 + ch * 8 + j] = a[0][j]; red[(kg * 2 + 1) * 512 + ch * 8 + j] = a[1][j]; }
        __syncthreads();
        for (int i = tid; i < 1024; i += 512) {
            float s = 0.f;
#pragma unroll
            for (int q = 0; q < 8; q++) s += red[q * 1024 + i];
            g_ypart[c * 1024 + i] = s;
        }
    }
}

__global__ void __launch_bounds__(512, 1) attn_kernel(const __nv_bfloat16* __restrict__ wg_, const __nv_bfloat16* __restrict__ wu_,
                                                      const __nv_bfloat16* __restrict__ wd_, float sc) {
    extern __shared__ uint8_t smem_raw[];
    const uint32_t sraw = smem_u32(smem_raw);
    const uint32_t sbase = (sraw + 1023u) & ~1023u;
    uint8_t* sptr = smem_raw + (sbase - sraw);
    if (blockIdx.x >= 128) {
        pdl_wait();
        pdl_launch();
        ffn_block(blockIdx.x - 128, sptr, wg_, wu_, wd_);
        return;
    }
    const uint32_t bars = sbase + 163840;
    const int head = blockIdx.x >> 2, quarter = blockIdx.x & 3;
    const int wg = threadIdx.x >> 7, warp = (threadIdx.x >> 5) & 3, lane = threadIdx.x & 31;
    if (threadIdx.x == 0) {
        for (int c = 0; c < 8; c++) mbar_init(bars + 8 * c, 1);
        fence_barrier_init();
    }
    {
        uint4* ones = reinterpret_cast<uint4*>(sptr + 131072);
        for (int i = threadIdx.x; i < 2048; i += 512) ones[i] = make_uint4(0x3f803f80u, 0x3f803f80u, 0x3f803f80u, 0x3f803f80u);
        fence_proxy_async();
    }
    __syncthreads();
    pdl_wait();
    pdl_launch();
    if (threadIdx.x == 0) {
        const uint8_t* kp = reinterpret_cast<const uint8_t*>(g_k + head * 4096);
        const uint8_t* vp = reinterpret_cast<const uint8_t*>(g_v + head * 4096);
        for (int c = 0; c < 8; c++) {
            mbar_expect_tx(bars + 8 * c, 16384);
            bulk_g2s(sbase + c * 4096, kp + c * 4096, 4096, bars + 8 * c);
            bulk_g2s(sbase + 32768 + c * 4096, kp + 32768 + c * 4096, 4096, bars + 8 * c);
            bulk_g2s(sbase + 65536 + c * 4096, vp + c * 4096, 4096, bars + 8 * c);
            bulk_g2s(sbase + 98304 + c * 4096, vp + 32768 + c * 4096, 4096, bars + 8 * c);
        }
    }
    const uint64_t kdesc0 = mkdesc(sbase, 32768, 128, 0);
    const uint64_t vdesc0 = mkdesc(sbase + 65536, 128, 32768, 0);
#pragma unroll 1
    for (int mt = 0; mt < 2; mt++) {
        const int m64 = quarter * 8 + mt * 4 + wg;
        uint32_t q[4];
        { const uint4 qq = g_q[(head * 128 + m64 * 4 + warp) * 32 + lane]; q[0] = qq.x; q[1] = qq.y; q[2] = qq.z; q[3] = qq.w; }
        float s[32], s2[32], o[12];
#pragma unroll
        for (int i = 0; i < 12; i++) o[i] = 0.f;
        mbar_wait(bars, 0);
        WG_FENCE();
        qk64(s, q, kdesc0);
        WG_COMMIT(); WG_WAIT(0);
        float mx0 = -INFINITY, mx1 = -INFINITY;
#pragma unroll
        for (int i = 0; i < 8; i++) { mx0 = fmaxf(mx0, fmaxf(s[4 * i], s[4 * i + 1])); mx1 = fmaxf(mx1, fmaxf(s[4 * i + 2], s[4 * i + 3])); }
        mx0 = fmaxf(mx0, __shfl_xor_sync(~0u, mx0, 1)); mx0 = fmaxf(mx0, __shfl_xor_sync(~0u, mx0, 2));
        mx1 = fmaxf(mx1, __shfl_xor_sync(~0u, mx1, 1)); mx1 = fmaxf(mx1, __shfl_xor_sync(~0u, mx1, 2));
        float cm0 = -(ceilf(mx0) + SHIFT), cm1 = -(ceilf(mx1) + SHIFT);
        float cp0 = (cm0 + 127.f) * sc, cp1 = (cm1 + 127.f) * sc;
        asm volatile("" : "+f"(cm0), "+f"(cm1), "+f"(cp0), "+f"(cp1));
        uint64_t kd = kdesc0, vd = vdesc0;
        auto step = [&](float (&sc_)[32], float (&sn)[32]) {
            kd += 64;
            WG_FENCE();
            qk64(sn, q, kd);
            WG_COMMIT();
#pragma unroll
            for (int kk = 0; kk < 4; kk++) {
                const int i0 = kk * 2, i1 = kk * 2 + 1;
                const uint32_t p0 = packbf(ex2(sc_[4 * i0] + cm0), ex2(sc_[4 * i0 + 1] + cm0));
                const uint32_t p1 = packbf(ex2(sc_[4 * i0 + 2] + cm1), ex2(sc_[4 * i0 + 3] + cm1));
                const uint32_t p2 = polyexp(fmaf(sc_[4 * i1], sc, cp0), fmaf(sc_[4 * i1 + 1], sc, cp0));
                const uint32_t p3 = polyexp(fmaf(sc_[4 * i1 + 2], sc, cp1), fmaf(sc_[4 * i1 + 3], sc, cp1));
                WG_FENCE();
                pv24(o, p0, p1, p2, p3, vd);
                vd += 16;
            }
            WG_COMMIT();
            WG_WAIT(1);
        };
#pragma unroll 1
        for (int c = 0; c < 8; c++) {
            if (mt == 0 && c < 7) mbar_wait(bars + 8 * (c + 1), 0);
            step(s, s2); step(s2, s); step(s, s2); step(s2, s);
        }
        WG_WAIT(0);
        bool bad = !(o[8] > 0.f) || !(o[10] > 0.f);
#pragma unroll
        for (int i = 0; i < 12; i++) bad = bad || !(fabsf(o[i]) <= 3.0e38f);
        uint32_t anybad;
        asm volatile("{\n.reg .pred p, q;\nsetp.ne.u32 p, %1, 0;\nbarrier.cta.red.or.pred q, %2, 128, p;\nselp.u32 %0, 1, 0, q;\n}"
                     : "=r"(anybad) : "r"((uint32_t)bad), "r"(wg + 1) : "memory");
        if (anybad) attn_safe(o, q, kdesc0, vdesc0);
        const int g = lane >> 2, t = lane & 3;
        const int row = m64 * 64 + warp * 16 + g;
        const float i0 = 1.f / o[8], i1 = 1.f / o[10];
        uint32_t* p0 = reinterpret_cast<uint32_t*>(g_o + (size_t)row * DM + head * 16 + t * 2);
        uint32_t* p1 = reinterpret_cast<uint32_t*>(g_o + (size_t)(row + 8) * DM + head * 16 + t * 2);
        p0[0] = packbf(o[0] * i0, o[1] * i0); p0[4] = packbf(o[4] * i0, o[5] * i0);
        p1[0] = packbf(o[2] * i1, o[3] * i1); p1[4] = packbf(o[6] * i1, o[7] * i1);
    }
}

constexpr int K3_SMEM = 8 * 8192 + 8 * 16384 + 1024 + 128;

__device__ __forceinline__ void wgmma_n64(float (&d)[32], uint64_t da, uint64_t db, int scale_d) {
    asm volatile("{\n.reg .pred p;\nsetp.ne.b32 p, %34, 0;\n"
        "wgmma.mma_async.sync.aligned.m64n64k16.f32.bf16.bf16 "
        "{%0,%1,%2,%3,%4,%5,%6,%7,%8,%9,%10,%11,%12,%13,%14,%15,%16,%17,%18,%19,%20,%21,%22,%23,%24,%25,%26,%27,%28,%29,%30,%31}, "
        "%32, %33, p, 1, 1, 0, 1;\n}"
        : "+f"(d[0]), "+f"(d[1]), "+f"(d[2]), "+f"(d[3]), "+f"(d[4]), "+f"(d[5]), "+f"(d[6]), "+f"(d[7]),
          "+f"(d[8]), "+f"(d[9]), "+f"(d[10]), "+f"(d[11]), "+f"(d[12]), "+f"(d[13]), "+f"(d[14]), "+f"(d[15]),
          "+f"(d[16]), "+f"(d[17]), "+f"(d[18]), "+f"(d[19]), "+f"(d[20]), "+f"(d[21]), "+f"(d[22]), "+f"(d[23]),
          "+f"(d[24]), "+f"(d[25]), "+f"(d[26]), "+f"(d[27]), "+f"(d[28]), "+f"(d[29]), "+f"(d[30]), "+f"(d[31])
        : "l"(da), "l"(db), "r"(scale_d));
}

__global__ void __launch_bounds__(256, 1) oproj_kernel(const __grid_constant__ CUtensorMap mapA, const __grid_constant__ CUtensorMap mapB,
                                                       const __nv_bfloat16* __restrict__ x, __nv_bfloat16* __restrict__ out) {
    extern __shared__ uint8_t smem_raw[];
    const uint32_t sbase = (smem_u32(smem_raw) + 1023u) & ~1023u;
    const uint32_t sA = sbase, sB = sbase + 8 * 8192, bars = sbase + 8 * 8192 + 8 * 16384;
    const int warp = threadIdx.x >> 5, lane = threadIdx.x & 31, wg = warp >> 2;
    const int nb = blockIdx.x & 3, mb = blockIdx.x >> 2;
    if (threadIdx.x == 0) {
        for (int c = 0; c < 8; c++) mbar_init(bars + 8 * c, 1);
        fence_barrier_init();
        for (int c = 0; c < 8; c++) {
            mbar_expect_tx(bars + 8 * c, 8192 + 16384);
            tma2d(sB + c * 16384, &mapB, bars + 8 * c, nb * 128, c * 64);
            tma2d(sB + c * 16384 + 8192, &mapB, bars + 8 * c, nb * 128 + 64, c * 64);
        }
    }
    const int g = lane >> 2, t = lane & 3;
    const int row0 = mb * 64 + (warp & 3) * 16 + g;
    const int col0 = nb * 128 + wg * 64 + t * 2;
    uint32_t xv[16], nv[16];
#pragma unroll
    for (int i = 0; i < 8; i++) {
        xv[2 * i] = *reinterpret_cast<const uint32_t*>(x + (size_t)row0 * DM + col0 + i * 8);
        xv[2 * i + 1] = *reinterpret_cast<const uint32_t*>(x + (size_t)(row0 + 8) * DM + col0 + i * 8);
        nv[2 * i] = *reinterpret_cast<const uint32_t*>(g_xn + (size_t)row0 * DM + col0 + i * 8);
        nv[2 * i + 1] = *reinterpret_cast<const uint32_t*>(g_xn + (size_t)(row0 + 8) * DM + col0 + i * 8);
    }
    __syncthreads();
    pdl_wait();
    if (threadIdx.x == 0) {
        for (int c = 0; c < 8; c++) tma2d(sA + c * 8192, &mapA, bars + 8 * c, c * 64, mb * 64);
    }
    float acc[32];
#pragma unroll
    for (int i = 0; i < 32; i++) acc[i] = 0.f;
#pragma unroll 1
    for (int c = 0; c < 8; c++) {
        mbar_wait(bars + 8 * c, 0);
        const uint64_t da = mkdesc(sA + c * 8192, 16, 1024, 1);
        const uint64_t db = mkdesc(sB + c * 16384 + wg * 8192, 8192, 1024, 1);
        WG_FENCE();
#pragma unroll
        for (int k = 0; k < 4; k++) wgmma_n64(acc, da + k * 2, db + k * 128, (c | k) != 0);
        WG_COMMIT();
    }
    const int sel0 = g_sel[0], sel1 = g_sel[1];
    WG_WAIT(0);
#pragma unroll
    for (int h = 0; h < 2; h++) {
        const int row = row0 + h * 8;
        const int which = row == sel0 ? 0 : (row == sel1 ? 1 : -1);
#pragma unroll
        for (int i = 0; i < 8; i++) {
            const int col = col0 + i * 8;
            float b0 = bf_lo(nv[2 * i + h]), b1 = bf_hi(nv[2 * i + h]);
            if (which >= 0) {
                float y0 = 0.f, y1 = 0.f;
#pragma unroll
                for (int c = 0; c < 4; c++) { y0 += g_ypart[c * 1024 + which * 512 + col]; y1 += g_ypart[c * 1024 + which * 512 + col + 1]; }
                const float gt = g_gate[which];
                b0 = bfr(b0 + bfr(bfr(y0) * gt)); b1 = bfr(b1 + bfr(bfr(y1) * gt));
            }
            const float t0 = bfr(bf_lo(xv[2 * i + h]) + bfr(acc[4 * i + 2 * h]));
            const float t1 = bfr(bf_hi(xv[2 * i + h]) + bfr(acc[4 * i + 2 * h + 1]));
            *reinterpret_cast<uint32_t*>(out + (size_t)row * DM + col) = packbf(t0 + b0, t1 + b1);
        }
    }
}

typedef CUresult (*EncodeFn)(CUtensorMap*, CUtensorMapDataType, cuuint32_t, void*, const cuuint64_t*, const cuuint64_t*,
                             const cuuint32_t*, const cuuint32_t*, CUtensorMapInterleave, CUtensorMapSwizzle,
                             CUtensorMapL2promotion, CUtensorMapFloatOOBfill);

void make_map(EncodeFn fn, CUtensorMap* m, const void* ptr, uint64_t inner, uint64_t outer, uint32_t box_inner, uint32_t box_outer) {
    cuuint64_t dims[2] = {inner, outer};
    cuuint64_t strides[1] = {inner * 2};
    cuuint32_t box[2] = {box_inner, box_outer};
    cuuint32_t es[2] = {1, 1};
    fn(m, CU_TENSOR_MAP_DATA_TYPE_BFLOAT16, 2, const_cast<void*>(ptr), dims, strides, box, es, CU_TENSOR_MAP_INTERLEAVE_NONE,
       CU_TENSOR_MAP_SWIZZLE_128B, CU_TENSOR_MAP_L2_PROMOTION_L2_256B, CU_TENSOR_MAP_FLOAT_OOB_FILL_NONE);
}

template <typename... KArgs, typename... Args>
void launch(void (*kern)(KArgs...), int grid, int block, int smem, bool pdl, Args... args) {
    cudaLaunchConfig_t cfg = {};
    cfg.gridDim = dim3(grid); cfg.blockDim = dim3(block); cfg.dynamicSmemBytes = smem; cfg.stream = cudaStreamPerThread;
    cudaLaunchAttribute at[1];
    at[0].id = cudaLaunchAttributeProgrammaticStreamSerialization;
    at[0].val.programmaticStreamSerializationAllowed = 1;
    cfg.attrs = at; cfg.numAttrs = pdl ? 1 : 0;
    cudaLaunchKernelEx(&cfg, kern, KArgs(args)...);
}

}

extern "C" void kernel_launch(void* const* d_in, const int* in_sizes, int n_in, void* d_out, int out_size) {
    const __nv_bfloat16* x = (const __nv_bfloat16*)d_in[0];
    const __nv_bfloat16* wqkv = (const __nv_bfloat16*)d_in[1];
    const __nv_bfloat16* wo = (const __nv_bfloat16*)d_in[2];
    const __nv_bfloat16* wr = (const __nv_bfloat16*)d_in[4];
    const __nv_bfloat16* wgate = (const __nv_bfloat16*)d_in[5];
    const __nv_bfloat16* wup = (const __nv_bfloat16*)d_in[6];
    const __nv_bfloat16* wdown = (const __nv_bfloat16*)d_in[7];
    __nv_bfloat16* out = (__nv_bfloat16*)d_out;

    static EncodeFn enc = nullptr;
    static void* p_xn = nullptr; static void* p_o = nullptr;
    if (!enc) {
        void* fn = nullptr; cudaDriverEntryPointQueryResult qr;
        cudaGetDriverEntryPoint("cuTensorMapEncodeTiled", &fn, cudaEnableDefault, &qr);
        enc = (EncodeFn)fn;
        cudaGetSymbolAddress(&p_xn, g_xn);
        cudaGetSymbolAddress(&p_o, g_o);
        cudaFuncSetAttribute(qkv_kernel, cudaFuncAttributeMaxDynamicSharedMemorySize, K1_SMEM);
        cudaFuncSetAttribute(attn_kernel, cudaFuncAttributeMaxDynamicSharedMemorySize, K2_SMEM);
        cudaFuncSetAttribute(oproj_kernel, cudaFuncAttributeMaxDynamicSharedMemorySize, K3_SMEM);
    }
    CUtensorMap mXn, mWqkv, mO, mWo;
    make_map(enc, &mXn, p_xn, DM, S_LEN, 64, 128);
    make_map(enc, &mWqkv, wqkv, 3 * DM, DM, 64, 64);
    make_map(enc, &mO, p_o, DM, S_LEN, 64, 64);
    make_map(enc, &mWo, wo, DM, DM, 64, 64);

    const float sc = 1.7936620522e-43f;
    (void)sc;
    union { uint32_t u; float f; } scu; scu.u = 128u;

    launch(ln_kernel, S_LEN / 8, 256, 0, false, x, wr);
    launch(qkv_kernel, 128, 288, K1_SMEM, true, mXn, mWqkv);
    launch(attn_kernel, 132, 512, K2_SMEM, true, wgate, wup, wdown, scu.f);
    launch(oproj_kernel, 128, 256, K3_SMEM, true, mO, mWo, x, out);
}
```

```cpp
#include <cuda_runtime.h>
#include <cuda_bf16.h>
#include <cuda.h>
#include <stdint.h>
#include <type_traits>

namespace {

constexpr int S_LEN = 2048;
constexpr int DM = 512;
constexpr int NH = 32;
constexpr int FF = 1792;

__device__ __align__(1024) __nv_bfloat16 g_xn[S_LEN * DM];
__device__ float g_r[S_LEN];
__device__ __align__(1024) uint4 g_q[NH * 128 * 32];
__device__ __align__(1024) uint4 g_k[NH * 4096];
__device__ __align__(1024) uint4 g_v[NH * 4096];
__device__ __align__(1024) __nv_bfloat16 g_o[S_LEN * DM];
__device__ float g_ypart[4 * 2 * DM];
__device__ int g_sel[2];
__device__ float g_gate[2];

__device__ __forceinline__ uint32_t smem_u32(const void* p) { return (uint32_t)__cvta_generic_to_shared(p); }
__device__ __forceinline__ void pdl_wait() { asm volatile("griddepcontrol.wait;" ::: "memory"); }
__device__ __forceinline__ void pdl_launch() { asm volatile("griddepcontrol.launch_dependents;" ::: "memory"); }
__device__ __forceinline__ void mbar_init(uint32_t bar, uint32_t cnt) {
    asm volatile("mbarrier.init.shared::cta.b64 [%0], %1;" :: "r"(bar), "r"(cnt) : "memory");
}
__device__ __forceinline__ void mbar_expect_tx(uint32_t bar, uint32_t bytes) {
    asm volatile("mbarrier.arrive.expect_tx.shared::cta.b64 _, [%0], %1;" :: "r"(bar), "r"(bytes) : "memory");
}
__device__ __forceinline__ void mbar_arrive(uint32_t bar) {
    asm volatile("mbarrier.arrive.shared::cta.b64 _, [%0];" :: "r"(bar) : "memory");
}
__device__ __forceinline__ void mbar_wait(uint32_t bar, uint32_t parity) {
    asm volatile("{\n.reg .pred p;\n.reg .u32 n;\nmov.u32 n, 0;\n"
                 "WAIT_%=:\n"
                 "mbarrier.try_wait.parity.shared::cta.b64 p, [%0], %1;\n"
                 "@p bra DONE_%=;\n"
                 "add.u32 n, n, 1;\n"
                 "setp.lt.u32 p, n, 4000000;\n"
                 "@p bra WAIT_%=;\n"
                 "trap;\n"
                 "DONE_%=:\n}"
                 :: "r"(bar), "r"(parity) : "memory");
}
__device__ __forceinline__ void fence_barrier_init() { asm volatile("fence.mbarrier_init.release.cluster;" ::: "memory"); }
__device__ __forceinline__ void fence_proxy_async() { asm volatile("fence.proxy.async.shared::cta;" ::: "memory"); }
__device__ __forceinline__ void tma2d(uint32_t dst, const CUtensorMap* map, uint32_t bar, int c0, int c1) {
    asm volatile("cp.async.bulk.tensor.2d.shared::cluster.global.mbarrier::complete_tx::bytes [%0], [%1, {%3, %4}], [%2];"
                 :: "r"(dst), "l"((uint64_t)map), "r"(bar), "r"(c0), "r"(c1) : "memory");
}
__device__ __forceinline__ void bulk_g2s(uint32_t dst, const void* src, uint32_t bytes, uint32_t bar) {
    asm volatile("cp.async.bulk.shared::cluster.global.mbarrier::complete_tx::bytes [%0], [%1], %2, [%3];"
                 :: "r"(dst), "l"((uint64_t)src), "r"(bytes), "r"(bar) : "memory");
}
__device__ __forceinline__ uint64_t mkdesc(uint32_t addr, uint32_t lbo, uint32_t sbo, uint32_t swz) {
    return (uint64_t)((addr & 0x3FFFF) >> 4) | ((uint64_t)(lbo >> 4) << 16) | ((uint64_t)(sbo >> 4) << 32) | ((uint64_t)swz << 62);
}
#define WG_FENCE() asm volatile("wgmma.fence.sync.aligned;" ::: "memory")
#define WG_COMMIT() asm volatile("wgmma.commit_group.sync.aligned;" ::: "memory")
#define WG_WAIT(n) asm volatile("wgmma.wait_group.sync.aligned %0;" :: "n"(n) : "memory")

__device__ __forceinline__ float ex2(float x) { float y; asm("ex2.approx.ftz.f32 %0, %1;" : "=f"(y) : "f"(x)); return y; }
__device__ __forceinline__ uint32_t packbf(float lo, float hi) {
    uint32_t r; asm("cvt.rn.bf16x2.f32 %0, %1, %2;" : "=r"(r) : "f"(hi), "f"(lo)); return r;
}
__device__ __forceinline__ float bf_lo(uint32_t v) { return __uint_as_float(v << 16); }
__device__ __forceinline__ float bf_hi(uint32_t v) { return __uint_as_float(v & 0xffff0000u); }
__device__ __forceinline__ float bfr(float x) { return __bfloat162float(__float2bfloat16_rn(x)); }

__global__ void __launch_bounds__(256) ln_kernel(const __nv_bfloat16* __restrict__ x, const __nv_bfloat16* __restrict__ wr) {
    pdl_launch();
    const int warp = threadIdx.x >> 5, lane = threadIdx.x & 31;
    const int row = blockIdx.x * 8 + warp;
    const uint4* xr = reinterpret_cast<const uint4*>(x + (size_t)row * DM);
    uint4 a = xr[lane], b = xr[32 + lane];
    const uint4* wp = reinterpret_cast<const uint4*>(wr);
    uint4 wa = wp[lane], wb = wp[32 + lane];
    uint32_t u[8] = {a.x, a.y, a.z, a.w, b.x, b.y, b.z, b.w};
    uint32_t w[8] = {wa.x, wa.y, wa.z, wa.w, wb.x, wb.y, wb.z, wb.w};
    float f[16];
    float sum = 0.f;
#pragma unroll
    for (int i = 0; i < 8; i++) { f[2 * i] = bf_lo(u[i]); f[2 * i + 1] = bf_hi(u[i]); sum += f[2 * i] + f[2 * i + 1]; }
#pragma unroll
    for (int o = 16; o > 0; o >>= 1) sum += __shfl_xor_sync(~0u, sum, o);
    const float mean = sum * (1.f / DM);
    float sq = 0.f;
#pragma unroll
    for (int i = 0; i < 16; i++) { float d = f[i] - mean; sq = fmaf(d, d, sq); }
#pragma unroll
    for (int o = 16; o > 0; o >>= 1) sq += __shfl_xor_sync(~0u, sq, o);
    const float mb = bfr(mean);
    const float vb = bfr(sq * (1.f / DM));
    const float den = bfr(sqrtf(bfr(vb + 1e-5f)));
    const float rinv = 1.f / den;
    uint32_t o[8];
    float r = 0.f;
#pragma unroll
    for (int i = 0; i < 8; i++) {
        float d0 = bfr(f[2 * i] - mb), d1 = bfr(f[2 * i + 1] - mb);
        o[i] = packbf(d0 * rinv, d1 * rinv);
        r = fmaf(bf_lo(o[i]), bf_lo(w[i]), r);
        r = fmaf(bf_hi(o[i]), bf_hi(w[i]), r);
    }
#pragma unroll
    for (int of = 16; of > 0; of >>= 1) r += __shfl_xor_sync(~0u, r, of);
    uint4* xo = reinterpret_cast<uint4*>(g_xn + (size_t)row * DM);
    xo[lane] = make_uint4(o[0], o[1], o[2], o[3]);
    xo[32 + lane] = make_uint4(o[4], o[5], o[6], o[7]);
    if (lane == 0) g_r[row] = r;
}

constexpr int K1_ST = 5;
constexpr int K1_STAGE = 16384 + 24576;
constexpr int K1_SMEM = K1_ST * K1_STAGE + 1024 + 128;

__device__ __forceinline__ void wgmma_n192(float (&d)[96], uint64_t da, uint64_t db, int scale_d) {
    asm volatile("{\n.reg .pred p;\nsetp.ne.b32 p, %98, 0;\n"
        "wgmma.mma_async.sync.aligned.m64n192k16.f32.bf16.bf16 "
        "{%0,%1,%2,%3,%4,%5,%6,%7,%8,%9,%10,%11,%12,%13,%14,%15,%16,%17,%18,%19,%20,%21,%22,%23,"
        "%24,%25,%26,%27,%28,%29,%30,%31,%32,%33,%34,%35,%36,%37,%38,%39,%40,%41,%42,%43,%44,%45,%46,%47,"
        "%48,%49,%50,%51,%52,%53,%54,%55,%56,%57,%58,%59,%60,%61,%62,%63,%64,%65,%66,%67,%68,%69,%70,%71,"
        "%72,%73,%74,%75,%76,%77,%78,%79,%80,%81,%82,%83,%84,%85,%86,%87,%88,%89,%90,%91,%92,%93,%94,%95}, "
        "%96, %97, p, 1, 1, 0, 1;\n}"
        : "+f"(d[0]), "+f"(d[1]), "+f"(d[2]), "+f"(d[3]), "+f"(d[4]), "+f"(d[5]), "+f"(d[6]), "+f"(d[7]),
          "+f"(d[8]), "+f"(d[9]), "+f"(d[10]), "+f"(d[11]), "+f"(d[12]), "+f"(d[13]), "+f"(d[14]), "+f"(d[15]),
          "+f"(d[16]), "+f"(d[17]), "+f"(d[18]), "+f"(d[19]), "+f"(d[20]), "+f"(d[21]), "+f"(d[22]), "+f"(d[23]),
          "+f"(d[24]), "+f"(d[25]), "+f"(d[26]), "+f"(d[27]), "+f"(d[28]), "+f"(d[29]), "+f"(d[30]), "+f"(d[31]),
          "+f"(d[32]), "+f"(d[33]), "+f"(d[34]), "+f"(d[35]), "+f"(d[36]), "+f"(d[37]), "+f"(d[38]), "+f"(d[39]),
          "+f"(d[40]), "+f"(d[41]), "+f"(d[42]), "+f"(d[43]), "+f"(d[44]), "+f"(d[45]), "+f"(d[46]), "+f"(d[47]),
          "+f"(d[48]), "+f"(d[49]), "+f"(d[50]), "+f"(d[51]), "+f"(d[52]), "+f"(d[53]), "+f"(d[54]), "+f"(d[55]),
          "+f"(d[56]), "+f"(d[57]), "+f"(d[58]), "+f"(d[59]), "+f"(d[60]), "+f"(d[61]), "+f"(d[62]), "+f"(d[63]),
          "+f"(d[64]), "+f"(d[65]), "+f"(d[66]), "+f"(d[67]), "+f"(d[68]), "+f"(d[69]), "+f"(d[70]), "+f"(d[71]),
          "+f"(d[72]), "+f"(d[73]), "+f"(d[74]), "+f"(d[75]), "+f"(d[76]), "+f"(d[77]), "+f"(d[78]), "+f"(d[79]),
          "+f"(d[80]), "+f"(d[81]), "+f"(d[82]), "+f"(d[83]), "+f"(d[84]), "+f"(d[85]), "+f"(d[86]), "+f"(d[87]),
          "+f"(d[88]), "+f"(d[89]), "+f"(d[90]), "+f"(d[91]), "+f"(d[92]), "+f"(d[93]), "+f"(d[94]), "+f"(d[95])
        : "l"(da), "l"(db), "r"(scale_d));
}

__global__ void __launch_bounds__(288, 1) qkv_kernel(const __grid_constant__ CUtensorMap mapA, const __grid_constant__ CUtensorMap mapB) {
    extern __shared__ uint8_t smem_raw[];
    const uint32_t sbase = (smem_u32(smem_raw) + 1023u) & ~1023u;
    const uint32_t bars = sbase + K1_ST * K1_STAGE;
    const int warp = threadIdx.x >> 5, lane = threadIdx.x & 31;
    const int nb = blockIdx.x & 7, mb = blockIdx.x >> 3;
    if (threadIdx.x == 0) {
        for (int s = 0; s < K1_ST; s++) { mbar_init(bars + 8 * s, 1); mbar_init(bars + 8 * (K1_ST + s), 2); }
        fence_barrier_init();
    }
    __syncthreads();
    if (warp == 8) {
        if (lane == 0) {
            for (int c = 0; c < K1_ST; c++) {
                const uint32_t st = sbase + c * K1_STAGE;
                mbar_expect_tx(bars + 8 * c, K1_STAGE);
                for (int j = 0; j < 3; j++) tma2d(st + 16384 + j * 8192, &mapB, bars + 8 * c, nb * 192 + j * 64, c * 64);
            }
            pdl_wait();
            pdl_launch();
            for (int c = 0; c < K1_ST; c++) tma2d(sbase + c * K1_STAGE, &mapA, bars + 8 * c, c * 64, mb * 128);
            for (int c = K1_ST; c < 8; c++) {
                const int s = c - K1_ST;
                const uint32_t st = sbase + s * K1_STAGE;
                mbar_wait(bars + 8 * (K1_ST + s), 0);
                mbar_expect_tx(bars + 8 * s, K1_STAGE);
                tma2d(st, &mapA, bars + 8 * s, c * 64, mb * 128);
                for (int j = 0; j < 3; j++) tma2d(st + 16384 + j * 8192, &mapB, bars + 8 * s, nb * 192 + j * 64, c * 64);
            }
        }
        return;
    }
    const int wg = warp >> 2;
    float acc[96];
#pragma unroll
    for (int i = 0; i < 96; i++) acc[i] = 0.f;
#pragma unroll 1
    for (int c = 0; c < 8; c++) {
        const int s = c < K1_ST ? c : c - K1_ST;
        const uint32_t st = sbase + s * K1_STAGE;
        mbar_wait(bars + 8 * s, c < K1_ST ? 0 : 1);
        const uint64_t da = mkdesc(st + wg * 8192, 16, 1024, 1);
        const uint64_t db = mkdesc(st + 16384, 8192, 1024, 1);
        WG_FENCE();
#pragma unroll
        for (int k = 0; k < 4; k++) wgmma_n192(acc, da + k * 2, db + k * 128, (c | k) != 0);
        WG_COMMIT();
        if (c + K1_ST < 8 + 1) {
            WG_WAIT(1);
            if (c >= 1 && (threadIdx.x & 127) == 0) mbar_arrive(bars + 8 * (K1_ST + c - 1));
        }
    }
    WG_WAIT(0);
    const int g = lane >> 2, t = lane & 3;
    const int mt = mb * 8 + warp;
    const float qs = 0.25f * 1.4426950408889634f;
#pragma unroll
    for (int hh = 0; hh < 12; hh++) {
        const int gh = nb * 12 + hh;
        const float* a = &acc[hh * 8];
        if (gh < 32) {
            uint4 v;
            v.x = packbf(a[0] * qs, a[1] * qs); v.y = packbf(a[2] * qs, a[3] * qs);
            v.z = packbf(a[4] * qs, a[5] * qs); v.w = packbf(a[6] * qs, a[7] * qs);
            g_q[(gh * 128 + mt) * 32 + lane] = v;
        } else {
            uint32_t* dst = reinterpret_cast<uint32_t*>(gh < 64 ? g_k + (gh - 32) * 4096 : g_v + (gh - 64) * 4096);
            const int off = (mt * 16 + g) * 4 + t;
            dst[off] = packbf(a[0], a[1]);
            dst[off + 32] = packbf(a[2], a[3]);
            dst[8192 + off] = packbf(a[4], a[5]);
            dst[8192 + off + 32] = packbf(a[6], a[7]);
        }
    }
}

constexpr float SHIFT = 90.0f;
constexpr int K2_SMEM = 163840 + 1024 + 128;

__device__ __forceinline__ uint32_t polyexp(float lo, float hi) {
    uint32_t w, g, q, h;
    asm("cvt.pack.sat.s16.s32 %0, %1, %2;" : "=r"(w) : "r"(__float_as_uint(hi)), "r"(__float_as_uint(lo)));
    g = w & 0x007F007Fu;
    asm("fma.rn.f16x2 %0, %1, %2, %3;" : "=r"(q) : "r"(g), "r"(0xf940f940u), "r"(0x35513551u));
    asm("mul.rn.f16x2 %0, %1, %2;" : "=r"(h) : "r"(q), "r"(g));
    return w - h;
}
__device__ __forceinline__ void qk64(float (&s)[32], const uint32_t (&q)[4], uint64_t db) {
    asm volatile("wgmma.mma_async.sync.aligned.m64n64k16.f32.bf16.bf16 "
        "{%0,%1,%2,%3,%4,%5,%6,%7,%8,%9,%10,%11,%12,%13,%14,%15,%16,%17,%18,%19,%20,%21,%22,%23,%24,%25,%26,%27,%28,%29,%30,%31}, "
        "{%32,%33,%34,%35}, %36, 0, 1, 1, 0;"
        : "=f"(s[0]), "=f"(s[1]), "=f"(s[2]), "=f"(s[3]), "=f"(s[4]), "=f"(s[5]), "=f"(s[6]), "=f"(s[7]),
          "=f"(s[8]), "=f"(s[9]), "=f"(s[10]), "=f"(s[11]), "=f"(s[12]), "=f"(s[13]), "=f"(s[14]), "=f"(s[15]),
          "=f"(s[16]), "=f"(s[17]), "=f"(s[18]), "=f"(s[19]), "=f"(s[20]), "=f"(s[21]), "=f"(s[22]), "=f"(s[23]),
          "=f"(s[24]), "=f"(s[25]), "=f"(s[26]), "=f"(s[27]), "=f"(s[28]), "=f"(s[29]), "=f"(s[30]), "=f"(s[31])
        : "r"(q[0]), "r"(q[1]), "r"(q[2]), "r"(q[3]), "l"(db));
}
__device__ __forceinline__ void pv24(float (&o)[12], uint32_t a0, uint32_t a1, uint32_t a2, uint32_t a3, uint64_t db) {
    asm volatile("wgmma.mma_async.sync.aligned.m64n24k16.f32.bf16.bf16 "
        "{%0,%1,%2,%3,%4,%5,%6,%7,%8,%9,%10,%11}, {%12,%13,%14,%15}, %16, 1, 1, 1, 1;"
        : "+f"(o[0]), "+f"(o[1]), "+f"(o[2]), "+f"(o[3]), "+f"(o[4]), "+f"(o[5]), "+f"(o[6]), "+f"(o[7]),
          "+f"(o[8]), "+f"(o[9]), "+f"(o[10]), "+f"(o[11])
        : "r"(a0), "r"(a1), "r"(a2), "r"(a3), "l"(db));
}

__device__ __forceinline__ void attn_safe(float (&o)[12], const uint32_t (&q)[4], uint64_t kdesc0, uint64_t vdesc0) {
    float s[32];
    float m0 = -INFINITY, m1 = -INFINITY;
#pragma unroll
    for (int i = 0; i < 12; i++) o[i] = 0.f;
#pragma unroll 1
    for (int j = 0; j < 32; j++) {
        WG_FENCE();
        qk64(s, q, kdesc0 + (uint64_t)(j * 64));
        WG_COMMIT(); WG_WAIT(0);
        float n0 = m0, n1 = m1;
#pragma unroll
        for (int i = 0; i < 8; i++) { n0 = fmaxf(n0, fmaxf(s[4 * i], s[4 * i + 1])); n1 = fmaxf(n1, fmaxf(s[4 * i + 2], s[4 * i + 3])); }
        n0 = fmaxf(n0, __shfl_xor_sync(~0u, n0, 1)); n0 = fmaxf(n0, __shfl_xor_sync(~0u, n0, 2));
        n1 = fmaxf(n1, __shfl_xor_sync(~0u, n1, 1)); n1 = fmaxf(n1, __shfl_xor_sync(~0u, n1, 2));
        const float c0 = ex2(m0 - n0), c1 = ex2(m1 - n1);
        m0 = n0; m1 = n1;
#pragma unroll
        for (int i = 0; i < 3; i++) { o[4 * i] *= c0; o[4 * i + 1] *= c0; o[4 * i + 2] *= c1; o[4 * i + 3] *= c1; }
        uint32_t p[16];
#pragma unroll
        for (int i = 0; i < 8; i++) {
            p[2 * i] = packbf(ex2(s[4 * i] - m0), ex2(s[4 * i + 1] - m0));
            p[2 * i + 1] = packbf(ex2(s[4 * i + 2] - m1), ex2(s[4 * i + 3] - m1));
        }
        WG_FENCE();
#pragma unroll
        for (int kk = 0; kk < 4; kk++) pv24(o, p[4 * kk], p[4 * kk + 1], p[4 * kk + 2], p[4 * kk + 3], vdesc0 + (uint64_t)(j * 64 + kk * 16));
        WG_COMMIT(); WG_WAIT(0);
    }
}

__device__ __forceinline__ void attn_store(const float (&o)[12], int head, int m64, int warp, int lane) {
    const int g = lane >> 2, t = lane & 3;
    const int row = m64 * 64 + warp * 16 + g;
    const float i0 = 1.f / o[8], i1 = 1.f / o[10];
    uint32_t* p0 = reinterpret_cast<uint32_t*>(g_o + (size_t)row * DM + head * 16 + t * 2);
    uint32_t* p1 = reinterpret_cast<uint32_t*>(g_o + (size_t)(row + 8) * DM + head * 16 + t * 2);
    p0[0] = packbf(o[0] * i0, o[1] * i0); p0[4] = packbf(o[4] * i0, o[5] * i0);
    p1[0] = packbf(o[2] * i1, o[3] * i1); p1[4] = packbf(o[6] * i1, o[7] * i1);
}

__device__ void ffn_block(int c, uint8_t* smem, const __nv_bfloat16* __restrict__ wg, const __nv_bfloat16* __restrict__ wu,
                          const __nv_bfloat16* __restrict__ wd) {
    const int tid = threadIdx.x, warp = tid >> 5, lane = tid & 31;
    float* sx = reinterpret_cast<float*>(smem);
    float* sh = sx + 1024;
    float* red = sh + 1024;
    __shared__ float tv[32]; __shared__ int ti[32];
    __shared__ int ssel[2];
    float b1 = -INFINITY, b2 = -INFINITY; int i1 = 0x7fffffff, i2 = 0x7fffffff;
    auto push = [&](float v, int i) {
        if (v > b1 || (v == b1 && i < i1)) { b2 = b1; i2 = i1; b1 = v; i1 = i; }
        else if (v > b2 || (v == b2 && i < i2)) { b2 = v; i2 = i; }
    };
    for (int i = tid; i < S_LEN; i += 512) push(g_r[i], i);
#pragma unroll
    for (int o = 16; o > 0; o >>= 1) {
        float v1 = __shfl_xor_sync(~0u, b1, o), v2 = __shfl_xor_sync(~0u, b2, o);
        int j1 = __shfl_xor_sync(~0u, i1, o), j2 = __shfl_xor_sync(~0u, i2, o);
        push(v1, j1); push(v2, j2);
    }
    if (lane == 0) { tv[2 * warp] = b1; ti[2 * warp] = i1; tv[2 * warp + 1] = b2; ti[2 * warp + 1] = i2; }
    __syncthreads();
    if (warp == 0) {
        b1 = tv[lane]; i1 = ti[lane]; b2 = -INFINITY; i2 = 0x7fffffff;
#pragma unroll
        for (int o = 16; o > 0; o >>= 1) {
            float v1 = __shfl_xor_sync(~0u, b1, o), v2 = __shfl_xor_sync(~0u, b2, o);
            int j1 = __shfl_xor_sync(~0u, i1, o), j2 = __shfl_xor_sync(~0u, i2, o);
            push(v1, j1); push(v2, j2);
        }
        if (lane == 0) {
            i1 = min(max(i1, 0), S_LEN - 1); i2 = min(max(i2, 0), S_LEN - 1);
            ssel[0] = i1; ssel[1] = i2;
            if (c == 0) {
                g_sel[0] = i1; g_sel[1] = i2;
                g_gate[0] = bfr(1.f / (1.f + __expf(-bfr(b1))));
                g_gate[1] = bfr(1.f / (1.f + __expf(-bfr(b2))));
            }
        }
    }
    __syncthreads();
    for (int i = tid; i < 1024; i += 512) sx[i] = __bfloat162float(g_xn[(size_t)ssel[i >> 9] * DM + (i & 511)]);
    __syncthreads();
    {
        const int ch = tid % 56, kg = tid / 56;
        float ag[2][8], au[2][8];
#pragma unroll
        for (int j = 0; j < 8; j++) { ag[0][j] = ag[1][j] = au[0][j] = au[1][j] = 0.f; }
        if (kg < 9) {
            const uint4* pg = reinterpret_cast<const uint4*>(wg + c * 448 + ch * 8);
            const uint4* pu = reinterpret_cast<const uint4*>(wu + c * 448 + ch * 8);
#pragma unroll 4
            for (int k = kg; k < DM; k += 9) {
                const uint4 vg = __ldg(pg + (size_t)k * (FF / 8)), vu = __ldg(pu + (size_t)k * (FF / 8));
                const float x0 = sx[k], x1 = sx[512 + k];
                const uint32_t gw[4] = {vg.x, vg.y, vg.z, vg.w}, uw[4] = {vu.x, vu.y, vu.z, vu.w};
#pragma unroll
                for (int j = 0; j < 4; j++) {
                    const float g0 = bf_lo(gw[j]), g1 = bf_hi(gw[j]), u0 = bf_lo(uw[j]), u1 = bf_hi(uw[j]);
                    ag[0][2 * j] = fmaf(x0, g0, ag[0][2 * j]); ag[0][2 * j + 1] = fmaf(x0, g1, ag[0][2 * j + 1]);
                    ag[1][2 * j] = fmaf(x1, g0, ag[1][2 * j]); ag[1][2 * j + 1] = fmaf(x1, g1, ag[1][2 * j + 1]);
                    au[0][2 * j] = fmaf(x0, u0, au[0][2 * j]); au[0][2 * j + 1] = fmaf(x0, u1, au[0][2 * j + 1]);
                    au[1][2 * j] = fmaf(x1, u0, au[1][2 * j]); au[1][2 * j + 1] = fmaf(x1, u1, au[1][2 * j + 1]);
                }
            }
#pragma unroll
            for (int j = 0; j < 8; j++) {
                red[(kg * 4 + 0) * 448 + ch * 8 + j] = ag[0][j]; red[(kg * 4 + 1) * 448 + ch * 8 + j] = ag[1][j];
                red[(kg * 4 + 2) * 448 + ch * 8 + j] = au[0][j]; red[(kg * 4 + 3) * 448 + ch * 8 + j] = au[1][j];
            }
        }
        __syncthreads();
        for (int i = tid; i < 896; i += 512) {
            const int tok = i / 448, col = i % 448;
            float gs = 0.f, us = 0.f;
#pragma unroll
            for (int q = 0; q < 9; q++) { gs += red[(q * 4 + tok) * 448 + col]; us += red[(q * 4 + 2 + tok) * 448 + col]; }
            gs = bfr(gs); us = bfr(us);
            const float sg = bfr(gs / (1.f + __expf(-gs)));
            sh[tok * 448 + col] = bfr(sg * us);
        }
        __syncthreads();
    }
    {
        const int ch = tid & 63, kg = tid >> 6;
        float a[2][8];
#pragma unroll
        for (int j = 0; j < 8; j++) a[0][j] = a[1][j] = 0.f;
        const uint4* pd = reinterpret_cast<const uint4*>(wd + (size_t)c * 448 * DM + ch * 8);
#pragma unroll 8
        for (int k = kg; k < 448; k += 8) {
            const uint4 v = __ldg(pd + (size_t)k * (DM / 8));
            const float h0 = sh[k], h1 = sh[448 + k];
            const uint32_t w[4] = {v.x, v.y, v.z, v.w};
#pragma unroll
            for (int j = 0; j < 4; j++) {
                const float w0 = bf_lo(w[j]), w1 = bf_hi(w[j]);
                a[0][2 * j] = fmaf(h0, w0, a[0][2 * j]); a[0][2 * j + 1] = fmaf(h0, w1, a[0][2 * j + 1]);
                a[1][2 * j] = fmaf(h1, w0, a[1][2 * j]); a[1][2 * j + 1] = fmaf(h1, w1, a[1][2 * j + 1]);
            }
        }
#pragma unroll
        for (int j = 0; j < 8; j++) { red[(kg * 2 + 0) * 512 + ch * 8 + j] = a[0][j]; red[(kg * 2 + 1) * 512 + ch * 8 + j] = a[1][j]; }
        __syncthreads();
        for (int i = tid; i < 1024; i += 512) {
            float s = 0.f;
#pragma unroll
            for (int q = 0; q < 8; q++) s += red[q * 1024 + i];
            g_ypart[c * 1024 + i] = s;
        }
    }
}

__global__ void __launch_bounds__(512, 1) attn_kernel(const __nv_bfloat16* __restrict__ wg_, const __nv_bfloat16* __restrict__ wu_,
                                                      const __nv_bfloat16* __restrict__ wd_, float sc) {
    extern __shared__ uint8_t smem_raw[];
    const uint32_t sraw = smem_u32(smem_raw);
    const uint32_t sbase = (sraw + 1023u) & ~1023u;
    uint8_t* sptr = smem_raw + (sbase - sraw);
    if (blockIdx.x >= 128) {
        pdl_wait();
        pdl_launch();
        ffn_block(blockIdx.x - 128, sptr, wg_, wu_, wd_);
        return;
    }
    const uint32_t bars = sbase + 163840;
    const int head = blockIdx.x >> 2, quarter = blockIdx.x & 3;
    const int wg = threadIdx.x >> 7, warp = (threadIdx.x >> 5) & 3, lane = threadIdx.x & 31;
    if (threadIdx.x == 0) {
        for (int c = 0; c < 8; c++) mbar_init(bars + 8 * c, 1);
        fence_barrier_init();
    }
    {
        uint4* ones = reinterpret_cast<uint4*>(sptr + 131072);
        for (int i = threadIdx.x; i < 2048; i += 512) ones[i] = make_uint4(0x3f803f80u, 0x3f803f80u, 0x3f803f80u, 0x3f803f80u);
        fence_proxy_async();
    }
    __syncthreads();
    pdl_wait();
    pdl_launch();
    if (threadIdx.x == 0) {
        const uint8_t* kp = reinterpret_cast<const uint8_t*>(g_k + head * 4096);
        const uint8_t* vp = reinterpret_cast<const uint8_t*>(g_v + head * 4096);
        for (int c = 0; c < 8; c++) {
            mbar_expect_tx(bars + 8 * c, 16384);
            bulk_g2s(sbase + c * 4096, kp + c * 4096, 4096, bars + 8 * c);
            bulk_g2s(sbase + 32768 + c * 4096, kp + 32768 + c * 4096, 4096, bars + 8 * c);
            bulk_g2s(sbase + 65536 + c * 4096, vp + c * 4096, 4096, bars + 8 * c);
            bulk_g2s(sbase + 98304 + c * 4096, vp + 32768 + c * 4096, 4096, bars + 8 * c);
        }
    }
    const uint64_t kdesc0 = mkdesc(sbase, 32768, 128, 0);
    const uint64_t vdesc0 = mkdesc(sbase + 65536, 128, 32768, 0);
    uint32_t badmask = 0;
#pragma unroll 1
    for (int mt = 0; mt < 2; mt++) {
        const int m64 = quarter * 8 + mt * 4 + wg;
        uint32_t q[4];
        { const uint4 qq = g_q[(head * 128 + m64 * 4 + warp) * 32 + lane]; q[0] = qq.x; q[1] = qq.y; q[2] = qq.z; q[3] = qq.w; }
        float s[32], s2[32], o[12];
#pragma unroll
        for (int i = 0; i < 12; i++) o[i] = 0.f;
        mbar_wait(bars, 0);
        WG_FENCE();
        qk64(s, q, kdesc0);
        WG_COMMIT(); WG_WAIT(0);
        float mx0 = -INFINITY, mx1 = -INFINITY;
#pragma unroll
        for (int i = 0; i < 8; i++) { mx0 = fmaxf(mx0, fmaxf(s[4 * i], s[4 * i + 1])); mx1 = fmaxf(mx1, fmaxf(s[4 * i + 2], s[4 * i + 3])); }
        mx0 = fmaxf(mx0, __shfl_xor_sync(~0u, mx0, 1)); mx0 = fmaxf(mx0, __shfl_xor_sync(~0u, mx0, 2));
        mx1 = fmaxf(mx1, __shfl_xor_sync(~0u, mx1, 1)); mx1 = fmaxf(mx1, __shfl_xor_sync(~0u, mx1, 2));
        float cm0 = -(ceilf(mx0) + SHIFT), cm1 = -(ceilf(mx1) + SHIFT);
        float cp0 = (cm0 + 127.f) * sc, cp1 = (cm1 + 127.f) * sc;
        asm volatile("" : "+f"(cm0), "+f"(cm1), "+f"(cp0), "+f"(cp1));
        uint64_t kd = kdesc0, vd = vdesc0;
        auto step = [&](float (&sc_)[32], float (&sn)[32]) {
            kd += 64;
            WG_FENCE();
            qk64(sn, q, kd);
            WG_COMMIT();
#pragma unroll
            for (int kk = 0; kk < 4; kk++) {
                const int i0 = kk * 2, i1 = kk * 2 + 1;
                const uint32_t p0 = packbf(ex2(sc_[4 * i0] + cm0), ex2(sc_[4 * i0 + 1] + cm0));
                const uint32_t p1 = packbf(ex2(sc_[4 * i0 + 2] + cm1), ex2(sc_[4 * i0 + 3] + cm1));
                const uint32_t p2 = polyexp(fmaf(sc_[4 * i1], sc, cp0), fmaf(sc_[4 * i1 + 1], sc, cp0));
                const uint32_t p3 = polyexp(fmaf(sc_[4 * i1 + 2], sc, cp1), fmaf(sc_[4 * i1 + 3], sc, cp1));
                WG_FENCE();
                pv24(o, p0, p1, p2, p3, vd);
                vd += 16;
            }
            WG_COMMIT();
            WG_WAIT(1);
        };
#pragma unroll 1
        for (int c = 0; c < 16; c++) {
            if (mt == 0 && (c & 1) == 0 && c < 14) mbar_wait(bars + 4 * c + 8, 0);
            step(s, s2); step(s2, s);
        }
        WG_WAIT(0);
        bool bad = !(o[8] > 0.f) || !(o[10] > 0.f);
#pragma unroll
        for (int i = 0; i < 12; i++) bad = bad || !(fabsf(o[i]) <= 3.0e38f);
        uint32_t anybad;
        asm volatile("{\n.reg .pred p, q;\nsetp.ne.u32 p, %1, 0;\nbarrier.cta.red.or.pred q, %2, 128, p;\nselp.u32 %0, 1, 0, q;\n}"
                     : "=r"(anybad) : "r"((uint32_t)bad), "r"(wg + 1) : "memory");
        badmask |= anybad << mt;
        attn_store(o, head, m64, warp, lane);
    }
#pragma unroll 1
    for (int mt = 0; mt < 2; mt++) {
        if (!((badmask >> mt) & 1)) continue;
        const int m64 = quarter * 8 + mt * 4 + wg;
        uint32_t q[4];
        { const uint4 qq = g_q[(head * 128 + m64 * 4 + warp) * 32 + lane]; q[0] = qq.x; q[1] = qq.y; q[2] = qq.z; q[3] = qq.w; }
        float o[12];
        attn_safe(o, q, mkdesc(sbase, 32768, 128, 0), mkdesc(sbase + 65536, 128, 32768, 0));
        attn_store(o, head, m64, warp, lane);
    }
}

constexpr int K3_SMEM = 8 * 8192 + 8 * 16384 + 1024 + 128;

__device__ __forceinline__ void wgmma_n64(float (&d)[32], uint64_t da, uint64_t db, int scale_d) {
    asm volatile("{\n.reg .pred p;\nsetp.ne.b32 p, %34, 0;\n"
        "wgmma.mma_async.sync.aligned.m64n64k16.f32.bf16.bf16 "
        "{%0,%1,%2,%3,%4,%5,%6,%7,%8,%9,%10,%11,%12,%13,%14,%15,%16,%17,%18,%19,%20,%21,%22,%23,%24,%25,%26,%27,%28,%29,%30,%31}, "
        "%32, %33, p, 1, 1, 0, 1;\n}"
        : "+f"(d[0]), "+f"(d[1]), "+f"(d[2]), "+f"(d[3]), "+f"(d[4]), "+f"(d[5]), "+f"(d[6]), "+f"(d[7]),
          "+f"(d[8]), "+f"(d[9]), "+f"(d[10]), "+f"(d[11]), "+f"(d[12]), "+f"(d[13]), "+f"(d[14]), "+f"(d[15]),
          "+f"(d[16]), "+f"(d[17]), "+f"(d[18]), "+f"(d[19]), "+f"(d[20]), "+f"(d[21]), "+f"(d[22]), "+f"(d[23]),
          "+f"(d[24]), "+f"(d[25]), "+f"(d[26]), "+f"(d[27]), "+f"(d[28]), "+f"(d[29]), "+f"(d[30]), "+f"(d[31])
        : "l"(da), "l"(db), "r"(scale_d));
}

__global__ void __launch_bounds__(256, 1) oproj_kernel(const __grid_constant__ CUtensorMap mapA, const __grid_constant__ CUtensorMap mapB,
                                                       const __nv_bfloat16* __restrict__ x, __nv_bfloat16* __restrict__ out) {
    extern __shared__ uint8_t smem_raw[];
    const uint32_t sbase = (smem_u32(smem_raw) + 1023u) & ~1023u;
    const uint32_t sA = sbase, sB = sbase + 8 * 8192, bars = sbase + 8 * 8192 + 8 * 16384;
    const int warp = threadIdx.x >> 5, lane = threadIdx.x & 31, wg = warp >> 2;
    const int nb = blockIdx.x & 3, mb = blockIdx.x >> 2;
    if (threadIdx.x == 0) {
        for (int c = 0; c < 8; c++) mbar_init(bars + 8 * c, 1);
        fence_barrier_init();
        for (int c = 0; c < 8; c++) {
            mbar_expect_tx(bars + 8 * c, 8192 + 16384);
            tma2d(sB + c * 16384, &mapB, bars + 8 * c, nb * 128, c * 64);
            tma2d(sB + c * 16384 + 8192, &mapB, bars + 8 * c, nb * 128 + 64, c * 64);
        }
    }
    const int g = lane >> 2, t = lane & 3;
    const int row0 = mb * 64 + (warp & 3) * 16 + g;
    const int col0 = nb * 128 + wg * 64 + t * 2;
    uint32_t xv[16], nv[16];
#pragma unroll
    for (int i = 0; i < 8; i++) {
        xv[2 * i] = *reinterpret_cast<const uint32_t*>(x + (size_t)row0 * DM + col0 + i * 8);
        xv[2 * i + 1] = *reinterpret_cast<const uint32_t*>(x + (size_t)(row0 + 8) * DM + col0 + i * 8);
        nv[2 * i] = *reinterpret_cast<const uint32_t*>(g_xn + (size_t)row0 * DM + col0 + i * 8);
        nv[2 * i + 1] = *reinterpret_cast<const uint32_t*>(g_xn + (size_t)(row0 + 8) * DM + col0 + i * 8);
    }
    __syncthreads();
    pdl_wait();
    if (threadIdx.x == 0) {
        for (int c = 0; c < 8; c++) tma2d(sA + c * 8192, &mapA, bars + 8 * c, c * 64, mb * 64);
    }
    float acc[32];
#pragma unroll
    for (int i = 0; i < 32; i++) acc[i] = 0.f;
#pragma unroll 1
    for (int c = 0; c < 8; c++) {
        mbar_wait(bars + 8 * c, 0);
        const uint64_t da = mkdesc(sA + c * 8192, 16, 1024, 1);
        const uint64_t db = mkdesc(sB + c * 16384 + wg * 8192, 8192, 1024, 1);
        WG_FENCE();
#pragma unroll
        for (int k = 0; k < 4; k++) wgmma_n64(acc, da + k * 2, db + k * 128, (c | k) != 0);
        WG_COMMIT();
    }
    const int sel0 = g_sel[0], sel1 = g_sel[1];
    WG_WAIT(0);
#pragma unroll
    for (int h = 0; h < 2; h++) {
        const int row = row0 + h * 8;
        const int which = row == sel0 ? 0 : (row == sel1 ? 1 : -1);
#pragma unroll
        for (int i = 0; i < 8; i++) {
            const int col = col0 + i * 8;
            float b0 = bf_lo(nv[2 * i + h]), b1 = bf_hi(nv[2 * i + h]);
            if (which >= 0) {
                float y0 = 0.f, y1 = 0.f;
#pragma unroll
                for (int c = 0; c < 4; c++) { y0 += g_ypart[c * 1024 + which * 512 + col]; y1 += g_ypart[c * 1024 + which * 512 + col + 1]; }
                const float gt = g_gate[which];
                b0 = bfr(b0 + bfr(bfr(y0) * gt)); b1 = bfr(b1 + bfr(bfr(y1) * gt));
            }
            const float t0 = bfr(bf_lo(xv[2 * i + h]) + bfr(acc[4 * i + 2 * h]));
            const float t1 = bfr(bf_hi(xv[2 * i + h]) + bfr(acc[4 * i + 2 * h + 1]));
            *reinterpret_cast<uint32_t*>(out + (size_t)row * DM + col) = packbf(t0 + b0, t1 + b1);
        }
    }
}

typedef CUresult (*EncodeFn)(CUtensorMap*, CUtensorMapDataType, cuuint32_t, void*, const cuuint64_t*, const cuuint64_t*,
                             const cuuint32_t*, const cuuint32_t*, CUtensorMapInterleave, CUtensorMapSwizzle,
                             CUtensorMapL2promotion, CUtensorMapFloatOOBfill);

void make_map(EncodeFn fn, CUtensorMap* m, const void* ptr, uint64_t inner, uint64_t outer, uint32_t box_inner, uint32_t box_outer) {
    cuuint64_t dims[2] = {inner, outer};
    cuuint64_t strides[1] = {inner * 2};
    cuuint32_t box[2] = {box_inner, box_outer};
    cuuint32_t es[2] = {1, 1};
    fn(m, CU_TENSOR_MAP_DATA_TYPE_BFLOAT16, 2, const_cast<void*>(ptr), dims, strides, box, es, CU_TENSOR_MAP_INTERLEAVE_NONE,
       CU_TENSOR_MAP_SWIZZLE_128B, CU_TENSOR_MAP_L2_PROMOTION_L2_256B, CU_TENSOR_MAP_FLOAT_OOB_FILL_NONE);
}

template <typename... KArgs, typename... Args>
void launch(void (*kern)(KArgs...), int grid, int block, int smem, bool pdl, Args... args) {
    cudaLaunchConfig_t cfg = {};
    cfg.gridDim = dim3(grid); cfg.blockDim = dim3(block); cfg.dynamicSmemBytes = smem; cfg.stream = cudaStreamPerThread;
    cudaLaunchAttribute at[1];
    at[0].id = cudaLaunchAttributeProgrammaticStreamSerialization;
    at[0].val.programmaticStreamSerializationAllowed = 1;
    cfg.attrs = at; cfg.numAttrs = pdl ? 1 : 0;
    cudaLaunchKernelEx(&cfg, kern, KArgs(args)...);
}

}

extern "C" void kernel_launch(void* const* d_in, const int* in_sizes, int n_in, void* d_out, int out_size) {
    const __nv_bfloat16* x = (const __nv_bfloat16*)d_in[0];
    const __nv_bfloat16* wqkv = (const __nv_bfloat16*)d_in[1];
    const __nv_bfloat16* wo = (const __nv_bfloat16*)d_in[2];
    const __nv_bfloat16* wr = (const __nv_bfloat16*)d_in[4];
    const __nv_bfloat16* wgate = (const __nv_bfloat16*)d_in[5];
    const __nv_bfloat16* wup = (const __nv_bfloat16*)d_in[6];
    const __nv_bfloat16* wdown = (const __nv_bfloat16*)d_in[7];
    __nv_bfloat16* out = (__nv_bfloat16*)d_out;

    static EncodeFn enc = nullptr;
    static void* p_xn = nullptr; static void* p_o = nullptr;
    if (!enc) {
        void* fn = nullptr; cudaDriverEntryPointQueryResult qr;
        cudaGetDriverEntryPoint("cuTensorMapEncodeTiled", &fn, cudaEnableDefault, &qr);
        enc = (EncodeFn)fn;
        cudaGetSymbolAddress(&p_xn, g_xn);
        cudaGetSymbolAddress(&p_o, g_o);
        cudaFuncSetAttribute(qkv_kernel, cudaFuncAttributeMaxDynamicSharedMemorySize, K1_SMEM);
        cudaFuncSetAttribute(attn_kernel, cudaFuncAttributeMaxDynamicSharedMemorySize, K2_SMEM);
        cudaFuncSetAttribute(oproj_kernel, cudaFuncAttributeMaxDynamicSharedMemorySize, K3_SMEM);
    }
    CUtensorMap mXn, mWqkv, mO, mWo;
    make_map(enc, &mXn, p_xn, DM, S_LEN, 64, 128);
    make_map(enc, &mWqkv, wqkv, 3 * DM, DM, 64, 64);
    make_map(enc, &mO, p_o, DM, S_LEN, 64, 64);
    make_map(enc, &mWo, wo, DM, DM, 64, 64);

    const float sc = 1.7936620522e-43f;
    (void)sc;
    union { uint32_t u; float f; } scu; scu.u = 128u;

    launch(ln_kernel, S_LEN / 8, 256, 0, false, x, wr);
    launch(qkv_kernel, 128, 288, K1_SMEM, true, mXn, mWqkv);
    launch(attn_kernel, 132, 512, K2_SMEM, true, wgate, wup, wdown, scu.f);
    launch(oproj_kernel, 128, 256, K3_SMEM, true, mO, mWo, x, out);
}
```

```cpp
#include <cuda_runtime.h>
#include <cuda_bf16.h>
#include <cuda.h>
#include <stdint.h>
#include <type_traits>

namespace {

constexpr int S_LEN = 2048;
constexpr int DM = 512;
constexpr int NH = 32;
constexpr int FF = 1792;

__device__ __align__(1024) __nv_bfloat16 g_xn[S_LEN * DM];
__device__ float g_r[S_LEN];
__device__ __align__(1024) uint4 g_q[NH * 128 * 32];
__device__ __align__(1024) uint4 g_k[NH * 4096];
__device__ __align__(1024) uint4 g_v[NH * 4096];
__device__ __align__(1024) __nv_bfloat16 g_o[S_LEN * DM];
__device__ float g_ypart[4 * 2 * DM];
__device__ int g_sel[2];
__device__ float g_gate[2];

#define TL(k, slot) do {} while (0)

__device__ __forceinline__ uint32_t smem_u32(const void* p) { return (uint32_t)__cvta_generic_to_shared(p); }
__device__ __forceinline__ void pdl_wait() { asm volatile("griddepcontrol.wait;" ::: "memory"); }
__device__ __forceinline__ void pdl_launch() { asm volatile("griddepcontrol.launch_dependents;" ::: "memory"); }
__device__ __forceinline__ void mbar_init(uint32_t bar, uint32_t cnt) {
    asm volatile("mbarrier.init.shared::cta.b64 [%0], %1;" :: "r"(bar), "r"(cnt) : "memory");
}
__device__ __forceinline__ void mbar_expect_tx(uint32_t bar, uint32_t bytes) {
    asm volatile("mbarrier.arrive.expect_tx.shared::cta.b64 _, [%0], %1;" :: "r"(bar), "r"(bytes) : "memory");
}
__device__ __forceinline__ void mbar_arrive(uint32_t bar) {
    asm volatile("mbarrier.arrive.shared::cta.b64 _, [%0];" :: "r"(bar) : "memory");
}
__device__ __forceinline__ void mbar_wait(uint32_t bar, uint32_t parity) {
    asm volatile("{\n.reg .pred p;\n.reg .u32 n;\nmov.u32 n, 0;\n"
                 "WAIT_%=:\n"
                 "mbarrier.try_wait.parity.shared::cta.b64 p, [%0], %1;\n"
                 "@p bra DONE_%=;\n"
                 "add.u32 n, n, 1;\n"
                 "setp.lt.u32 p, n, 4000000;\n"
                 "@p bra WAIT_%=;\n"
                 "trap;\n"
                 "DONE_%=:\n}"
                 :: "r"(bar), "r"(parity) : "memory");
}
__device__ __forceinline__ void fence_barrier_init() { asm volatile("fence.mbarrier_init.release.cluster;" ::: "memory"); }
__device__ __forceinline__ void fence_proxy_async() { asm volatile("fence.proxy.async.shared::cta;" ::: "memory"); }
__device__ __forceinline__ void tma2d(uint32_t dst, const CUtensorMap* map, uint32_t bar, int c0, int c1) {
    asm volatile("cp.async.bulk.tensor.2d.shared::cluster.global.mbarrier::complete_tx::bytes [%0], [%1, {%3, %4}], [%2];"
                 :: "r"(dst), "l"((uint64_t)map), "r"(bar), "r"(c0), "r"(c1) : "memory");
}
__device__ __forceinline__ void bulk_g2s(uint32_t dst, const void* src, uint32_t bytes, uint32_t bar) {
    asm volatile("cp.async.bulk.shared::cluster.global.mbarrier::complete_tx::bytes [%0], [%1], %2, [%3];"
                 :: "r"(dst), "l"((uint64_t)src), "r"(bytes), "r"(bar) : "memory");
}
__device__ __forceinline__ uint64_t mkdesc(uint32_t addr, uint32_t lbo, uint32_t sbo, uint32_t swz) {
    return (uint64_t)((addr & 0x3FFFF) >> 4) | ((uint64_t)(lbo >> 4) << 16) | ((uint64_t)(sbo >> 4) << 32) | ((uint64_t)swz << 62);
}
#define WG_FENCE() asm volatile("wgmma.fence.sync.aligned;" ::: "memory")
#define WG_COMMIT() asm volatile("wgmma.commit_group.sync.aligned;" ::: "memory")
#define WG_WAIT(n) asm volatile("wgmma.wait_group.sync.aligned %0;" :: "n"(n) : "memory")

__device__ __forceinline__ float ex2(float x) { float y; asm("ex2.approx.ftz.f32 %0, %1;" : "=f"(y) : "f"(x)); return y; }
__device__ __forceinline__ uint32_t packbf(float lo, float hi) {
    uint32_t r; asm("cvt.rn.bf16x2.f32 %0, %1, %2;" : "=r"(r) : "f"(hi), "f"(lo)); return r;
}
__device__ __forceinline__ float bf_lo(uint32_t v) { return __uint_as_float(v << 16); }
__device__ __forceinline__ float bf_hi(uint32_t v) { return __uint_as_float(v & 0xffff0000u); }
__device__ __forceinline__ float bfr(float x) { return __bfloat162float(__float2bfloat16_rn(x)); }

__global__ void __launch_bounds__(256) ln_kernel(const __nv_bfloat16* __restrict__ x, const __nv_bfloat16* __restrict__ wr) {
    TL(0, 0);
    pdl_launch();
    const int warp = threadIdx.x >> 5, lane = threadIdx.x & 31;
    const int row = blockIdx.x * 8 + warp;
    const uint4* xr = reinterpret_cast<const uint4*>(x + (size_t)row * DM);
    uint4 a = xr[lane], b = xr[32 + lane];
    const uint4* wp = reinterpret_cast<const uint4*>(wr);
    uint4 wa = wp[lane], wb = wp[32 + lane];
    uint32_t u[8] = {a.x, a.y, a.z, a.w, b.x, b.y, b.z, b.w};
    uint32_t w[8] = {wa.x, wa.y, wa.z, wa.w, wb.x, wb.y, wb.z, wb.w};
    float f[16];
    float sum = 0.f;
#pragma unroll
    for (int i = 0; i < 8; i++) { f[2 * i] = bf_lo(u[i]); f[2 * i + 1] = bf_hi(u[i]); sum += f[2 * i] + f[2 * i + 1]; }
#pragma unroll
    for (int o = 16; o > 0; o >>= 1) sum += __shfl_xor_sync(~0u, sum, o);
    const float mean = sum * (1.f / DM);
    float sq = 0.f;
#pragma unroll
    for (int i = 0; i < 16; i++) { float d = f[i] - mean; sq = fmaf(d, d, sq); }
#pragma unroll
    for (int o = 16; o > 0; o >>= 1) sq += __shfl_xor_sync(~0u, sq, o);
    const float mb = bfr(mean);
    const float vb = bfr(sq * (1.f / DM));
    const float den = bfr(sqrtf(bfr(vb + 1e-5f)));
    const float rinv = 1.f / den;
    uint32_t o[8];
    float r = 0.f;
#pragma unroll
    for (int i = 0; i < 8; i++) {
        float d0 = bfr(f[2 * i] - mb), d1 = bfr(f[2 * i + 1] - mb);
        o[i] = packbf(d0 * rinv, d1 * rinv);
        r = fmaf(bf_lo(o[i]), bf_lo(w[i]), r);
        r = fmaf(bf_hi(o[i]), bf_hi(w[i]), r);
    }
#pragma unroll
    for (int of = 16; of > 0; of >>= 1) r += __shfl_xor_sync(~0u, r, of);
    uint4* xo = reinterpret_cast<uint4*>(g_xn + (size_t)row * DM);
    xo[lane] = make_uint4(o[0], o[1], o[2], o[3]);
    xo[32 + lane] = make_uint4(o[4], o[5], o[6], o[7]);
    if (lane == 0) g_r[row] = r;
    TL(0, 3);
}

constexpr int K1_ST = 5;
constexpr int K1_STAGE = 16384 + 24576;
constexpr int K1_SMEM = K1_ST * K1_STAGE + 1024 + 128;

__device__ __forceinline__ void wgmma_n192(float (&d)[96], uint64_t da, uint64_t db, int scale_d) {
    asm volatile("{\n.reg .pred p;\nsetp.ne.b32 p, %98, 0;\n"
        "wgmma.mma_async.sync.aligned.m64n192k16.f32.bf16.bf16 "
        "{%0,%1,%2,%3,%4,%5,%6,%7,%8,%9,%10,%11,%12,%13,%14,%15,%16,%17,%18,%19,%20,%21,%22,%23,"
        "%24,%25,%26,%27,%28,%29,%30,%31,%32,%33,%34,%35,%36,%37,%38,%39,%40,%41,%42,%43,%44,%45,%46,%47,"
        "%48,%49,%50,%51,%52,%53,%54,%55,%56,%57,%58,%59,%60,%61,%62,%63,%64,%65,%66,%67,%68,%69,%70,%71,"
        "%72,%73,%74,%75,%76,%77,%78,%79,%80,%81,%82,%83,%84,%85,%86,%87,%88,%89,%90,%91,%92,%93,%94,%95}, "
        "%96, %97, p, 1, 1, 0, 1;\n}"
        : "+f"(d[0]), "+f"(d[1]), "+f"(d[2]), "+f"(d[3]), "+f"(d[4]), "+f"(d[5]), "+f"(d[6]), "+f"(d[7]),
          "+f"(d[8]), "+f"(d[9]), "+f"(d[10]), "+f"(d[11]), "+f"(d[12]), "+f"(d[13]), "+f"(d[14]), "+f"(d[15]),
          "+f"(d[16]), "+f"(d[17]), "+f"(d[18]), "+f"(d[19]), "+f"(d[20]), "+f"(d[21]), "+f"(d[22]), "+f"(d[23]),
          "+f"(d[24]), "+f"(d[25]), "+f"(d[26]), "+f"(d[27]), "+f"(d[28]), "+f"(d[29]), "+f"(d[30]), "+f"(d[31]),
          "+f"(d[32]), "+f"(d[33]), "+f"(d[34]), "+f"(d[35]), "+f"(d[36]), "+f"(d[37]), "+f"(d[38]), "+f"(d[39]),
          "+f"(d[40]), "+f"(d[41]), "+f"(d[42]), "+f"(d[43]), "+f"(d[44]), "+f"(d[45]), "+f"(d[46]), "+f"(d[47]),
          "+f"(d[48]), "+f"(d[49]), "+f"(d[50]), "+f"(d[51]), "+f"(d[52]), "+f"(d[53]), "+f"(d[54]), "+f"(d[55]),
          "+f"(d[56]), "+f"(d[57]), "+f"(d[58]), "+f"(d[59]), "+f"(d[60]), "+f"(d[61]), "+f"(d[62]), "+f"(d[63]),
          "+f"(d[64]), "+f"(d[65]), "+f"(d[66]), "+f"(d[67]), "+f"(d[68]), "+f"(d[69]), "+f"(d[70]), "+f"(d[71]),
          "+f"(d[72]), "+f"(d[73]), "+f"(d[74]), "+f"(d[75]), "+f"(d[76]), "+f"(d[77]), "+f"(d[78]), "+f"(d[79]),
          "+f"(d[80]), "+f"(d[81]), "+f"(d[82]), "+f"(d[83]), "+f"(d[84]), "+f"(d[85]), "+f"(d[86]), "+f"(d[87]),
          "+f"(d[88]), "+f"(d[89]), "+f"(d[90]), "+f"(d[91]), "+f"(d[92]), "+f"(d[93]), "+f"(d[94]), "+f"(d[95])
        : "l"(da), "l"(db), "r"(scale_d));
}

__global__ void __launch_bounds__(288, 1) qkv_kernel(const __grid_constant__ CUtensorMap mapA, const __grid_constant__ CUtensorMap mapB) {
    extern __shared__ uint8_t smem_raw[];
    const uint32_t sbase = (smem_u32(smem_raw) + 1023u) & ~1023u;
    const uint32_t bars = sbase + K1_ST * K1_STAGE;
    const int warp = threadIdx.x >> 5, lane = threadIdx.x & 31;
    const int nb = blockIdx.x & 7, mb = blockIdx.x >> 3;
    TL(1, 0);
    if (threadIdx.x == 0) {
        for (int s = 0; s < K1_ST; s++) { mbar_init(bars + 8 * s, 1); mbar_init(bars + 8 * (K1_ST + s), 2); }
        fence_barrier_init();
    }
    __syncthreads();
    if (warp == 8) {
        if (lane == 0) {
            for (int c = 0; c < K1_ST; c++) {
                const uint32_t st = sbase + c * K1_STAGE;
                mbar_expect_tx(bars + 8 * c, K1_STAGE);
                for (int j = 0; j < 3; j++) tma2d(st + 16384 + j * 8192, &mapB, bars + 8 * c, nb * 192 + j * 64, c * 64);
            }
            pdl_wait();
            pdl_launch();
            for (int c = 0; c < K1_ST; c++) tma2d(sbase + c * K1_STAGE, &mapA, bars + 8 * c, c * 64, mb * 128);
            for (int c = K1_ST; c < 8; c++) {
                const int s = c - K1_ST;
                const uint32_t st = sbase + s * K1_STAGE;
                mbar_wait(bars + 8 * (K1_ST + s), 0);
                mbar_expect_tx(bars + 8 * s, K1_STAGE);
                tma2d(st, &mapA, bars + 8 * s, c * 64, mb * 128);
                for (int j = 0; j < 3; j++) tma2d(st + 16384 + j * 8192, &mapB, bars + 8 * s, nb * 192 + j * 64, c * 64);
            }
        }
        return;
    }
    const int wg = warp >> 2;
    float acc[96];
#pragma unroll
    for (int i = 0; i < 96; i++) acc[i] = 0.f;
#pragma unroll 1
    for (int c = 0; c < 8; c++) {
        const int s = c < K1_ST ? c : c - K1_ST;
        const uint32_t st = sbase + s * K1_STAGE;
        mbar_wait(bars + 8 * s, c < K1_ST ? 0 : 1);
        if (c == 0) TL(1, 1);
        const uint64_t da = mkdesc(st + wg * 8192, 16, 1024, 1);
        const uint64_t db = mkdesc(st + 16384, 8192, 1024, 1);
        WG_FENCE();
#pragma unroll
        for (int k = 0; k < 4; k++) wgmma_n192(acc, da + k * 2, db + k * 128, (c | k) != 0);
        WG_COMMIT();
        if (c + K1_ST < 8 + 1) {
            WG_WAIT(1);
            if (c >= 1 && (threadIdx.x & 127) == 0) mbar_arrive(bars + 8 * (K1_ST + c - 1));
        }
    }
    WG_WAIT(0);
    TL(1, 2);
    const int g = lane >> 2, t = lane & 3;
    const int mt = mb * 8 + warp;
#pragma unroll
    for (int hh = 0; hh < 12; hh++) {
        const int gh = nb * 12 + hh;
        const float* a = &acc[hh * 8];
        if (gh < 32) {
            uint4 v;
            v.x = packbf(a[0], a[1]); v.y = packbf(a[2], a[3]);
            v.z = packbf(a[4], a[5]); v.w = packbf(a[6], a[7]);
            g_q[(gh * 128 + mt) * 32 + lane] = v;
        } else {
            uint32_t* dst = reinterpret_cast<uint32_t*>(gh < 64 ? g_k + (gh - 32) * 4096 : g_v + (gh - 64) * 4096);
            const float ks = gh < 64 ? 5.421010862427522e-20f : 1.0f;
            const int off = (mt * 16 + g) * 4 + t;
            dst[off] = packbf(a[0] * ks, a[1] * ks);
            dst[off + 32] = packbf(a[2] * ks, a[3] * ks);
            dst[8192 + off] = packbf(a[4] * ks, a[5] * ks);
            dst[8192 + off + 32] = packbf(a[6] * ks, a[7] * ks);
        }
    }
    TL(1, 3);
}

constexpr float SHIFT = 90.0f;
constexpr float QS = 0.25f * 1.4426950408889634f * 18446744073709551616.0f;
constexpr float scq = 0.25f * 1.4426950408889634f * 3.3087224502121107e-24f;
constexpr int K2_SMEM = 163840 + 1024 + 128;

__device__ __forceinline__ uint32_t polyexp(float lo, float hi) {
    uint32_t w, g, q, h;
    asm("cvt.pack.sat.s16.s32 %0, %1, %2;" : "=r"(w) : "r"(__float_as_uint(hi)), "r"(__float_as_uint(lo)));
    g = w & 0x007F007Fu;
    asm("fma.rn.f16x2 %0, %1, %2, %3;" : "=r"(q) : "r"(g), "r"(0xf940f940u), "r"(0x35513551u));
    asm("mul.rn.f16x2 %0, %1, %2;" : "=r"(h) : "r"(q), "r"(g));
    return w - h;
}
__device__ __forceinline__ void qk64(float (&s)[32], const uint32_t (&q)[4], uint64_t db) {
    asm volatile("wgmma.mma_async.sync.aligned.m64n64k16.f32.bf16.bf16 "
        "{%0,%1,%2,%3,%4,%5,%6,%7,%8,%9,%10,%11,%12,%13,%14,%15,%16,%17,%18,%19,%20,%21,%22,%23,%24,%25,%26,%27,%28,%29,%30,%31}, "
        "{%32,%33,%34,%35}, %36, 0, 1, 1, 0;"
        : "=f"(s[0]), "=f"(s[1]), "=f"(s[2]), "=f"(s[3]), "=f"(s[4]), "=f"(s[5]), "=f"(s[6]), "=f"(s[7]),
          "=f"(s[8]), "=f"(s[9]), "=f"(s[10]), "=f"(s[11]), "=f"(s[12]), "=f"(s[13]), "=f"(s[14]), "=f"(s[15]),
          "=f"(s[16]), "=f"(s[17]), "=f"(s[18]), "=f"(s[19]), "=f"(s[20]), "=f"(s[21]), "=f"(s[22]), "=f"(s[23]),
          "=f"(s[24]), "=f"(s[25]), "=f"(s[26]), "=f"(s[27]), "=f"(s[28]), "=f"(s[29]), "=f"(s[30]), "=f"(s[31])
        : "r"(q[0]), "r"(q[1]), "r"(q[2]), "r"(q[3]), "l"(db));
}
__device__ __forceinline__ void pv24(float (&o)[12], uint32_t a0, uint32_t a1, uint32_t a2, uint32_t a3, uint64_t db) {
    asm volatile("wgmma.mma_async.sync.aligned.m64n24k16.f32.bf16.bf16 "
        "{%0,%1,%2,%3,%4,%5,%6,%7,%8,%9,%10,%11}, {%12,%13,%14,%15}, %16, 1, 1, 1, 1;"
        : "+f"(o[0]), "+f"(o[1]), "+f"(o[2]), "+f"(o[3]), "+f"(o[4]), "+f"(o[5]), "+f"(o[6]), "+f"(o[7]),
          "+f"(o[8]), "+f"(o[9]), "+f"(o[10]), "+f"(o[11])
        : "r"(a0), "r"(a1), "r"(a2), "r"(a3), "l"(db));
}

__device__ __forceinline__ void attn_safe(float (&o)[12], const uint32_t (&q)[4], uint64_t kdesc0, uint64_t vdesc0) {
    float s[32];
    float m0 = -INFINITY, m1 = -INFINITY;
#pragma unroll
    for (int i = 0; i < 12; i++) o[i] = 0.f;
#pragma unroll 1
    for (int j = 0; j < 32; j++) {
        WG_FENCE();
        qk64(s, q, kdesc0 + (uint64_t)(j * 64));
        WG_COMMIT(); WG_WAIT(0);
        float n0 = m0, n1 = m1;
#pragma unroll
        for (int i = 0; i < 8; i++) { n0 = fmaxf(n0, fmaxf(s[4 * i], s[4 * i + 1])); n1 = fmaxf(n1, fmaxf(s[4 * i + 2], s[4 * i + 3])); }
        n0 = fmaxf(n0, __shfl_xor_sync(~0u, n0, 1)); n0 = fmaxf(n0, __shfl_xor_sync(~0u, n0, 2));
        n1 = fmaxf(n1, __shfl_xor_sync(~0u, n1, 1)); n1 = fmaxf(n1, __shfl_xor_sync(~0u, n1, 2));
        const float c0 = ex2((m0 - n0) * QS), c1 = ex2((m1 - n1) * QS);
        m0 = n0; m1 = n1;
#pragma unroll
        for (int i = 0; i < 3; i++) { o[4 * i] *= c0; o[4 * i + 1] *= c0; o[4 * i + 2] *= c1; o[4 * i + 3] *= c1; }
        uint32_t p[16];
#pragma unroll
        for (int i = 0; i < 8; i++) {
            p[2 * i] = packbf(ex2((s[4 * i] - m0) * QS), ex2((s[4 * i + 1] - m0) * QS));
            p[2 * i + 1] = packbf(ex2((s[4 * i + 2] - m1) * QS), ex2((s[4 * i + 3] - m1) * QS));
        }
        WG_FENCE();
#pragma unroll
        for (int kk = 0; kk < 4; kk++) pv24(o, p[4 * kk], p[4 * kk + 1], p[4 * kk + 2], p[4 * kk + 3], vdesc0 + (uint64_t)(j * 64 + kk * 16));
        WG_COMMIT(); WG_WAIT(0);
    }
}

__device__ __forceinline__ void attn_store(const float (&o)[12], int head, int m64, int warp, int lane) {
    const int g = lane >> 2, t = lane & 3;
    const int row = m64 * 64 + warp * 16 + g;
    const float i0 = 1.f / o[8], i1 = 1.f / o[10];
    uint32_t* p0 = reinterpret_cast<uint32_t*>(g_o + (size_t)row * DM + head * 16 + t * 2);
    uint32_t* p1 = reinterpret_cast<uint32_t*>(g_o + (size_t)(row + 8) * DM + head * 16 + t * 2);
    p0[0] = packbf(o[0] * i0, o[1] * i0); p0[4] = packbf(o[4] * i0, o[5] * i0);
    p1[0] = packbf(o[2] * i1, o[3] * i1); p1[4] = packbf(o[6] * i1, o[7] * i1);
}

__device__ void ffn_block(int c, uint8_t* smem, const __nv_bfloat16* __restrict__ wg, const __nv_bfloat16* __restrict__ wu,
                          const __nv_bfloat16* __restrict__ wd) {
    const int tid = threadIdx.x, warp = tid >> 5, lane = tid & 31;
    float* sx = reinterpret_cast<float*>(smem);
    float* sh = sx + 1024;
    float* red = sh + 1024;
    __shared__ float tv[32]; __shared__ int ti[32];
    __shared__ int ssel[2];
    float b1 = -INFINITY, b2 = -INFINITY; int i1 = 0x7fffffff, i2 = 0x7fffffff;
    auto push = [&](float v, int i) {
        if (v > b1 || (v == b1 && i < i1)) { b2 = b1; i2 = i1; b1 = v; i1 = i; }
        else if (v > b2 || (v == b2 && i < i2)) { b2 = v; i2 = i; }
    };
    for (int i = tid; i < S_LEN; i += 512) push(g_r[i], i);
#pragma unroll
    for (int o = 16; o > 0; o >>= 1) {
        float v1 = __shfl_xor_sync(~0u, b1, o), v2 = __shfl_xor_sync(~0u, b2, o);
        int j1 = __shfl_xor_sync(~0u, i1, o), j2 = __shfl_xor_sync(~0u, i2, o);
        push(v1, j1); push(v2, j2);
    }
    if (lane == 0) { tv[2 * warp] = b1; ti[2 * warp] = i1; tv[2 * warp + 1] = b2; ti[2 * warp + 1] = i2; }
    __syncthreads();
    if (warp == 0) {
        b1 = tv[lane]; i1 = ti[lane]; b2 = -INFINITY; i2 = 0x7fffffff;
#pragma unroll
        for (int o = 16; o > 0; o >>= 1) {
            float v1 = __shfl_xor_sync(~0u, b1, o), v2 = __shfl_xor_sync(~0u, b2, o);
            int j1 = __shfl_xor_sync(~0u, i1, o), j2 = __shfl_xor_sync(~0u, i2, o);
            push(v1, j1); push(v2, j2);
        }
        if (lane == 0) {
            i1 = min(max(i1, 0), S_LEN - 1); i2 = min(max(i2, 0), S_LEN - 1);
            ssel[0] = i1; ssel[1] = i2;
            if (c == 0) {
                g_sel[0] = i1; g_sel[1] = i2;
                g_gate[0] = bfr(1.f / (1.f + __expf(-bfr(b1))));
                g_gate[1] = bfr(1.f / (1.f + __expf(-bfr(b2))));
            }
        }
    }
    __syncthreads();
    for (int i = tid; i < 1024; i += 512) sx[i] = __bfloat162float(g_xn[(size_t)ssel[i >> 9] * DM + (i & 511)]);
    __syncthreads();
    {
        const int ch = tid % 56, kg = tid / 56;
        float ag[2][8], au[2][8];
#pragma unroll
        for (int j = 0; j < 8; j++) { ag[0][j] = ag[1][j] = au[0][j] = au[1][j] = 0.f; }
        if (kg < 9) {
            const uint4* pg = reinterpret_cast<const uint4*>(wg + c * 448 + ch * 8);
            const uint4* pu = reinterpret_cast<const uint4*>(wu + c * 448 + ch * 8);
#pragma unroll 1
            for (int k0 = kg; k0 < DM; k0 += 72) {
                uint4 vg[8], vu[8];
#pragma unroll
                for (int b = 0; b < 8; b++) {
                    const int k = min(k0 + b * 9, DM - 1);
                    vg[b] = __ldg(pg + (size_t)k * (FF / 8)); vu[b] = __ldg(pu + (size_t)k * (FF / 8));
                }
#pragma unroll
                for (int b = 0; b < 8; b++) {
                    const int k = k0 + b * 9;
                    const float x0 = k < DM ? sx[k] : 0.f, x1 = k < DM ? sx[512 + k] : 0.f;
                    const uint32_t gw[4] = {vg[b].x, vg[b].y, vg[b].z, vg[b].w}, uw[4] = {vu[b].x, vu[b].y, vu[b].z, vu[b].w};
#pragma unroll
                    for (int j = 0; j < 4; j++) {
                        const float g0 = bf_lo(gw[j]), g1 = bf_hi(gw[j]), u0 = bf_lo(uw[j]), u1 = bf_hi(uw[j]);
                        ag[0][2 * j] = fmaf(x0, g0, ag[0][2 * j]); ag[0][2 * j + 1] = fmaf(x0, g1, ag[0][2 * j + 1]);
                        ag[1][2 * j] = fmaf(x1, g0, ag[1][2 * j]); ag[1][2 * j + 1] = fmaf(x1, g1, ag[1][2 * j + 1]);
                        au[0][2 * j] = fmaf(x0, u0, au[0][2 * j]); au[0][2 * j + 1] = fmaf(x0, u1, au[0][2 * j + 1]);
                        au[1][2 * j] = fmaf(x1, u0, au[1][2 * j]); au[1][2 * j + 1] = fmaf(x1, u1, au[1][2 * j + 1]);
                    }
                }
            }
#pragma unroll
            for (int j = 0; j < 8; j++) {
                red[(kg * 4 + 0) * 448 + ch * 8 + j] = ag[0][j]; red[(kg * 4 + 1) * 448 + ch * 8 + j] = ag[1][j];
                red[(kg * 4 + 2) * 448 + ch * 8 + j] = au[0][j]; red[(kg * 4 + 3) * 448 + ch * 8 + j] = au[1][j];
            }
        }
        __syncthreads();
        for (int i = tid; i < 896; i += 512) {
            const int tok = i / 448, col = i % 448;
            float gs = 0.f, us = 0.f;
#pragma unroll
            for (int q = 0; q < 9; q++) { gs += red[(q * 4 + tok) * 448 + col]; us += red[(q * 4 + 2 + tok) * 448 + col]; }
            gs = bfr(gs); us = bfr(us);
            const float sg = bfr(gs / (1.f + __expf(-gs)));
            sh[tok * 448 + col] = bfr(sg * us);
        }
        __syncthreads();
    }
    {
        const int ch = tid & 63, kg = tid >> 6;
        float a[2][8];
#pragma unroll
        for (int j = 0; j < 8; j++) a[0][j] = a[1][j] = 0.f;
        const uint4* pd = reinterpret_cast<const uint4*>(wd + (size_t)c * 448 * DM + ch * 8);
#pragma unroll 1
        for (int k0 = kg; k0 < 448; k0 += 112) {
            uint4 v[14];
#pragma unroll
            for (int b = 0; b < 14; b++) v[b] = __ldg(pd + (size_t)(k0 + b * 8) * (DM / 8));
#pragma unroll
            for (int b = 0; b < 14; b++) {
                const int k = k0 + b * 8;
                const float h0 = sh[k], h1 = sh[448 + k];
                const uint32_t w[4] = {v[b].x, v[b].y, v[b].z, v[b].w};
#pragma unroll
                for (int j = 0; j < 4; j++) {
                    const float w0 = bf_lo(w[j]), w1 = bf_hi(w[j]);
                    a[0][2 * j] = fmaf(h0, w0, a[0][2 * j]); a[0][2 * j + 1] = fmaf(h0, w1, a[0][2 * j + 1]);
                    a[1][2 * j] = fmaf(h1, w0, a[1][2 * j]); a[1][2 * j + 1] = fmaf(h1, w1, a[1][2 * j + 1]);
                }
            }
        }
#pragma unroll
        for (int j = 0; j < 8; j++) { red[(kg * 2 + 0) * 512 + ch * 8 + j] = a[0][j]; red[(kg * 2 + 1) * 512 + ch * 8 + j] = a[1][j]; }
        __syncthreads();
        for (int i = tid; i < 1024; i += 512) {
            float s = 0.f;
#pragma unroll
            for (int q = 0; q < 8; q++) s += red[q * 1024 + i];
            g_ypart[c * 1024 + i] = s;
        }
    }
}

__global__ void __launch_bounds__(512, 1) attn_kernel(const __nv_bfloat16* __restrict__ wg_, const __nv_bfloat16* __restrict__ wu_,
                                                      const __nv_bfloat16* __restrict__ wd_, float sc) {
    extern __shared__ uint8_t smem_raw[];
    const uint32_t sraw = smem_u32(smem_raw);
    const uint32_t sbase = (sraw + 1023u) & ~1023u;
    uint8_t* sptr = smem_raw + (sbase - sraw);
    TL(2, 0);
    if (blockIdx.x >= 128) {
        pdl_wait();
        pdl_launch();
        TL(2, 1);
        ffn_block(blockIdx.x - 128, sptr, wg_, wu_, wd_);
        TL(2, 3);
        return;
    }
    const uint32_t bars = sbase + 163840;
    const int head = blockIdx.x >> 2, quarter = blockIdx.x & 3;
    const int wg = threadIdx.x >> 7, warp = (threadIdx.x >> 5) & 3, lane = threadIdx.x & 31;
    if (threadIdx.x == 0) {
        for (int c = 0; c < 8; c++) mbar_init(bars + 8 * c, 1);
        fence_barrier_init();
    }
    {
        uint4* ones = reinterpret_cast<uint4*>(sptr + 131072);
        for (int i = threadIdx.x; i < 2048; i += 512) ones[i] = make_uint4(0x3f803f80u, 0x3f803f80u, 0x3f803f80u, 0x3f803f80u);
        fence_proxy_async();
    }
    __syncthreads();
    pdl_wait();
    pdl_launch();
    TL(2, 1);
    if (threadIdx.x == 0) {
        const uint8_t* kp = reinterpret_cast<const uint8_t*>(g_k + head * 4096);
        const uint8_t* vp = reinterpret_cast<const uint8_t*>(g_v + head * 4096);
        for (int c = 0; c < 8; c++) {
            mbar_expect_tx(bars + 8 * c, 16384);
            bulk_g2s(sbase + c * 4096, kp + c * 4096, 4096, bars + 8 * c);
            bulk_g2s(sbase + 32768 + c * 4096, kp + 32768 + c * 4096, 4096, bars + 8 * c);
            bulk_g2s(sbase + 65536 + c * 4096, vp + c * 4096, 4096, bars + 8 * c);
            bulk_g2s(sbase + 98304 + c * 4096, vp + 32768 + c * 4096, 4096, bars + 8 * c);
        }
    }
    const uint64_t kdesc0 = mkdesc(sbase, 32768, 128, 0);
    const uint64_t vdesc0 = mkdesc(sbase + 65536, 128, 32768, 0);
    uint32_t badmask = 0;
#pragma unroll 1
    for (int mt = 0; mt < 2; mt++) {
        const int m64 = quarter * 8 + mt * 4 + wg;
        uint32_t q[4];
        { const uint4 qq = g_q[(head * 128 + m64 * 4 + warp) * 32 + lane]; q[0] = qq.x; q[1] = qq.y; q[2] = qq.z; q[3] = qq.w; }
        float s[32], s2[32], o[12];
#pragma unroll
        for (int i = 0; i < 12; i++) o[i] = 0.f;
        mbar_wait(bars, 0);
        if (mt == 0) TL(2, 2);
        WG_FENCE();
        qk64(s, q, kdesc0);
        WG_COMMIT(); WG_WAIT(0);
        float mx0 = -INFINITY, mx1 = -INFINITY;
#pragma unroll
        for (int i = 0; i < 8; i++) { mx0 = fmaxf(mx0, fmaxf(s[4 * i], s[4 * i + 1])); mx1 = fmaxf(mx1, fmaxf(s[4 * i + 2], s[4 * i + 3])); }
        mx0 = fmaxf(mx0, __shfl_xor_sync(~0u, mx0, 1)); mx0 = fmaxf(mx0, __shfl_xor_sync(~0u, mx0, 2));
        mx1 = fmaxf(mx1, __shfl_xor_sync(~0u, mx1, 1)); mx1 = fmaxf(mx1, __shfl_xor_sync(~0u, mx1, 2));
        float cm0 = -(ceilf(mx0 * QS) + SHIFT), cm1 = -(ceilf(mx1 * QS) + SHIFT);
        float cp0 = (cm0 + 127.f) * sc, cp1 = (cm1 + 127.f) * sc;
        asm volatile("" : "+f"(cm0), "+f"(cm1), "+f"(cp0), "+f"(cp1));
        uint64_t kd = kdesc0, vd = vdesc0;
        auto step = [&](float (&sc_)[32], float (&sn)[32]) {
            kd += 64;
            WG_FENCE();
            qk64(sn, q, kd);
            WG_COMMIT();
#pragma unroll
            for (int kk = 0; kk < 4; kk++) {
                const int i0 = kk * 2, i1 = kk * 2 + 1;
                const uint32_t p0 = packbf(ex2(fmaf(sc_[4 * i0], QS, cm0)), ex2(fmaf(sc_[4 * i0 + 1], QS, cm0)));
                const uint32_t p1 = packbf(ex2(fmaf(sc_[4 * i0 + 2], QS, cm1)), ex2(fmaf(sc_[4 * i0 + 3], QS, cm1)));
                const uint32_t p2 = polyexp(fmaf(sc_[4 * i1], scq, cp0), fmaf(sc_[4 * i1 + 1], scq, cp0));
                const uint32_t p3 = polyexp(fmaf(sc_[4 * i1 + 2], scq, cp1), fmaf(sc_[4 * i1 + 3], scq, cp1));
                WG_FENCE();
                pv24(o, p0, p1, p2, p3, vd);
                vd += 16;
            }
            WG_COMMIT();
            WG_WAIT(1);
        };
#pragma unroll 1
        for (int c = 0; c < 16; c++) {
            if (mt == 0 && (c & 1) == 0 && c < 14) mbar_wait(bars + 4 * c + 8, 0);
            step(s, s2); step(s2, s);
        }
        WG_WAIT(0);
        bool bad = !(o[8] > 0.f) || !(o[10] > 0.f);
#pragma unroll
        for (int i = 0; i < 12; i++) bad = bad || !(fabsf(o[i]) <= 3.0e38f);
        uint32_t anybad;
        asm volatile("{\n.reg .pred p, q;\nsetp.ne.u32 p, %1, 0;\nbarrier.cta.red.or.pred q, %2, 128, p;\nselp.u32 %0, 1, 0, q;\n}"
                     : "=r"(anybad) : "r"((uint32_t)bad), "r"(wg + 1) : "memory");
        badmask |= anybad << mt;
        attn_store(o, head, m64, warp, lane);
    }
#pragma unroll 1
    for (int mt = 0; mt < 2; mt++) {
        if (!((badmask >> mt) & 1)) continue;
        const int m64 = quarter * 8 + mt * 4 + wg;
        uint32_t q[4];
        { const uint4 qq = g_q[(head * 128 + m64 * 4 + warp) * 32 + lane]; q[0] = qq.x; q[1] = qq.y; q[2] = qq.z; q[3] = qq.w; }
        float o[12];
        attn_safe(o, q, mkdesc(sbase, 32768, 128, 0), mkdesc(sbase + 65536, 128, 32768, 0));
        attn_store(o, head, m64, warp, lane);
    }
    TL(2, 3);
}

constexpr int K3_SMEM = 8 * 8192 + 8 * 16384 + 1024 + 128;

__device__ __forceinline__ void wgmma_n64(float (&d)[32], uint64_t da, uint64_t db, int scale_d) {
    asm volatile("{\n.reg .pred p;\nsetp.ne.b32 p, %34, 0;\n"
        "wgmma.mma_async.sync.aligned.m64n64k16.f32.bf16.bf16 "
        "{%0,%1,%2,%3,%4,%5,%6,%7,%8,%9,%10,%11,%12,%13,%14,%15,%16,%17,%18,%19,%20,%21,%22,%23,%24,%25,%26,%27,%28,%29,%30,%31}, "
        "%32, %33, p, 1, 1, 0, 1;\n}"
        : "+f"(d[0]), "+f"(d[1]), "+f"(d[2]), "+f"(d[3]), "+f"(d[4]), "+f"(d[5]), "+f"(d[6]), "+f"(d[7]),
          "+f"(d[8]), "+f"(d[9]), "+f"(d[10]), "+f"(d[11]), "+f"(d[12]), "+f"(d[13]), "+f"(d[14]), "+f"(d[15]),
          "+f"(d[16]), "+f"(d[17]), "+f"(d[18]), "+f"(d[19]), "+f"(d[20]), "+f"(d[21]), "+f"(d[22]), "+f"(d[23]),
          "+f"(d[24]), "+f"(d[25]), "+f"(d[26]), "+f"(d[27]), "+f"(d[28]), "+f"(d[29]), "+f"(d[30]), "+f"(d[31])
        : "l"(da), "l"(db), "r"(scale_d));
}

__global__ void __launch_bounds__(256, 1) oproj_kernel(const __grid_constant__ CUtensorMap mapA, const __grid_constant__ CUtensorMap mapB,
                                                       const __nv_bfloat16* __restrict__ x, __nv_bfloat16* __restrict__ out) {
    extern __shared__ uint8_t smem_raw[];
    const uint32_t sbase = (smem_u32(smem_raw) + 1023u) & ~1023u;
    const uint32_t sA = sbase, sB = sbase + 8 * 8192, bars = sbase + 8 * 8192 + 8 * 16384;
    const int warp = threadIdx.x >> 5, lane = threadIdx.x & 31, wg = warp >> 2;
    const int nb = blockIdx.x & 3, mb = blockIdx.x >> 2;
    TL(3, 0);
    if (threadIdx.x == 0) {
        for (int c = 0; c < 8; c++) mbar_init(bars + 8 * c, 1);
        fence_barrier_init();
        for (int c = 0; c < 8; c++) {
            mbar_expect_tx(bars + 8 * c, 8192 + 16384);
            tma2d(sB + c * 16384, &mapB, bars + 8 * c, nb * 128, c * 64);
            tma2d(sB + c * 16384 + 8192, &mapB, bars + 8 * c, nb * 128 + 64, c * 64);
        }
    }
    const int g = lane >> 2, t = lane & 3;
    const int row0 = mb * 64 + (warp & 3) * 16 + g;
    const int col0 = nb * 128 + wg * 64 + t * 2;
    uint32_t xv[16], nv[16];
#pragma unroll
    for (int i = 0; i < 8; i++) {
        xv[2 * i] = *reinterpret_cast<const uint32_t*>(x + (size_t)row0 * DM + col0 + i * 8);
        xv[2 * i + 1] = *reinterpret_cast<const uint32_t*>(x + (size_t)(row0 + 8) * DM + col0 + i * 8);
        nv[2 * i] = *reinterpret_cast<const uint32_t*>(g_xn + (size_t)row0 * DM + col0 + i * 8);
        nv[2 * i + 1] = *reinterpret_cast<const uint32_t*>(g_xn + (size_t)(row0 + 8) * DM + col0 + i * 8);
    }
    __syncthreads();
    pdl_wait();
    TL(3, 1);
    if (threadIdx.x == 0) {
        for (int c = 0; c < 8; c++) tma2d(sA + c * 8192, &mapA, bars + 8 * c, c * 64, mb * 64);
    }
    float acc[32];
#pragma unroll
    for (int i = 0; i < 32; i++) acc[i] = 0.f;
#pragma unroll 1
    for (int c = 0; c < 8; c++) {
        mbar_wait(bars + 8 * c, 0);
        const uint64_t da = mkdesc(sA + c * 8192, 16, 1024, 1);
        const uint64_t db = mkdesc(sB + c * 16384 + wg * 8192, 8192, 1024, 1);
        WG_FENCE();
#pragma unroll
        for (int k = 0; k < 4; k++) wgmma_n64(acc, da + k * 2, db + k * 128, (c | k) != 0);
        WG_COMMIT();
    }
    const int sel0 = g_sel[0], sel1 = g_sel[1];
    WG_WAIT(0);
    TL(3, 2);
#pragma unroll
    for (int h = 0; h < 2; h++) {
        const int row = row0 + h * 8;
        const int which = row == sel0 ? 0 : (row == sel1 ? 1 : -1);
#pragma unroll
        for (int i = 0; i < 8; i++) {
            const int col = col0 + i * 8;
            float b0 = bf_lo(nv[2 * i + h]), b1 = bf_hi(nv[2 * i + h]);
            if (which >= 0) {
                float y0 = 0.f, y1 = 0.f;
#pragma unroll
                for (int c = 0; c < 4; c++) { y0 += g_ypart[c * 1024 + which * 512 + col]; y1 += g_ypart[c * 1024 + which * 512 + col + 1]; }
                const float gt = g_gate[which];
                b0 = bfr(b0 + bfr(bfr(y0) * gt)); b1 = bfr(b1 + bfr(bfr(y1) * gt));
            }
            const float t0 = bfr(bf_lo(xv[2 * i + h]) + bfr(acc[4 * i + 2 * h]));
            const float t1 = bfr(bf_hi(xv[2 * i + h]) + bfr(acc[4 * i + 2 * h + 1]));
            *reinterpret_cast<uint32_t*>(out + (size_t)row * DM + col) = packbf(t0 + b0, t1 + b1);
        }
    }
    TL(3, 3);
}

typedef CUresult (*EncodeFn)(CUtensorMap*, CUtensorMapDataType, cuuint32_t, void*, const cuuint64_t*, const cuuint64_t*,
                             const cuuint32_t*, const cuuint32_t*, CUtensorMapInterleave, CUtensorMapSwizzle,
                             CUtensorMapL2promotion, CUtensorMapFloatOOBfill);

void make_map(EncodeFn fn, CUtensorMap* m, const void* ptr, uint64_t inner, uint64_t outer, uint32_t box_inner, uint32_t box_outer) {
    cuuint64_t dims[2] = {inner, outer};
    cuuint64_t strides[1] = {inner * 2};
    cuuint32_t box[2] = {box_inner, box_outer};
    cuuint32_t es[2] = {1, 1};
    fn(m, CU_TENSOR_MAP_DATA_TYPE_BFLOAT16, 2, const_cast<void*>(ptr), dims, strides, box, es, CU_TENSOR_MAP_INTERLEAVE_NONE,
       CU_TENSOR_MAP_SWIZZLE_128B, CU_TENSOR_MAP_L2_PROMOTION_L2_256B, CU_TENSOR_MAP_FLOAT_OOB_FILL_NONE);
}

template <typename... KArgs, typename... Args>
void launch(void (*kern)(KArgs...), int grid, int block, int smem, bool pdl, Args... args) {
    cudaLaunchConfig_t cfg = {};
    cfg.gridDim = dim3(grid); cfg.blockDim = dim3(block); cfg.dynamicSmemBytes = smem; cfg.stream = cudaStreamPerThread;
    cudaLaunchAttribute at[1];
    at[0].id = cudaLaunchAttributeProgrammaticStreamSerialization;
    at[0].val.programmaticStreamSerializationAllowed = 1;
    cfg.attrs = at; cfg.numAttrs = pdl ? 1 : 0;
    cudaLaunchKernelEx(&cfg, kern, KArgs(args)...);
}

}

extern "C" void kernel_launch(void* const* d_in, const int* in_sizes, int n_in, void* d_out, int out_size) {
    const __nv_bfloat16* x = (const __nv_bfloat16*)d_in[0];
    const __nv_bfloat16* wqkv = (const __nv_bfloat16*)d_in[1];
    const __nv_bfloat16* wo = (const __nv_bfloat16*)d_in[2];
    const __nv_bfloat16* wr = (const __nv_bfloat16*)d_in[4];
    const __nv_bfloat16* wgate = (const __nv_bfloat16*)d_in[5];
    const __nv_bfloat16* wup = (const __nv_bfloat16*)d_in[6];
    const __nv_bfloat16* wdown = (const __nv_bfloat16*)d_in[7];
    __nv_bfloat16* out = (__nv_bfloat16*)d_out;

    static EncodeFn enc = nullptr;
    static void* p_xn = nullptr; static void* p_o = nullptr;
    if (!enc) {
        void* fn = nullptr; cudaDriverEntryPointQueryResult qr;
        cudaGetDriverEntryPoint("cuTensorMapEncodeTiled", &fn, cudaEnableDefault, &qr);
        enc = (EncodeFn)fn;
        cudaGetSymbolAddress(&p_xn, g_xn);
        cudaGetSymbolAddress(&p_o, g_o);
        cudaFuncSetAttribute(qkv_kernel, cudaFuncAttributeMaxDynamicSharedMemorySize, K1_SMEM);
        cudaFuncSetAttribute(attn_kernel, cudaFuncAttributeMaxDynamicSharedMemorySize, K2_SMEM);
        cudaFuncSetAttribute(oproj_kernel, cudaFuncAttributeMaxDynamicSharedMemorySize, K3_SMEM);
    }
    CUtensorMap mXn, mWqkv, mO, mWo;
    make_map(enc, &mXn, p_xn, DM, S_LEN, 64, 128);
    make_map(enc, &mWqkv, wqkv, 3 * DM, DM, 64, 64);
    make_map(enc, &mO, p_o, DM, S_LEN, 64, 64);
    make_map(enc, &mWo, wo, DM, DM, 64, 64);

    union { uint32_t u; float f; } scu; scu.u = 128u;

    launch(ln_kernel, S_LEN / 8, 256, 0, false, x, wr);
    launch(qkv_kernel, 128, 288, K1_SMEM, true, mXn, mWqkv);
    launch(attn_kernel, 132, 512, K2_SMEM, true, wgate, wup, wdown, scu.f);
    launch(oproj_kernel, 128, 256, K3_SMEM, true, mO, mWo, x, out);
}
```

```cpp
#include <cuda_runtime.h>
#include <cuda_bf16.h>
#include <cuda.h>
#include <stdint.h>
#include <type_traits>

namespace {

constexpr int S_LEN = 2048;
constexpr int DM = 512;
constexpr int NH = 32;
constexpr int FF = 1792;

__device__ __align__(1024) __nv_bfloat16 g_xn[S_LEN * DM];
__device__ __align__(16) float g_r[S_LEN];
__device__ __align__(1024) uint4 g_q[NH * 128 * 32];
__device__ __align__(1024) uint4 g_k[NH * 4096];
__device__ __align__(1024) uint4 g_v[NH * 4096];
__device__ __align__(1024) __nv_bfloat16 g_o[S_LEN * DM];
__device__ float g_ypart[4 * 2 * DM];
__device__ int g_sel[2];
__device__ float g_gate[2];

#define TL(k, slot) do {} while (0)

__device__ __forceinline__ uint32_t smem_u32(const void* p) { return (uint32_t)__cvta_generic_to_shared(p); }
__device__ __forceinline__ void pdl_wait() { asm volatile("griddepcontrol.wait;" ::: "memory"); }
__device__ __forceinline__ void pdl_launch() { asm volatile("griddepcontrol.launch_dependents;" ::: "memory"); }
__device__ __forceinline__ void mbar_init(uint32_t bar, uint32_t cnt) {
    asm volatile("mbarrier.init.shared::cta.b64 [%0], %1;" :: "r"(bar), "r"(cnt) : "memory");
}
__device__ __forceinline__ void mbar_expect_tx(uint32_t bar, uint32_t bytes) {
    asm volatile("mbarrier.arrive.expect_tx.shared::cta.b64 _, [%0], %1;" :: "r"(bar), "r"(bytes) : "memory");
}
__device__ __forceinline__ void mbar_arrive(uint32_t bar) {
    asm volatile("mbarrier.arrive.shared::cta.b64 _, [%0];" :: "r"(bar) : "memory");
}
__device__ __forceinline__ void mbar_wait(uint32_t bar, uint32_t parity) {
    asm volatile("{\n.reg .pred p;\n.reg .u32 n;\nmov.u32 n, 0;\n"
                 "WAIT_%=:\n"
                 "mbarrier.try_wait.parity.shared::cta.b64 p, [%0], %1;\n"
                 "@p bra DONE_%=;\n"
                 "add.u32 n, n, 1;\n"
                 "setp.lt.u32 p, n, 4000000;\n"
                 "@p bra WAIT_%=;\n"
                 "trap;\n"
                 "DONE_%=:\n}"
                 :: "r"(bar), "r"(parity) : "memory");
}
__device__ __forceinline__ void fence_barrier_init() { asm volatile("fence.mbarrier_init.release.cluster;" ::: "memory"); }
__device__ __forceinline__ void fence_proxy_async() { asm volatile("fence.proxy.async.shared::cta;" ::: "memory"); }
__device__ __forceinline__ void tma2d(uint32_t dst, const CUtensorMap* map, uint32_t bar, int c0, int c1) {
    asm volatile("cp.async.bulk.tensor.2d.shared::cluster.global.mbarrier::complete_tx::bytes [%0], [%1, {%3, %4}], [%2];"
                 :: "r"(dst), "l"((uint64_t)map), "r"(bar), "r"(c0), "r"(c1) : "memory");
}
__device__ __forceinline__ void bulk_g2s(uint32_t dst, const void* src, uint32_t bytes, uint32_t bar) {
    asm volatile("cp.async.bulk.shared::cluster.global.mbarrier::complete_tx::bytes [%0], [%1], %2, [%3];"
                 :: "r"(dst), "l"((uint64_t)src), "r"(bytes), "r"(bar) : "memory");
}
__device__ __forceinline__ void l2_prefetch(const void* src, uint32_t bytes) {
    asm volatile("cp.async.bulk.prefetch.L2.global [%0], %1;" :: "l"((uint64_t)src), "r"(bytes) : "memory");
}
__device__ __forceinline__ uint64_t mkdesc(uint32_t addr, uint32_t lbo, uint32_t sbo, uint32_t swz) {
    return (uint64_t)((addr & 0x3FFFF) >> 4) | ((uint64_t)(lbo >> 4) << 16) | ((uint64_t)(sbo >> 4) << 32) | ((uint64_t)swz << 62);
}
#define WG_FENCE() asm volatile("wgmma.fence.sync.aligned;" ::: "memory")
#define WG_COMMIT() asm volatile("wgmma.commit_group.sync.aligned;" ::: "memory")
#define WG_WAIT(n) asm volatile("wgmma.wait_group.sync.aligned %0;" :: "n"(n) : "memory")

__device__ __forceinline__ float ex2(float x) { float y; asm("ex2.approx.ftz.f32 %0, %1;" : "=f"(y) : "f"(x)); return y; }
__device__ __forceinline__ uint32_t packbf(float lo, float hi) {
    uint32_t r; asm("cvt.rn.bf16x2.f32 %0, %1, %2;" : "=r"(r) : "f"(hi), "f"(lo)); return r;
}
__device__ __forceinline__ float bf_lo(uint32_t v) { return __uint_as_float(v << 16); }
__device__ __forceinline__ float bf_hi(uint32_t v) { return __uint_as_float(v & 0xffff0000u); }
__device__ __forceinline__ float bfr(float x) { return __bfloat162float(__float2bfloat16_rn(x)); }

__global__ void __launch_bounds__(256) ln_kernel(const __nv_bfloat16* __restrict__ x, const __nv_bfloat16* __restrict__ wr) {
    TL(0, 0);
    pdl_launch();
    const int warp = threadIdx.x >> 5, lane = threadIdx.x & 31;
    const int row = blockIdx.x * 8 + warp;
    const uint4* xr = reinterpret_cast<const uint4*>(x + (size_t)row * DM);
    uint4 a = xr[lane], b = xr[32 + lane];
    const uint4* wp = reinterpret_cast<const uint4*>(wr);
    uint4 wa = wp[lane], wb = wp[32 + lane];
    uint32_t u[8] = {a.x, a.y, a.z, a.w, b.x, b.y, b.z, b.w};
    uint32_t w[8] = {wa.x, wa.y, wa.z, wa.w, wb.x, wb.y, wb.z, wb.w};
    float f[16];
    float sum = 0.f;
#pragma unroll
    for (int i = 0; i < 8; i++) { f[2 * i] = bf_lo(u[i]); f[2 * i + 1] = bf_hi(u[i]); sum += f[2 * i] + f[2 * i + 1]; }
#pragma unroll
    for (int o = 16; o > 0; o >>= 1) sum += __shfl_xor_sync(~0u, sum, o);
    const float mean = sum * (1.f / DM);
    float sq = 0.f;
#pragma unroll
    for (int i = 0; i < 16; i++) { float d = f[i] - mean; sq = fmaf(d, d, sq); }
#pragma unroll
    for (int o = 16; o > 0; o >>= 1) sq += __shfl_xor_sync(~0u, sq, o);
    const float mb = bfr(mean);
    const float vb = bfr(sq * (1.f / DM));
    const float den = bfr(sqrtf(bfr(vb + 1e-5f)));
    const float rinv = 1.f / den;
    uint32_t o[8];
    float r = 0.f;
#pragma unroll
    for (int i = 0; i < 8; i++) {
        float d0 = bfr(f[2 * i] - mb), d1 = bfr(f[2 * i + 1] - mb);
        o[i] = packbf(d0 * rinv, d1 * rinv);
        r = fmaf(bf_lo(o[i]), bf_lo(w[i]), r);
        r = fmaf(bf_hi(o[i]), bf_hi(w[i]), r);
    }
#pragma unroll
    for (int of = 16; of > 0; of >>= 1) r += __shfl_xor_sync(~0u, r, of);
    uint4* xo = reinterpret_cast<uint4*>(g_xn + (size_t)row * DM);
    xo[lane] = make_uint4(o[0], o[1], o[2], o[3]);
    xo[32 + lane] = make_uint4(o[4], o[5], o[6], o[7]);
    if (lane == 0) g_r[row] = r;
    TL(0, 3);
}

constexpr int K1_ST = 5;
constexpr int K1_STAGE = 16384 + 24576;
constexpr int K1_SMEM = K1_ST * K1_STAGE + 1024 + 128;

__device__ __forceinline__ void wgmma_n192(float (&d)[96], uint64_t da, uint64_t db, int scale_d) {
    asm volatile("{\n.reg .pred p;\nsetp.ne.b32 p, %98, 0;\n"
        "wgmma.mma_async.sync.aligned.m64n192k16.f32.bf16.bf16 "
        "{%0,%1,%2,%3,%4,%5,%6,%7,%8,%9,%10,%11,%12,%13,%14,%15,%16,%17,%18,%19,%20,%21,%22,%23,"
        "%24,%25,%26,%27,%28,%29,%30,%31,%32,%33,%34,%35,%36,%37,%38,%39,%40,%41,%42,%43,%44,%45,%46,%47,"
        "%48,%49,%50,%51,%52,%53,%54,%55,%56,%57,%58,%59,%60,%61,%62,%63,%64,%65,%66,%67,%68,%69,%70,%71,"
        "%72,%73,%74,%75,%76,%77,%78,%79,%80,%81,%82,%83,%84,%85,%86,%87,%88,%89,%90,%91,%92,%93,%94,%95}, "
        "%96, %97, p, 1, 1, 0, 1;\n}"
        : "+f"(d[0]), "+f"(d[1]), "+f"(d[2]), "+f"(d[3]), "+f"(d[4]), "+f"(d[5]), "+f"(d[6]), "+f"(d[7]),
          "+f"(d[8]), "+f"(d[9]), "+f"(d[10]), "+f"(d[11]), "+f"(d[12]), "+f"(d[13]), "+f"(d[14]), "+f"(d[15]),
          "+f"(d[16]), "+f"(d[17]), "+f"(d[18]), "+f"(d[19]), "+f"(d[20]), "+f"(d[21]), "+f"(d[22]), "+f"(d[23]),
          "+f"(d[24]), "+f"(d[25]), "+f"(d[26]), "+f"(d[27]), "+f"(d[28]), "+f"(d[29]), "+f"(d[30]), "+f"(d[31]),
          "+f"(d[32]), "+f"(d[33]), "+f"(d[34]), "+f"(d[35]), "+f"(d[36]), "+f"(d[37]), "+f"(d[38]), "+f"(d[39]),
          "+f"(d[40]), "+f"(d[41]), "+f"(d[42]), "+f"(d[43]), "+f"(d[44]), "+f"(d[45]), "+f"(d[46]), "+f"(d[47]),
          "+f"(d[48]), "+f"(d[49]), "+f"(d[50]), "+f"(d[51]), "+f"(d[52]), "+f"(d[53]), "+f"(d[54]), "+f"(d[55]),
          "+f"(d[56]), "+f"(d[57]), "+f"(d[58]), "+f"(d[59]), "+f"(d[60]), "+f"(d[61]), "+f"(d[62]), "+f"(d[63]),
          "+f"(d[64]), "+f"(d[65]), "+f"(d[66]), "+f"(d[67]), "+f"(d[68]), "+f"(d[69]), "+f"(d[70]), "+f"(d[71]),
          "+f"(d[72]), "+f"(d[73]), "+f"(d[74]), "+f"(d[75]), "+f"(d[76]), "+f"(d[77]), "+f"(d[78]), "+f"(d[79]),
          "+f"(d[80]), "+f"(d[81]), "+f"(d[82]), "+f"(d[83]), "+f"(d[84]), "+f"(d[85]), "+f"(d[86]), "+f"(d[87]),
          "+f"(d[88]), "+f"(d[89]), "+f"(d[90]), "+f"(d[91]), "+f"(d[92]), "+f"(d[93]), "+f"(d[94]), "+f"(d[95])
        : "l"(da), "l"(db), "r"(scale_d));
}

__global__ void __launch_bounds__(288, 1) qkv_kernel(const __grid_constant__ CUtensorMap mapA, const __grid_constant__ CUtensorMap mapB) {
    extern __shared__ uint8_t smem_raw[];
    const uint32_t sbase = (smem_u32(smem_raw) + 1023u) & ~1023u;
    const uint32_t bars = sbase + K1_ST * K1_STAGE;
    const int warp = threadIdx.x >> 5, lane = threadIdx.x & 31;
    const int nb = blockIdx.x & 7, mb = blockIdx.x >> 3;
    TL(1, 0);
    if (threadIdx.x == 0) {
        for (int s = 0; s < K1_ST; s++) { mbar_init(bars + 8 * s, 1); mbar_init(bars + 8 * (K1_ST + s), 2); }
        fence_barrier_init();
    }
    __syncthreads();
    if (warp == 8) {
        if (lane == 0) {
            for (int c = 0; c < K1_ST; c++) {
                const uint32_t st = sbase + c * K1_STAGE;
                mbar_expect_tx(bars + 8 * c, K1_STAGE);
                for (int j = 0; j < 3; j++) tma2d(st + 16384 + j * 8192, &mapB, bars + 8 * c, nb * 192 + j * 64, c * 64);
            }
            pdl_wait();
            pdl_launch();
            for (int c = 0; c < K1_ST; c++) tma2d(sbase + c * K1_STAGE, &mapA, bars + 8 * c, c * 64, mb * 128);
            for (int c = K1_ST; c < 8; c++) {
                const int s = c - K1_ST;
                const uint32_t st = sbase + s * K1_STAGE;
                mbar_wait(bars + 8 * (K1_ST + s), 0);
                mbar_expect_tx(bars + 8 * s, K1_STAGE);
                tma2d(st, &mapA, bars + 8 * s, c * 64, mb * 128);
                for (int j = 0; j < 3; j++) tma2d(st + 16384 + j * 8192, &mapB, bars + 8 * s, nb * 192 + j * 64, c * 64);
            }
        }
        return;
    }
    const int wg = warp >> 2;
    float acc[96];
#pragma unroll
    for (int i = 0; i < 96; i++) acc[i] = 0.f;
#pragma unroll 1
    for (int c = 0; c < 8; c++) {
        const int s = c < K1_ST ? c : c - K1_ST;
        const uint32_t st = sbase + s * K1_STAGE;
        mbar_wait(bars + 8 * s, c < K1_ST ? 0 : 1);
        if (c == 0) TL(1, 1);
        const uint64_t da = mkdesc(st + wg * 8192, 16, 1024, 1);
        const uint64_t db = mkdesc(st + 16384, 8192, 1024, 1);
        WG_FENCE();
#pragma unroll
        for (int k = 0; k < 4; k++) wgmma_n192(acc, da + k * 2, db + k * 128, (c | k) != 0);
        WG_COMMIT();
        if (c + K1_ST < 8 + 1) {
            WG_WAIT(1);
            if (c >= 1 && (threadIdx.x & 127) == 0) mbar_arrive(bars + 8 * (K1_ST + c - 1));
        }
    }
    WG_WAIT(0);
    TL(1, 2);
    const int g = lane >> 2, t = lane & 3;
    const int mt = mb * 8 + warp;
#pragma unroll
    for (int hh = 0; hh < 12; hh++) {
        const int gh = nb * 12 + hh;
        const float* a = &acc[hh * 8];
        if (gh < 32) {
            uint4 v;
            v.x = packbf(a[0], a[1]); v.y = packbf(a[2], a[3]);
            v.z = packbf(a[4], a[5]); v.w = packbf(a[6], a[7]);
            g_q[(gh * 128 + mt) * 32 + lane] = v;
        } else {
            uint32_t* dst = reinterpret_cast<uint32_t*>(gh < 64 ? g_k + (gh - 32) * 4096 : g_v + (gh - 64) * 4096);
            const float ks = gh < 64 ? 5.421010862427522e-20f : 1.0f;
            const int off = (mt * 16 + g) * 4 + t;
            dst[off] = packbf(a[0] * ks, a[1] * ks);
            dst[off + 32] = packbf(a[2] * ks, a[3] * ks);
            dst[8192 + off] = packbf(a[4] * ks, a[5] * ks);
            dst[8192 + off + 32] = packbf(a[6] * ks, a[7] * ks);
        }
    }
    TL(1, 3);
}

constexpr float SHIFT = 90.0f;
constexpr float QS = 0.25f * 1.4426950408889634f * 18446744073709551616.0f;
constexpr float scq = 0.25f * 1.4426950408889634f * 3.3087224502121107e-24f;
constexpr int K2_SMEM = 163840 + 1024 + 128;

__device__ __forceinline__ uint32_t polyexp(float lo, float hi) {
    uint32_t w, g, q, h;
    asm("cvt.pack.sat.s16.s32 %0, %1, %2;" : "=r"(w) : "r"(__float_as_uint(hi)), "r"(__float_as_uint(lo)));
    g = w & 0x007F007Fu;
    asm("fma.rn.f16x2 %0, %1, %2, %3;" : "=r"(q) : "r"(g), "r"(0xf940f940u), "r"(0x35513551u));
    asm("mul.rn.f16x2 %0, %1, %2;" : "=r"(h) : "r"(q), "r"(g));
    return w - h;
}
__device__ __forceinline__ void qk64(float (&s)[32], const uint32_t (&q)[4], uint64_t db) {
    asm volatile("wgmma.mma_async.sync.aligned.m64n64k16.f32.bf16.bf16 "
        "{%0,%1,%2,%3,%4,%5,%6,%7,%8,%9,%10,%11,%12,%13,%14,%15,%16,%17,%18,%19,%20,%21,%22,%23,%24,%25,%26,%27,%28,%29,%30,%31}, "
        "{%32,%33,%34,%35}, %36, 0, 1, 1, 0;"
        : "=f"(s[0]), "=f"(s[1]), "=f"(s[2]), "=f"(s[3]), "=f"(s[4]), "=f"(s[5]), "=f"(s[6]), "=f"(s[7]),
          "=f"(s[8]), "=f"(s[9]), "=f"(s[10]), "=f"(s[11]), "=f"(s[12]), "=f"(s[13]), "=f"(s[14]), "=f"(s[15]),
          "=f"(s[16]), "=f"(s[17]), "=f"(s[18]), "=f"(s[19]), "=f"(s[20]), "=f"(s[21]), "=f"(s[22]), "=f"(s[23]),
          "=f"(s[24]), "=f"(s[25]), "=f"(s[26]), "=f"(s[27]), "=f"(s[28]), "=f"(s[29]), "=f"(s[30]), "=f"(s[31])
        : "r"(q[0]), "r"(q[1]), "r"(q[2]), "r"(q[3]), "l"(db));
}
__device__ __forceinline__ void pv24(float (&o)[12], uint32_t a0, uint32_t a1, uint32_t a2, uint32_t a3, uint64_t db) {
    asm volatile("wgmma.mma_async.sync.aligned.m64n24k16.f32.bf16.bf16 "
        "{%0,%1,%2,%3,%4,%5,%6,%7,%8,%9,%10,%11}, {%12,%13,%14,%15}, %16, 1, 1, 1, 1;"
        : "+f"(o[0]), "+f"(o[1]), "+f"(o[2]), "+f"(o[3]), "+f"(o[4]), "+f"(o[5]), "+f"(o[6]), "+f"(o[7]),
          "+f"(o[8]), "+f"(o[9]), "+f"(o[10]), "+f"(o[11])
        : "r"(a0), "r"(a1), "r"(a2), "r"(a3), "l"(db));
}

__device__ __forceinline__ void attn_safe(float (&o)[12], const uint32_t (&q)[4], uint64_t kdesc0, uint64_t vdesc0) {
    float s[32];
    float m0 = -INFINITY, m1 = -INFINITY;
#pragma unroll
    for (int i = 0; i < 12; i++) o[i] = 0.f;
#pragma unroll 1
    for (int j = 0; j < 32; j++) {
        WG_FENCE();
        qk64(s, q, kdesc0 + (uint64_t)(j * 64));
        WG_COMMIT(); WG_WAIT(0);
        float n0 = m0, n1 = m1;
#pragma unroll
        for (int i = 0; i < 8; i++) { n0 = fmaxf(n0, fmaxf(s[4 * i], s[4 * i + 1])); n1 = fmaxf(n1, fmaxf(s[4 * i + 2], s[4 * i + 3])); }
        n0 = fmaxf(n0, __shfl_xor_sync(~0u, n0, 1)); n0 = fmaxf(n0, __shfl_xor_sync(~0u, n0, 2));
        n1 = fmaxf(n1, __shfl_xor_sync(~0u, n1, 1)); n1 = fmaxf(n1, __shfl_xor_sync(~0u, n1, 2));
        const float c0 = ex2((m0 - n0) * QS), c1 = ex2((m1 - n1) * QS);
        m0 = n0; m1 = n1;
#pragma unroll
        for (int i = 0; i < 3; i++) { o[4 * i] *= c0; o[4 * i + 1] *= c0; o[4 * i + 2] *= c1; o[4 * i + 3] *= c1; }
        uint32_t p[16];
#pragma unroll
        for (int i = 0; i < 8; i++) {
            p[2 * i] = packbf(ex2((s[4 * i] - m0) * QS), ex2((s[4 * i + 1] - m0) * QS));
            p[2 * i + 1] = packbf(ex2((s[4 * i + 2] - m1) * QS), ex2((s[4 * i + 3] - m1) * QS));
        }
        WG_FENCE();
#pragma unroll
        for (int kk = 0; kk < 4; kk++) pv24(o, p[4 * kk], p[4 * kk + 1], p[4 * kk + 2], p[4 * kk + 3], vdesc0 + (uint64_t)(j * 64 + kk * 16));
        WG_COMMIT(); WG_WAIT(0);
    }
}

__device__ __forceinline__ void attn_store(const float (&o)[12], int head, int m64, int warp, int lane) {
    const int g = lane >> 2, t = lane & 3;
    const int row = m64 * 64 + warp * 16 + g;
    const float i0 = 1.f / o[8], i1 = 1.f / o[10];
    uint32_t* p0 = reinterpret_cast<uint32_t*>(g_o + (size_t)row * DM + head * 16 + t * 2);
    uint32_t* p1 = reinterpret_cast<uint32_t*>(g_o + (size_t)(row + 8) * DM + head * 16 + t * 2);
    p0[0] = packbf(o[0] * i0, o[1] * i0); p0[4] = packbf(o[4] * i0, o[5] * i0);
    p1[0] = packbf(o[2] * i1, o[3] * i1); p1[4] = packbf(o[6] * i1, o[7] * i1);
}

constexpr int FS_N = 5;
constexpr int FS_BYTES = 29696;
__device__ void ffn_block(int c, uint8_t* smem, uint32_t sbase, const __nv_bfloat16* __restrict__ wg, const __nv_bfloat16* __restrict__ wu,
                          const __nv_bfloat16* __restrict__ wd) {
    const int tid = threadIdx.x, warp = tid >> 5, lane = tid & 31;
    float* sx = reinterpret_cast<float*>(smem + FS_N * FS_BYTES);
    float* sh = sx + 1024;
    const uint32_t bars = sbase + FS_N * FS_BYTES + 8192;
    __shared__ float tv[32]; __shared__ int ti[32];
    __shared__ int ssel[2];
    if (tid == 0) { for (int i = 0; i < FS_N; i++) mbar_init(bars + 8 * i, 1); fence_barrier_init(); }
    __syncthreads();
    auto issue = [&](int item) {
        const int slot = item % FS_N;
        const uint32_t dst = sbase + slot * FS_BYTES, bar = bars + 8 * slot;
        if (item < 32) {
            if (lane == 0) mbar_expect_tx(bar, 32 * 896);
            __syncwarp();
            const __nv_bfloat16* src = (lane < 16 ? wg : wu) + (size_t)(item * 16 + (lane & 15)) * FF + c * 448;
            bulk_g2s(dst + lane * 912, src, 896, bar);
        } else {
            if (lane == 0) mbar_expect_tx(bar, 28 * 1024);
            __syncwarp();
            if (lane < 28) bulk_g2s(dst + lane * 1040, wd + ((size_t)c * 448 + (item - 32) * 28 + lane) * DM, 1024, bar);
        }
    };
    if (warp == 0) for (int i = 0; i < FS_N; i++) issue(i);
    float b1 = -INFINITY, b2 = -INFINITY; int i1 = 0x7fffffff, i2 = 0x7fffffff;
    auto push = [&](float v, int i) {
        if (v > b1 || (v == b1 && i < i1)) { b2 = b1; i2 = i1; b1 = v; i1 = i; }
        else if (v > b2 || (v == b2 && i < i2)) { b2 = v; i2 = i; }
    };
    {
        const float4 rv = reinterpret_cast<const float4*>(g_r)[tid];
        push(rv.x, 4 * tid); push(rv.y, 4 * tid + 1); push(rv.z, 4 * tid + 2); push(rv.w, 4 * tid + 3);
    }
#pragma unroll
    for (int o = 16; o > 0; o >>= 1) {
        float v1 = __shfl_xor_sync(~0u, b1, o), v2 = __shfl_xor_sync(~0u, b2, o);
        int j1 = __shfl_xor_sync(~0u, i1, o), j2 = __shfl_xor_sync(~0u, i2, o);
        push(v1, j1); push(v2, j2);
    }
    if (lane == 0) { tv[2 * warp] = b1; ti[2 * warp] = i1; tv[2 * warp + 1] = b2; ti[2 * warp + 1] = i2; }
    __syncthreads();
    if (warp == 1) {
        b1 = tv[lane]; i1 = ti[lane]; b2 = -INFINITY; i2 = 0x7fffffff;
#pragma unroll
        for (int o = 16; o > 0; o >>= 1) {
            float v1 = __shfl_xor_sync(~0u, b1, o), v2 = __shfl_xor_sync(~0u, b2, o);
            int j1 = __shfl_xor_sync(~0u, i1, o), j2 = __shfl_xor_sync(~0u, i2, o);
            push(v1, j1); push(v2, j2);
        }
        if (lane == 0) {
            i1 = min(max(i1, 0), S_LEN - 1); i2 = min(max(i2, 0), S_LEN - 1);
            ssel[0] = i1; ssel[1] = i2;
            if (c == 0) {
                g_sel[0] = i1; g_sel[1] = i2;
                g_gate[0] = bfr(1.f / (1.f + __expf(-bfr(b1))));
                g_gate[1] = bfr(1.f / (1.f + __expf(-bfr(b2))));
            }
        }
    }
    __syncthreads();
    {
        const uint32_t v = *reinterpret_cast<const uint32_t*>(g_xn + (size_t)ssel[tid >> 8] * DM + (tid & 255) * 2);
        sx[2 * tid] = bf_lo(v); sx[2 * tid + 1] = bf_hi(v);
    }
    __syncthreads();
    TL(2, 1);
    const int kg = tid & 7, ch = tid >> 3;
    {
        float ag[2][8], au[2][8];
#pragma unroll
        for (int j = 0; j < 8; j++) { ag[0][j] = ag[1][j] = au[0][j] = au[1][j] = 0.f; }
#pragma unroll 1
        for (int it = 0; it < 32; it++) {
            const int slot = it % FS_N;
            mbar_wait(bars + 8 * slot, (it / FS_N) & 1);
            if (ch < 56) {
                const uint8_t* base = smem + slot * FS_BYTES + ch * 16;
#pragma unroll
                for (int h = 0; h < 2; h++) {
                    const int r = kg + h * 8;
                    const uint4 vg = *reinterpret_cast<const uint4*>(base + r * 912);
                    const uint4 vu = *reinterpret_cast<const uint4*>(base + (16 + r) * 912);
                    const float x0 = sx[it * 16 + r], x1 = sx[512 + it * 16 + r];
                    const uint32_t gw[4] = {vg.x, vg.y, vg.z, vg.w}, uw[4] = {vu.x, vu.y, vu.z, vu.w};
#pragma unroll
                    for (int j = 0; j < 4; j++) {
                        const float g0 = bf_lo(gw[j]), g1 = bf_hi(gw[j]), u0 = bf_lo(uw[j]), u1 = bf_hi(uw[j]);
                        ag[0][2 * j] = fmaf(x0, g0, ag[0][2 * j]); ag[0][2 * j + 1] = fmaf(x0, g1, ag[0][2 * j + 1]);
                        ag[1][2 * j] = fmaf(x1, g0, ag[1][2 * j]); ag[1][2 * j + 1] = fmaf(x1, g1, ag[1][2 * j + 1]);
                        au[0][2 * j] = fmaf(x0, u0, au[0][2 * j]); au[0][2 * j + 1] = fmaf(x0, u1, au[0][2 * j + 1]);
                        au[1][2 * j] = fmaf(x1, u0, au[1][2 * j]); au[1][2 * j + 1] = fmaf(x1, u1, au[1][2 * j + 1]);
                    }
                }
            }
            __syncthreads();
            if (warp == 0) issue(it + FS_N);
        }
#pragma unroll
        for (int j = 0; j < 8; j++) {
#pragma unroll
            for (int o = 1; o < 8; o <<= 1) {
                ag[0][j] += __shfl_xor_sync(~0u, ag[0][j], o); ag[1][j] += __shfl_xor_sync(~0u, ag[1][j], o);
                au[0][j] += __shfl_xor_sync(~0u, au[0][j], o); au[1][j] += __shfl_xor_sync(~0u, au[1][j], o);
            }
        }
        if (ch < 56 && kg < 2) {
#pragma unroll
            for (int j = 0; j < 8; j++) {
                const float gs = bfr(kg ? ag[1][j] : ag[0][j]), us = bfr(kg ? au[1][j] : au[0][j]);
                const float sg = bfr(gs / (1.f + __expf(-gs)));
                sh[kg * 448 + ch * 8 + j] = bfr(sg * us);
            }
        }
        __syncthreads();
    }
    TL(2, 2);
    {
        float a[2][8];
#pragma unroll
        for (int j = 0; j < 8; j++) a[0][j] = a[1][j] = 0.f;
#pragma unroll 1
        for (int it = 32; it < 48; it++) {
            const int slot = it % FS_N;
            mbar_wait(bars + 8 * slot, (it / FS_N) & 1);
            const uint8_t* base = smem + slot * FS_BYTES + ch * 16;
#pragma unroll
            for (int h = 0; h < 4; h++) {
                const int r = kg + h * 8;
                if (r < 28) {
                    const uint4 v = *reinterpret_cast<const uint4*>(base + r * 1040);
                    const float h0 = sh[(it - 32) * 28 + r], h1 = sh[448 + (it - 32) * 28 + r];
                    const uint32_t w[4] = {v.x, v.y, v.z, v.w};
#pragma unroll
                    for (int j = 0; j < 4; j++) {
                        const float w0 = bf_lo(w[j]), w1 = bf_hi(w[j]);
                        a[0][2 * j] = fmaf(h0, w0, a[0][2 * j]); a[0][2 * j + 1] = fmaf(h0, w1, a[0][2 * j + 1]);
                        a[1][2 * j] = fmaf(h1, w0, a[1][2 * j]); a[1][2 * j + 1] = fmaf(h1, w1, a[1][2 * j + 1]);
                    }
                }
            }
            __syncthreads();
            if (warp == 0 && it + FS_N < 48) issue(it + FS_N);
        }
#pragma unroll
        for (int j = 0; j < 8; j++) {
#pragma unroll
            for (int o = 1; o < 8; o <<= 1) { a[0][j] += __shfl_xor_sync(~0u, a[0][j], o); a[1][j] += __shfl_xor_sync(~0u, a[1][j], o); }
        }
        if (kg < 2) {
#pragma unroll
            for (int j = 0; j < 8; j++) g_ypart[c * 1024 + kg * 512 + ch * 8 + j] = kg ? a[1][j] : a[0][j];
        }
    }
}

__global__ void __launch_bounds__(512, 1) attn_kernel(const __nv_bfloat16* __restrict__ wg_, const __nv_bfloat16* __restrict__ wu_,
                                                      const __nv_bfloat16* __restrict__ wd_, float sc) {
    extern __shared__ uint8_t smem_raw[];
    const uint32_t sraw = smem_u32(smem_raw);
    const uint32_t sbase = (sraw + 1023u) & ~1023u;
    uint8_t* sptr = smem_raw + (sbase - sraw);
    TL(2, 0);
    if (blockIdx.x < 4) {
        pdl_launch();
        ffn_block(blockIdx.x, sptr, sbase, wg_, wu_, wd_);
        TL(2, 3);
        return;
    }
    const uint32_t bars = sbase + 163840;
    const int head = (blockIdx.x - 4) >> 2, quarter = blockIdx.x & 3;
    const int wg = threadIdx.x >> 7, warp = (threadIdx.x >> 5) & 3, lane = threadIdx.x & 31;
    if (threadIdx.x == 0) {
        for (int c = 0; c < 8; c++) mbar_init(bars + 8 * c, 1);
        fence_barrier_init();
    }
    {
        uint4* ones = reinterpret_cast<uint4*>(sptr + 131072);
        for (int i = threadIdx.x; i < 2048; i += 512) ones[i] = make_uint4(0x3f803f80u, 0x3f803f80u, 0x3f803f80u, 0x3f803f80u);
        fence_proxy_async();
    }
    __syncthreads();
    pdl_wait();
    pdl_launch();
    TL(2, 1);
    if (threadIdx.x == 0) {
        const uint8_t* kp = reinterpret_cast<const uint8_t*>(g_k + head * 4096);
        const uint8_t* vp = reinterpret_cast<const uint8_t*>(g_v + head * 4096);
        for (int c = 0; c < 8; c++) {
            mbar_expect_tx(bars + 8 * c, 16384);
            bulk_g2s(sbase + c * 4096, kp + c * 4096, 4096, bars + 8 * c);
            bulk_g2s(sbase + 32768 + c * 4096, kp + 32768 + c * 4096, 4096, bars + 8 * c);
            bulk_g2s(sbase + 65536 + c * 4096, vp + c * 4096, 4096, bars + 8 * c);
            bulk_g2s(sbase + 98304 + c * 4096, vp + 32768 + c * 4096, 4096, bars + 8 * c);
        }
    }
    const uint64_t kdesc0 = mkdesc(sbase, 32768, 128, 0);
    const uint64_t vdesc0 = mkdesc(sbase + 65536, 128, 32768, 0);
    uint32_t badmask = 0;
#pragma unroll 1
    for (int mt = 0; mt < 2; mt++) {
        const int m64 = quarter * 8 + mt * 4 + wg;
        uint32_t q[4];
        { const uint4 qq = g_q[(head * 128 + m64 * 4 + warp) * 32 + lane]; q[0] = qq.x; q[1] = qq.y; q[2] = qq.z; q[3] = qq.w; }
        float s[32], s2[32], o[12];
#pragma unroll
        for (int i = 0; i < 12; i++) o[i] = 0.f;
        mbar_wait(bars, 0);
        if (mt == 0) TL(2, 2);
        WG_FENCE();
        qk64(s, q, kdesc0);
        WG_COMMIT(); WG_WAIT(0);
        float mx0 = -INFINITY, mx1 = -INFINITY;
#pragma unroll
        for (int i = 0; i < 8; i++) { mx0 = fmaxf(mx0, fmaxf(s[4 * i], s[4 * i + 1])); mx1 = fmaxf(mx1, fmaxf(s[4 * i + 2], s[4 * i + 3])); }
        mx0 = fmaxf(mx0, __shfl_xor_sync(~0u, mx0, 1)); mx0 = fmaxf(mx0, __shfl_xor_sync(~0u, mx0, 2));
        mx1 = fmaxf(mx1, __shfl_xor_sync(~0u, mx1, 1)); mx1 = fmaxf(mx1, __shfl_xor_sync(~0u, mx1, 2));
        float cm0 = -(ceilf(mx0 * QS) + SHIFT), cm1 = -(ceilf(mx1 * QS) + SHIFT);
        float cp0 = (cm0 + 127.f) * sc, cp1 = (cm1 + 127.f) * sc;
        asm volatile("" : "+f"(cm0), "+f"(cm1), "+f"(cp0), "+f"(cp1));
        uint64_t kd = kdesc0, vd = vdesc0;
        auto step = [&](float (&sc_)[32], float (&sn)[32]) {
            kd += 64;
            WG_FENCE();
            qk64(sn, q, kd);
            WG_COMMIT();
#pragma unroll
            for (int kk = 0; kk < 4; kk++) {
                const int i0 = kk * 2, i1 = kk * 2 + 1;
                const uint32_t p0 = packbf(ex2(fmaf(sc_[4 * i0], QS, cm0)), ex2(fmaf(sc_[4 * i0 + 1], QS, cm0)));
                const uint32_t p1 = packbf(ex2(fmaf(sc_[4 * i0 + 2], QS, cm1)), ex2(fmaf(sc_[4 * i0 + 3], QS, cm1)));
                const uint32_t p2 = polyexp(fmaf(sc_[4 * i1], scq, cp0), fmaf(sc_[4 * i1 + 1], scq, cp0));
                const uint32_t p3 = polyexp(fmaf(sc_[4 * i1 + 2], scq, cp1), fmaf(sc_[4 * i1 + 3], scq, cp1));
                WG_FENCE();
                pv24(o, p0, p1, p2, p3, vd);
                vd += 16;
            }
            WG_COMMIT();
            WG_WAIT(1);
        };
#pragma unroll 1
        for (int c = 0; c < 16; c++) {
            if (mt == 0 && (c & 1) == 0 && c < 14) mbar_wait(bars + 4 * c + 8, 0);
            step(s, s2); step(s2, s);
        }
        WG_WAIT(0);
        bool bad = !(o[8] > 0.f) || !(o[10] > 0.f);
#pragma unroll
        for (int i = 0; i < 12; i++) bad = bad || !(fabsf(o[i]) <= 3.0e38f);
        uint32_t anybad;
        asm volatile("{\n.reg .pred p, q;\nsetp.ne.u32 p, %1, 0;\nbarrier.cta.red.or.pred q, %2, 128, p;\nselp.u32 %0, 1, 0, q;\n}"
                     : "=r"(anybad) : "r"((uint32_t)bad), "r"(wg + 1) : "memory");
        badmask |= anybad << mt;
        attn_store(o, head, m64, warp, lane);
    }
#pragma unroll 1
    for (int mt = 0; mt < 2; mt++) {
        if (!((badmask >> mt) & 1)) continue;
        const int m64 = quarter * 8 + mt * 4 + wg;
        uint32_t q[4];
        { const uint4 qq = g_q[(head * 128 + m64 * 4 + warp) * 32 + lane]; q[0] = qq.x; q[1] = qq.y; q[2] = qq.z; q[3] = qq.w; }
        float o[12];
        attn_safe(o, q, mkdesc(sbase, 32768, 128, 0), mkdesc(sbase + 65536, 128, 32768, 0));
        attn_store(o, head, m64, warp, lane);
    }
    TL(2, 3);
}

constexpr int K3_SMEM = 8 * 8192 + 8 * 16384 + 1024 + 128;

__device__ __forceinline__ void wgmma_n64(float (&d)[32], uint64_t da, uint64_t db, int scale_d) {
    asm volatile("{\n.reg .pred p;\nsetp.ne.b32 p, %34, 0;\n"
        "wgmma.mma_async.sync.aligned.m64n64k16.f32.bf16.bf16 "
        "{%0,%1,%2,%3,%4,%5,%6,%7,%8,%9,%10,%11,%12,%13,%14,%15,%16,%17,%18,%19,%20,%21,%22,%23,%24,%25,%26,%27,%28,%29,%30,%31}, "
        "%32, %33, p, 1, 1, 0, 1;\n}"
        : "+f"(d[0]), "+f"(d[1]), "+f"(d[2]), "+f"(d[3]), "+f"(d[4]), "+f"(d[5]), "+f"(d[6]), "+f"(d[7]),
          "+f"(d[8]), "+f"(d[9]), "+f"(d[10]), "+f"(d[11]), "+f"(d[12]), "+f"(d[13]), "+f"(d[14]), "+f"(d[15]),
          "+f"(d[16]), "+f"(d[17]), "+f"(d[18]), "+f"(d[19]), "+f"(d[20]), "+f"(d[21]), "+f"(d[22]), "+f"(d[23]),
          "+f"(d[24]), "+f"(d[25]), "+f"(d[26]), "+f"(d[27]), "+f"(d[28]), "+f"(d[29]), "+f"(d[30]), "+f"(d[31])
        : "l"(da), "l"(db), "r"(scale_d));
}

__global__ void __launch_bounds__(256, 1) oproj_kernel(const __grid_constant__ CUtensorMap mapA, const __grid_constant__ CUtensorMap mapB,
                                                       const __nv_bfloat16* __restrict__ x, __nv_bfloat16* __restrict__ out) {
    extern __shared__ uint8_t smem_raw[];
    const uint32_t sbase = (smem_u32(smem_raw) + 1023u) & ~1023u;
    const uint32_t sA = sbase, sB = sbase + 8 * 8192, bars = sbase + 8 * 8192 + 8 * 16384;
    const int warp = threadIdx.x >> 5, lane = threadIdx.x & 31, wg = warp >> 2;
    const int nb = blockIdx.x & 3, mb = blockIdx.x >> 2;
    TL(3, 0);
    if (threadIdx.x == 0) {
        for (int c = 0; c < 8; c++) mbar_init(bars + 8 * c, 1);
        fence_barrier_init();
        for (int c = 0; c < 8; c++) {
            mbar_expect_tx(bars + 8 * c, 8192 + 16384);
            tma2d(sB + c * 16384, &mapB, bars + 8 * c, nb * 128, c * 64);
            tma2d(sB + c * 16384 + 8192, &mapB, bars + 8 * c, nb * 128 + 64, c * 64);
        }
    }
    const int g = lane >> 2, t = lane & 3;
    const int row0 = mb * 64 + (warp & 3) * 16 + g;
    const int col0 = nb * 128 + wg * 64 + t * 2;
    uint32_t xv[16], nv[16];
#pragma unroll
    for (int i = 0; i < 8; i++) {
        xv[2 * i] = *reinterpret_cast<const uint32_t*>(x + (size_t)row0 * DM + col0 + i * 8);
        xv[2 * i + 1] = *reinterpret_cast<const uint32_t*>(x + (size_t)(row0 + 8) * DM + col0 + i * 8);
        nv[2 * i] = *reinterpret_cast<const uint32_t*>(g_xn + (size_t)row0 * DM + col0 + i * 8);
        nv[2 * i + 1] = *reinterpret_cast<const uint32_t*>(g_xn + (size_t)(row0 + 8) * DM + col0 + i * 8);
    }
    __syncthreads();
    pdl_wait();
    TL(3, 1);
    if (threadIdx.x == 0) {
        for (int c = 0; c < 8; c++) tma2d(sA + c * 8192, &mapA, bars + 8 * c, c * 64, mb * 64);
    }
    float acc[32];
#pragma unroll
    for (int i = 0; i < 32; i++) acc[i] = 0.f;
#pragma unroll 1
    for (int c = 0; c < 8; c++) {
        mbar_wait(bars + 8 * c, 0);
        const uint64_t da = mkdesc(sA + c * 8192, 16, 1024, 1);
        const uint64_t db = mkdesc(sB + c * 16384 + wg * 8192, 8192, 1024, 1);
        WG_FENCE();
#pragma unroll
        for (int k = 0; k < 4; k++) wgmma_n64(acc, da + k * 2, db + k * 128, (c | k) != 0);
        WG_COMMIT();
    }
    const int sel0 = g_sel[0], sel1 = g_sel[1];
    WG_WAIT(0);
    TL(3, 2);
#pragma unroll
    for (int h = 0; h < 2; h++) {
        const int row = row0 + h * 8;
        const int which = row == sel0 ? 0 : (row == sel1 ? 1 : -1);
#pragma unroll
        for (int i = 0; i < 8; i++) {
            const int col = col0 + i * 8;
            float b0 = bf_lo(nv[2 * i + h]), b1 = bf_hi(nv[2 * i + h]);
            if (which >= 0) {
                float y0 = 0.f, y1 = 0.f;
#pragma unroll
                for (int c = 0; c < 4; c++) { y0 += g_ypart[c * 1024 + which * 512 + col]; y1 += g_ypart[c * 1024 + which * 512 + col + 1]; }
                const float gt = g_gate[which];
                b0 = bfr(b0 + bfr(bfr(y0) * gt)); b1 = bfr(b1 + bfr(bfr(y1) * gt));
            }
            const float t0 = bfr(bf_lo(xv[2 * i + h]) + bfr(acc[4 * i + 2 * h]));
            const float t1 = bfr(bf_hi(xv[2 * i + h]) + bfr(acc[4 * i + 2 * h + 1]));
            *reinterpret_cast<uint32_t*>(out + (size_t)row * DM + col) = packbf(t0 + b0, t1 + b1);
        }
    }
    TL(3, 3);
}

typedef CUresult (*EncodeFn)(CUtensorMap*, CUtensorMapDataType, cuuint32_t, void*, const cuuint64_t*, const cuuint64_t*,
                             const cuuint32_t*, const cuuint32_t*, CUtensorMapInterleave, CUtensorMapSwizzle,
                             CUtensorMapL2promotion, CUtensorMapFloatOOBfill);

void make_map(EncodeFn fn, CUtensorMap* m, const void* ptr, uint64_t inner, uint64_t outer, uint32_t box_inner, uint32_t box_outer) {
    cuuint64_t dims[2] = {inner, outer};
    cuuint64_t strides[1] = {inner * 2};
    cuuint32_t box[2] = {box_inner, box_outer};
    cuuint32_t es[2] = {1, 1};
    fn(m, CU_TENSOR_MAP_DATA_TYPE_BFLOAT16, 2, const_cast<void*>(ptr), dims, strides, box, es, CU_TENSOR_MAP_INTERLEAVE_NONE,
       CU_TENSOR_MAP_SWIZZLE_128B, CU_TENSOR_MAP_L2_PROMOTION_L2_256B, CU_TENSOR_MAP_FLOAT_OOB_FILL_NONE);
}

template <typename... KArgs, typename... Args>
void launch(void (*kern)(KArgs...), int grid, int block, int smem, bool pdl, Args... args) {
    cudaLaunchConfig_t cfg = {};
    cfg.gridDim = dim3(grid); cfg.blockDim = dim3(block); cfg.dynamicSmemBytes = smem; cfg.stream = cudaStreamPerThread;
    cudaLaunchAttribute at[1];
    at[0].id = cudaLaunchAttributeProgrammaticStreamSerialization;
    at[0].val.programmaticStreamSerializationAllowed = 1;
    cfg.attrs = at; cfg.numAttrs = pdl ? 1 : 0;
    cudaLaunchKernelEx(&cfg, kern, KArgs(args)...);
}

}

extern "C" void kernel_launch(void* const* d_in, const int* in_sizes, int n_in, void* d_out, int out_size) {
    const __nv_bfloat16* x = (const __nv_bfloat16*)d_in[0];
    const __nv_bfloat16* wqkv = (const __nv_bfloat16*)d_in[1];
    const __nv_bfloat16* wo = (const __nv_bfloat16*)d_in[2];
    const __nv_bfloat16* wr = (const __nv_bfloat16*)d_in[4];
    const __nv_bfloat16* wgate = (const __nv_bfloat16*)d_in[5];
    const __nv_bfloat16* wup = (const __nv_bfloat16*)d_in[6];
    const __nv_bfloat16* wdown = (const __nv_bfloat16*)d_in[7];
    __nv_bfloat16* out = (__nv_bfloat16*)d_out;

    static EncodeFn enc = nullptr;
    static void* p_xn = nullptr; static void* p_o = nullptr;
    if (!enc) {
        void* fn = nullptr; cudaDriverEntryPointQueryResult qr;
        cudaGetDriverEntryPoint("cuTensorMapEncodeTiled", &fn, cudaEnableDefault, &qr);
        enc = (EncodeFn)fn;
        cudaGetSymbolAddress(&p_xn, g_xn);
        cudaGetSymbolAddress(&p_o, g_o);
        cudaFuncSetAttribute(qkv_kernel, cudaFuncAttributeMaxDynamicSharedMemorySize, K1_SMEM);
        cudaFuncSetAttribute(attn_kernel, cudaFuncAttributeMaxDynamicSharedMemorySize, K2_SMEM);
        cudaFuncSetAttribute(oproj_kernel, cudaFuncAttributeMaxDynamicSharedMemorySize, K3_SMEM);
    }
    CUtensorMap mXn, mWqkv, mO, mWo;
    make_map(enc, &mXn, p_xn, DM, S_LEN, 64, 128);
    make_map(enc, &mWqkv, wqkv, 3 * DM, DM, 64, 64);
    make_map(enc, &mO, p_o, DM, S_LEN, 64, 64);
    make_map(enc, &mWo, wo, DM, DM, 64, 64);

    union { uint32_t u; float f; } scu; scu.u = 128u;

    launch(ln_kernel, S_LEN / 8, 256, 0, false, x, wr);
    launch(qkv_kernel, 128, 288, K1_SMEM, true, mXn, mWqkv);
    launch(attn_kernel, 132, 512, K2_SMEM, true, wgate, wup, wdown, scu.f);
    launch(oproj_kernel, 128, 256, K3_SMEM, true, mO, mWo, x, out);
}
```

```cpp
#include <cuda_runtime.h>
#include <cuda_bf16.h>
#include <cuda.h>
#include <stdint.h>
#include <type_traits>

namespace {

constexpr int S_LEN = 2048;
constexpr int DM = 512;
constexpr int NH = 32;
constexpr int FF = 1792;

__device__ __align__(1024) __nv_bfloat16 g_xn[S_LEN * DM];
__device__ __align__(16) float g_r[S_LEN];
__device__ __align__(1024) uint4 g_q[NH * 128 * 32];
__device__ __align__(1024) uint4 g_k[NH * 4096];
__device__ __align__(1024) uint4 g_v[NH * 4096];
__device__ __align__(1024) __nv_bfloat16 g_o[S_LEN * DM];
__device__ float g_ypart[4 * 2 * DM];
__device__ int g_sel[2];
__device__ float g_gate[2];

#define TL(k, slot) do {} while (0)

__device__ __forceinline__ uint32_t smem_u32(const void* p) { return (uint32_t)__cvta_generic_to_shared(p); }
__device__ __forceinline__ void pdl_wait() { asm volatile("griddepcontrol.wait;" ::: "memory"); }
__device__ __forceinline__ void pdl_launch() { asm volatile("griddepcontrol.launch_dependents;" ::: "memory"); }
__device__ __forceinline__ void mbar_init(uint32_t bar, uint32_t cnt) {
    asm volatile("mbarrier.init.shared::cta.b64 [%0], %1;" :: "r"(bar), "r"(cnt) : "memory");
}
__device__ __forceinline__ void mbar_expect_tx(uint32_t bar, uint32_t bytes) {
    asm volatile("mbarrier.arrive.expect_tx.shared::cta.b64 _, [%0], %1;" :: "r"(bar), "r"(bytes) : "memory");
}
__device__ __forceinline__ void mbar_arrive(uint32_t bar) {
    asm volatile("mbarrier.arrive.shared::cta.b64 _, [%0];" :: "r"(bar) : "memory");
}
__device__ __forceinline__ void mbar_wait(uint32_t bar, uint32_t parity) {
    asm volatile("{\n.reg .pred p;\n.reg .u32 n;\nmov.u32 n, 0;\n"
                 "WAIT_%=:\n"
                 "mbarrier.try_wait.parity.shared::cta.b64 p, [%0], %1;\n"
                 "@p bra DONE_%=;\n"
                 "add.u32 n, n, 1;\n"
                 "setp.lt.u32 p, n, 4000000;\n"
                 "@p bra WAIT_%=;\n"
                 "trap;\n"
                 "DONE_%=:\n}"
                 :: "r"(bar), "r"(parity) : "memory");
}
__device__ __forceinline__ void fence_barrier_init() { asm volatile("fence.mbarrier_init.release.cluster;" ::: "memory"); }
__device__ __forceinline__ void fence_proxy_async() { asm volatile("fence.proxy.async.shared::cta;" ::: "memory"); }
__device__ __forceinline__ void tma2d(uint32_t dst, const CUtensorMap* map, uint32_t bar, int c0, int c1) {
    asm volatile("cp.async.bulk.tensor.2d.shared::cluster.global.mbarrier::complete_tx::bytes [%0], [%1, {%3, %4}], [%2];"
                 :: "r"(dst), "l"((uint64_t)map), "r"(bar), "r"(c0), "r"(c1) : "memory");
}
__device__ __forceinline__ void bulk_g2s(uint32_t dst, const void* src, uint32_t bytes, uint32_t bar) {
    asm volatile("cp.async.bulk.shared::cluster.global.mbarrier::complete_tx::bytes [%0], [%1], %2, [%3];"
                 :: "r"(dst), "l"((uint64_t)src), "r"(bytes), "r"(bar) : "memory");
}
__device__ __forceinline__ uint64_t mkdesc(uint32_t addr, uint32_t lbo, uint32_t sbo, uint32_t swz) {
    return (uint64_t)((addr & 0x3FFFF) >> 4) | ((uint64_t)(lbo >> 4) << 16) | ((uint64_t)(sbo >> 4) << 32) | ((uint64_t)swz << 62);
}
#define WG_FENCE() asm volatile("wgmma.fence.sync.aligned;" ::: "memory")
#define WG_COMMIT() asm volatile("wgmma.commit_group.sync.aligned;" ::: "memory")
#define WG_WAIT(n) asm volatile("wgmma.wait_group.sync.aligned %0;" :: "n"(n) : "memory")

__device__ __forceinline__ float ex2(float x) { float y; asm("ex2.approx.ftz.f32 %0, %1;" : "=f"(y) : "f"(x)); return y; }
__device__ __forceinline__ uint32_t packbf(float lo, float hi) {
    uint32_t r; asm("cvt.rn.bf16x2.f32 %0, %1, %2;" : "=r"(r) : "f"(hi), "f"(lo)); return r;
}
__device__ __forceinline__ float bf_lo(uint32_t v) { return __uint_as_float(v << 16); }
__device__ __forceinline__ float bf_hi(uint32_t v) { return __uint_as_float(v & 0xffff0000u); }
__device__ __forceinline__ float bfr(float x) { return __bfloat162float(__float2bfloat16_rn(x)); }

__global__ void __launch_bounds__(256) ln_kernel(const __nv_bfloat16* __restrict__ x, const __nv_bfloat16* __restrict__ wr) {
    TL(0, 0);
    pdl_launch();
    const int warp = threadIdx.x >> 5, lane = threadIdx.x & 31;
    const int row = blockIdx.x * 8 + warp;
    const uint4* xr = reinterpret_cast<const uint4*>(x + (size_t)row * DM);
    uint4 a = xr[lane], b = xr[32 + lane];
    const uint4* wp = reinterpret_cast<const uint4*>(wr);
    uint4 wa = wp[lane], wb = wp[32 + lane];
    uint32_t u[8] = {a.x, a.y, a.z, a.w, b.x, b.y, b.z, b.w};
    uint32_t w[8] = {wa.x, wa.y, wa.z, wa.w, wb.x, wb.y, wb.z, wb.w};
    float f[16];
    float sum = 0.f;
#pragma unroll
    for (int i = 0; i < 8; i++) { f[2 * i] = bf_lo(u[i]); f[2 * i + 1] = bf_hi(u[i]); sum += f[2 * i] + f[2 * i + 1]; }
#pragma unroll
    for (int o = 16; o > 0; o >>= 1) sum += __shfl_xor_sync(~0u, sum, o);
    const float mean = sum * (1.f / DM);
    float sq = 0.f;
#pragma unroll
    for (int i = 0; i < 16; i++) { float d = f[i] - mean; sq = fmaf(d, d, sq); }
#pragma unroll
    for (int o = 16; o > 0; o >>= 1) sq += __shfl_xor_sync(~0u, sq, o);
    const float mb = bfr(mean);
    const float vb = bfr(sq * (1.f / DM));
    const float den = bfr(sqrtf(bfr(vb + 1e-5f)));
    const float rinv = 1.f / den;
    uint32_t o[8];
    float r = 0.f;
#pragma unroll
    for (int i = 0; i < 8; i++) {
        float d0 = bfr(f[2 * i] - mb), d1 = bfr(f[2 * i + 1] - mb);
        o[i] = packbf(d0 * rinv, d1 * rinv);
        r = fmaf(bf_lo(o[i]), bf_lo(w[i]), r);
        r = fmaf(bf_hi(o[i]), bf_hi(w[i]), r);
    }
#pragma unroll
    for (int of = 16; of > 0; of >>= 1) r += __shfl_xor_sync(~0u, r, of);
    uint4* xo = reinterpret_cast<uint4*>(g_xn + (size_t)row * DM);
    xo[lane] = make_uint4(o[0], o[1], o[2], o[3]);
    xo[32 + lane] = make_uint4(o[4], o[5], o[6], o[7]);
    if (lane == 0) g_r[row] = r;
    TL(0, 3);
}

constexpr int K1_ST = 5;
constexpr int K1_STAGE = 16384 + 24576;
constexpr int K1_SMEM = K1_ST * K1_STAGE + 1024 + 128;

__device__ __forceinline__ void wgmma_n192(float (&d)[96], uint64_t da, uint64_t db, int scale_d) {
    asm volatile("{\n.reg .pred p;\nsetp.ne.b32 p, %98, 0;\n"
        "wgmma.mma_async.sync.aligned.m64n192k16.f32.bf16.bf16 "
        "{%0,%1,%2,%3,%4,%5,%6,%7,%8,%9,%10,%11,%12,%13,%14,%15,%16,%17,%18,%19,%20,%21,%22,%23,"
        "%24,%25,%26,%27,%28,%29,%30,%31,%32,%33,%34,%35,%36,%37,%38,%39,%40,%41,%42,%43,%44,%45,%46,%47,"
        "%48,%49,%50,%51,%52,%53,%54,%55,%56,%57,%58,%59,%60,%61,%62,%63,%64,%65,%66,%67,%68,%69,%70,%71,"
        "%72,%73,%74,%75,%76,%77,%78,%79,%80,%81,%82,%83,%84,%85,%86,%87,%88,%89,%90,%91,%92,%93,%94,%95}, "
        "%96, %97, p, 1, 1, 0, 1;\n}"
        : "+f"(d[0]), "+f"(d[1]), "+f"(d[2]), "+f"(d[3]), "+f"(d[4]), "+f"(d[5]), "+f"(d[6]), "+f"(d[7]),
          "+f"(d[8]), "+f"(d[9]), "+f"(d[10]), "+f"(d[11]), "+f"(d[12]), "+f"(d[13]), "+f"(d[14]), "+f"(d[15]),
          "+f"(d[16]), "+f"(d[17]), "+f"(d[18]), "+f"(d[19]), "+f"(d[20]), "+f"(d[21]), "+f"(d[22]), "+f"(d[23]),
          "+f"(d[24]), "+f"(d[25]), "+f"(d[26]), "+f"(d[27]), "+f"(d[28]), "+f"(d[29]), "+f"(d[30]), "+f"(d[31]),
          "+f"(d[32]), "+f"(d[33]), "+f"(d[34]), "+f"(d[35]), "+f"(d[36]), "+f"(d[37]), "+f"(d[38]), "+f"(d[39]),
          "+f"(d[40]), "+f"(d[41]), "+f"(d[42]), "+f"(d[43]), "+f"(d[44]), "+f"(d[45]), "+f"(d[46]), "+f"(d[47]),
          "+f"(d[48]), "+f"(d[49]), "+f"(d[50]), "+f"(d[51]), "+f"(d[52]), "+f"(d[53]), "+f"(d[54]), "+f"(d[55]),
          "+f"(d[56]), "+f"(d[57]), "+f"(d[58]), "+f"(d[59]), "+f"(d[60]), "+f"(d[61]), "+f"(d[62]), "+f"(d[63]),
          "+f"(d[64]), "+f"(d[65]), "+f"(d[66]), "+f"(d[67]), "+f"(d[68]), "+f"(d[69]), "+f"(d[70]), "+f"(d[71]),
          "+f"(d[72]), "+f"(d[73]), "+f"(d[74]), "+f"(d[75]), "+f"(d[76]), "+f"(d[77]), "+f"(d[78]), "+f"(d[79]),
          "+f"(d[80]), "+f"(d[81]), "+f"(d[82]), "+f"(d[83]), "+f"(d[84]), "+f"(d[85]), "+f"(d[86]), "+f"(d[87]),
          "+f"(d[88]), "+f"(d[89]), "+f"(d[90]), "+f"(d[91]), "+f"(d[92]), "+f"(d[93]), "+f"(d[94]), "+f"(d[95])
        : "l"(da), "l"(db), "r"(scale_d));
}

__global__ void __launch_bounds__(288, 1) qkv_kernel(const __grid_constant__ CUtensorMap mapA, const __grid_constant__ CUtensorMap mapB) {
    extern __shared__ uint8_t smem_raw[];
    const uint32_t sbase = (smem_u32(smem_raw) + 1023u) & ~1023u;
    const uint32_t bars = sbase + K1_ST * K1_STAGE;
    const int warp = threadIdx.x >> 5, lane = threadIdx.x & 31;
    const int nb = blockIdx.x & 7, mb = blockIdx.x >> 3;
    TL(1, 0);
    if (threadIdx.x == 0) {
        for (int s = 0; s < K1_ST; s++) { mbar_init(bars + 8 * s, 1); mbar_init(bars + 8 * (K1_ST + s), 2); }
        fence_barrier_init();
    }
    __syncthreads();
    if (warp == 8) {
        if (lane == 0) {
            for (int c = 0; c < K1_ST; c++) {
                const uint32_t st = sbase + c * K1_STAGE;
                mbar_expect_tx(bars + 8 * c, K1_STAGE);
                for (int j = 0; j < 3; j++) tma2d(st + 16384 + j * 8192, &mapB, bars + 8 * c, nb * 192 + j * 64, c * 64);
            }
            pdl_wait();
            pdl_launch();
            for (int c = 0; c < K1_ST; c++) tma2d(sbase + c * K1_STAGE, &mapA, bars + 8 * c, c * 64, mb * 128);
            for (int c = K1_ST; c < 8; c++) {
                const int s = c - K1_ST;
                const uint32_t st = sbase + s * K1_STAGE;
                mbar_wait(bars + 8 * (K1_ST + s), 0);
                mbar_expect_tx(bars + 8 * s, K1_STAGE);
                tma2d(st, &mapA, bars + 8 * s, c * 64, mb * 128);
                for (int j = 0; j < 3; j++) tma2d(st + 16384 + j * 8192, &mapB, bars + 8 * s, nb * 192 + j * 64, c * 64);
            }
        }
        return;
    }
    const int wg = warp >> 2;
    float acc[96];
#pragma unroll
    for (int i = 0; i < 96; i++) acc[i] = 0.f;
#pragma unroll 1
    for (int c = 0; c < 8; c++) {
        const int s = c < K1_ST ? c : c - K1_ST;
        const uint32_t st = sbase + s * K1_STAGE;
        mbar_wait(bars + 8 * s, c < K1_ST ? 0 : 1);
        if (c == 0) TL(1, 1);
        const uint64_t da = mkdesc(st + wg * 8192, 16, 1024, 1);
        const uint64_t db = mkdesc(st + 16384, 8192, 1024, 1);
        WG_FENCE();
#pragma unroll
        for (int k = 0; k < 4; k++) wgmma_n192(acc, da + k * 2, db + k * 128, (c | k) != 0);
        WG_COMMIT();
        if (c + K1_ST < 8 + 1) {
            WG_WAIT(1);
            if (c >= 1 && (threadIdx.x & 127) == 0) mbar_arrive(bars + 8 * (K1_ST + c - 1));
        }
    }
    WG_WAIT(0);
    TL(1, 2);
    const int g = lane >> 2, t = lane & 3;
    const int mt = mb * 8 + warp;
#pragma unroll
    for (int hh = 0; hh < 12; hh++) {
        const int gh = nb * 12 + hh;
        const float* a = &acc[hh * 8];
        if (gh < 32) {
            uint4 v;
            v.x = packbf(a[0], a[1]); v.y = packbf(a[2], a[3]);
            v.z = packbf(a[4], a[5]); v.w = packbf(a[6], a[7]);
            g_q[(gh * 128 + mt) * 32 + lane] = v;
        } else {
            uint32_t* dst = reinterpret_cast<uint32_t*>(gh < 64 ? g_k + (gh - 32) * 4096 : g_v + (gh - 64) * 4096);
            const float ks = gh < 64 ? 5.421010862427522e-20f : 1.0f;
            const int off = (mt * 16 + g) * 4 + t;
            dst[off] = packbf(a[0] * ks, a[1] * ks);
            dst[off + 32] = packbf(a[2] * ks, a[3] * ks);
            dst[8192 + off] = packbf(a[4] * ks, a[5] * ks);
            dst[8192 + off + 32] = packbf(a[6] * ks, a[7] * ks);
        }
    }
    TL(1, 3);
}

constexpr float SHIFT = 90.0f;
constexpr float QS = 0.25f * 1.4426950408889634f * 18446744073709551616.0f;
constexpr float scq = 0.25f * 1.4426950408889634f * 3.3087224502121107e-24f;
constexpr int K2_SMEM = 163840 + 1024 + 128;

__device__ __forceinline__ uint32_t polyexp(float lo, float hi) {
    uint32_t w, g, q, h;
    asm("cvt.pack.sat.s16.s32 %0, %1, %2;" : "=r"(w) : "r"(__float_as_uint(hi)), "r"(__float_as_uint(lo)));
    g = w & 0x007F007Fu;
    asm("fma.rn.f16x2 %0, %1, %2, %3;" : "=r"(q) : "r"(g), "r"(0xf940f940u), "r"(0x35513551u));
    asm("mul.rn.f16x2 %0, %1, %2;" : "=r"(h) : "r"(q), "r"(g));
    return w - h;
}
__device__ __forceinline__ void qk64(float (&s)[32], const uint32_t (&q)[4], uint64_t db) {
    asm volatile("wgmma.mma_async.sync.aligned.m64n64k16.f32.bf16.bf16 "
        "{%0,%1,%2,%3,%4,%5,%6,%7,%8,%9,%10,%11,%12,%13,%14,%15,%16,%17,%18,%19,%20,%21,%22,%23,%24,%25,%26,%27,%28,%29,%30,%31}, "
        "{%32,%33,%34,%35}, %36, 0, 1, 1, 0;"
        : "=f"(s[0]), "=f"(s[1]), "=f"(s[2]), "=f"(s[3]), "=f"(s[4]), "=f"(s[5]), "=f"(s[6]), "=f"(s[7]),
          "=f"(s[8]), "=f"(s[9]), "=f"(s[10]), "=f"(s[11]), "=f"(s[12]), "=f"(s[13]), "=f"(s[14]), "=f"(s[15]),
          "=f"(s[16]), "=f"(s[17]), "=f"(s[18]), "=f"(s[19]), "=f"(s[20]), "=f"(s[21]), "=f"(s[22]), "=f"(s[23]),
          "=f"(s[24]), "=f"(s[25]), "=f"(s[26]), "=f"(s[27]), "=f"(s[28]), "=f"(s[29]), "=f"(s[30]), "=f"(s[31])
        : "r"(q[0]), "r"(q[1]), "r"(q[2]), "r"(q[3]), "l"(db));
}
__device__ __forceinline__ void pv24(float (&o)[12], uint32_t a0, uint32_t a1, uint32_t a2, uint32_t a3, uint64_t db) {
    asm volatile("wgmma.mma_async.sync.aligned.m64n24k16.f32.bf16.bf16 "
        "{%0,%1,%2,%3,%4,%5,%6,%7,%8,%9,%10,%11}, {%12,%13,%14,%15}, %16, 1, 1, 1, 1;"
        : "+f"(o[0]), "+f"(o[1]), "+f"(o[2]), "+f"(o[3]), "+f"(o[4]), "+f"(o[5]), "+f"(o[6]), "+f"(o[7]),
          "+f"(o[8]), "+f"(o[9]), "+f"(o[10]), "+f"(o[11])
        : "r"(a0), "r"(a1), "r"(a2), "r"(a3), "l"(db));
}

__device__ __forceinline__ void attn_safe(float (&o)[12], const uint32_t (&q)[4], uint64_t kdesc0, uint64_t vdesc0) {
    float s[32];
    float m0 = -INFINITY, m1 = -INFINITY;
#pragma unroll
    for (int i = 0; i < 12; i++) o[i] = 0.f;
#pragma unroll 1
    for (int j = 0; j < 32; j++) {
        WG_FENCE();
        qk64(s, q, kdesc0 + (uint64_t)(j * 64));
        WG_COMMIT(); WG_WAIT(0);
        float n0 = m0, n1 = m1;
#pragma unroll
        for (int i = 0; i < 8; i++) { n0 = fmaxf(n0, fmaxf(s[4 * i], s[4 * i + 1])); n1 = fmaxf(n1, fmaxf(s[4 * i + 2], s[4 * i + 3])); }
        n0 = fmaxf(n0, __shfl_xor_sync(~0u, n0, 1)); n0 = fmaxf(n0, __shfl_xor_sync(~0u, n0, 2));
        n1 = fmaxf(n1, __shfl_xor_sync(~0u, n1, 1)); n1 = fmaxf(n1, __shfl_xor_sync(~0u, n1, 2));
        const float c0 = ex2((m0 - n0) * QS), c1 = ex2((m1 - n1) * QS);
        m0 = n0; m1 = n1;
#pragma unroll
        for (int i = 0; i < 3; i++) { o[4 * i] *= c0; o[4 * i + 1] *= c0; o[4 * i + 2] *= c1; o[4 * i + 3] *= c1; }
        uint32_t p[16];
#pragma unroll
        for (int i = 0; i < 8; i++) {
            p[2 * i] = packbf(ex2((s[4 * i] - m0) * QS), ex2((s[4 * i + 1] - m0) * QS));
            p[2 * i + 1] = packbf(ex2((s[4 * i + 2] - m1) * QS), ex2((s[4 * i + 3] - m1) * QS));
        }
        WG_FENCE();
#pragma unroll
        for (int kk = 0; kk < 4; kk++) pv24(o, p[4 * kk], p[4 * kk + 1], p[4 * kk + 2], p[4 * kk + 3], vdesc0 + (uint64_t)(j * 64 + kk * 16));
        WG_COMMIT(); WG_WAIT(0);
    }
}

__device__ __forceinline__ void attn_store(const float (&o)[12], int head, int m64, int warp, int lane) {
    const int g = lane >> 2, t = lane & 3;
    const int row = m64 * 64 + warp * 16 + g;
    const float i0 = 1.f / o[8], i1 = 1.f / o[10];
    uint32_t* p0 = reinterpret_cast<uint32_t*>(g_o + (size_t)row * DM + head * 16 + t * 2);
    uint32_t* p1 = reinterpret_cast<uint32_t*>(g_o + (size_t)(row + 8) * DM + head * 16 + t * 2);
    p0[0] = packbf(o[0] * i0, o[1] * i0); p0[4] = packbf(o[4] * i0, o[5] * i0);
    p1[0] = packbf(o[2] * i1, o[3] * i1); p1[4] = packbf(o[6] * i1, o[7] * i1);
}

constexpr int FS_N = 4;
constexpr int FS_BYTES = 28672;
__device__ void ffn_block(int c, uint8_t* smem, uint32_t sbase, const CUtensorMap* mapG, const CUtensorMap* mapU,
                          const __nv_bfloat16* __restrict__ wd) {
    const int tid = threadIdx.x, warp = tid >> 5, lane = tid & 31;
    float* red = reinterpret_cast<float*>(smem + FS_N * FS_BYTES);
    float* sx = reinterpret_cast<float*>(smem + (FS_N + 1) * FS_BYTES);
    float* sh = sx + 1024;
    const uint32_t bars = sbase + (FS_N + 1) * FS_BYTES + 8192;
    __shared__ float tv[32]; __shared__ int ti[32];
    __shared__ int ssel[2];
    auto issue = [&](int item) {
        const int slot = item % FS_N;
        const uint32_t dst = sbase + slot * FS_BYTES, bar = bars + 8 * slot;
        mbar_expect_tx(bar, FS_BYTES);
        if (item < 32) {
            tma2d(dst, mapG, bar, c * 448, item * 16);
            tma2d(dst + 7168, mapG, bar, c * 448 + 224, item * 16);
            tma2d(dst + 14336, mapU, bar, c * 448, item * 16);
            tma2d(dst + 21504, mapU, bar, c * 448 + 224, item * 16);
        } else {
            bulk_g2s(dst, wd + ((size_t)c * 448 + (item - 32) * 28) * DM, FS_BYTES, bar);
        }
    };
    if (tid == 0) {
        for (int i = 0; i < FS_N; i++) mbar_init(bars + 8 * i, 1);
        fence_barrier_init();
        for (int i = 0; i < FS_N; i++) issue(i);
    }
    float b1 = -INFINITY, b2 = -INFINITY; int i1 = 0x7fffffff, i2 = 0x7fffffff;
    auto push = [&](float v, int i) {
        if (v > b1 || (v == b1 && i < i1)) { b2 = b1; i2 = i1; b1 = v; i1 = i; }
        else if (v > b2 || (v == b2 && i < i2)) { b2 = v; i2 = i; }
    };
    {
        const float4 rv = reinterpret_cast<const float4*>(g_r)[tid];
        push(rv.x, 4 * tid); push(rv.y, 4 * tid + 1); push(rv.z, 4 * tid + 2); push(rv.w, 4 * tid + 3);
    }
#pragma unroll
    for (int o = 16; o > 0; o >>= 1) {
        float v1 = __shfl_xor_sync(~0u, b1, o), v2 = __shfl_xor_sync(~0u, b2, o);
        int j1 = __shfl_xor_sync(~0u, i1, o), j2 = __shfl_xor_sync(~0u, i2, o);
        push(v1, j1); push(v2, j2);
    }
    if (lane == 0) { tv[2 * warp] = b1; ti[2 * warp] = i1; tv[2 * warp + 1] = b2; ti[2 * warp + 1] = i2; }
    __syncthreads();
    if (warp == 1) {
        b1 = tv[lane]; i1 = ti[lane]; b2 = -INFINITY; i2 = 0x7fffffff;
#pragma unroll
        for (int o = 16; o > 0; o >>= 1) {
            float v1 = __shfl_xor_sync(~0u, b1, o), v2 = __shfl_xor_sync(~0u, b2, o);
            int j1 = __shfl_xor_sync(~0u, i1, o), j2 = __shfl_xor_sync(~0u, i2, o);
            push(v1, j1); push(v2, j2);
        }
        if (lane == 0) {
            i1 = min(max(i1, 0), S_LEN - 1); i2 = min(max(i2, 0), S_LEN - 1);
            ssel[0] = i1; ssel[1] = i2;
            if (c == 0) {
                g_sel[0] = i1; g_sel[1] = i2;
                g_gate[0] = bfr(1.f / (1.f + __expf(-bfr(b1))));
                g_gate[1] = bfr(1.f / (1.f + __expf(-bfr(b2))));
            }
        }
    }
    __syncthreads();
    {
        const uint32_t v = *reinterpret_cast<const uint32_t*>(g_xn + (size_t)ssel[tid >> 8] * DM + (tid & 255) * 2);
        sx[2 * tid] = bf_lo(v); sx[2 * tid + 1] = bf_hi(v);
    }
    __syncthreads();
    TL(2, 1);
    {
        const int kg = tid / 56, ch = tid % 56;
        float ag[2][8], au[2][8];
#pragma unroll
        for (int j = 0; j < 8; j++) { ag[0][j] = ag[1][j] = au[0][j] = au[1][j] = 0.f; }
#pragma unroll 1
        for (int it = 0; it < 32; it++) {
            const int slot = it % FS_N;
            mbar_wait(bars + 8 * slot, (it / FS_N) & 1);
            if (kg < 8) {
                const uint8_t* base = smem + slot * FS_BYTES + (ch / 28) * 7168 + (ch % 28) * 16;
#pragma unroll
                for (int h = 0; h < 2; h++) {
                    const int r = kg + h * 8;
                    const uint4 vg = *reinterpret_cast<const uint4*>(base + r * 448);
                    const uint4 vu = *reinterpret_cast<const uint4*>(base + 14336 + r * 448);
                    const float x0 = sx[it * 16 + r], x1 = sx[512 + it * 16 + r];
                    const uint32_t gw[4] = {vg.x, vg.y, vg.z, vg.w}, uw[4] = {vu.x, vu.y, vu.z, vu.w};
#pragma unroll
                    for (int j = 0; j < 4; j++) {
                        const float g0 = bf_lo(gw[j]), g1 = bf_hi(gw[j]), u0 = bf_lo(uw[j]), u1 = bf_hi(uw[j]);
                        ag[0][2 * j] = fmaf(x0, g0, ag[0][2 * j]); ag[0][2 * j + 1] = fmaf(x0, g1, ag[0][2 * j + 1]);
                        ag[1][2 * j] = fmaf(x1, g0, ag[1][2 * j]); ag[1][2 * j + 1] = fmaf(x1, g1, ag[1][2 * j + 1]);
                        au[0][2 * j] = fmaf(x0, u0, au[0][2 * j]); au[0][2 * j + 1] = fmaf(x0, u1, au[0][2 * j + 1]);
                        au[1][2 * j] = fmaf(x1, u0, au[1][2 * j]); au[1][2 * j + 1] = fmaf(x1, u1, au[1][2 * j + 1]);
                    }
                }
            }
            __syncthreads();
            if (tid == 0) issue(it + FS_N);
        }
#pragma unroll
        for (int tok = 0; tok < 2; tok++) {
            if (kg < 8) {
#pragma unroll
                for (int j = 0; j < 8; j++) { red[(kg * 2) * 448 + ch * 8 + j] = ag[tok][j]; red[(kg * 2 + 1) * 448 + ch * 8 + j] = au[tok][j]; }
            }
            __syncthreads();
            if (tid < 448) {
                float gs = 0.f, us = 0.f;
#pragma unroll
                for (int q = 0; q < 8; q++) { gs += red[(q * 2) * 448 + tid]; us += red[(q * 2 + 1) * 448 + tid]; }
                gs = bfr(gs); us = bfr(us);
                const float sg = bfr(gs / (1.f + __expf(-gs)));
                sh[tok * 448 + tid] = bfr(sg * us);
            }
            __syncthreads();
        }
    }
    TL(2, 2);
    {
        const int ch = tid & 63, kg = tid >> 6;
        float a[2][8];
#pragma unroll
        for (int j = 0; j < 8; j++) a[0][j] = a[1][j] = 0.f;
#pragma unroll 1
        for (int it = 32; it < 48; it++) {
            const int slot = it % FS_N;
            mbar_wait(bars + 8 * slot, (it / FS_N) & 1);
            const uint8_t* base = smem + slot * FS_BYTES + ch * 16;
#pragma unroll
            for (int h = 0; h < 4; h++) {
                const int r = kg + h * 8;
                if (r < 28) {
                    const uint4 v = *reinterpret_cast<const uint4*>(base + r * 1024);
                    const float h0 = sh[(it - 32) * 28 + r], h1 = sh[448 + (it - 32) * 28 + r];
                    const uint32_t w[4] = {v.x, v.y, v.z, v.w};
#pragma unroll
                    for (int j = 0; j < 4; j++) {
                        const float w0 = bf_lo(w[j]), w1 = bf_hi(w[j]);
                        a[0][2 * j] = fmaf(h0, w0, a[0][2 * j]); a[0][2 * j + 1] = fmaf(h0, w1, a[0][2 * j + 1]);
                        a[1][2 * j] = fmaf(h1, w0, a[1][2 * j]); a[1][2 * j + 1] = fmaf(h1, w1, a[1][2 * j + 1]);
                    }
                }
            }
            __syncthreads();
            if (tid == 0 && it + FS_N < 48) issue(it + FS_N);
        }
        float* red2 = reinterpret_cast<float*>(smem);
#pragma unroll
        for (int j = 0; j < 8; j++) { red2[(kg * 2) * 512 + ch * 8 + j] = a[0][j]; red2[(kg * 2 + 1) * 512 + ch * 8 + j] = a[1][j]; }
        __syncthreads();
        for (int i = tid; i < 1024; i += 512) {
            float sum = 0.f;
#pragma unroll
            for (int q = 0; q < 8; q++) sum += red2[q * 1024 + i];
            g_ypart[c * 1024 + i] = sum;
        }
    }
}

__global__ void __launch_bounds__(512, 1) attn_kernel(const __grid_constant__ CUtensorMap mapG, const __grid_constant__ CUtensorMap mapU,
                                                      const __nv_bfloat16* __restrict__ wd_, float sc) {
    extern __shared__ uint8_t smem_raw[];
    const uint32_t sraw = smem_u32(smem_raw);
    const uint32_t sbase = (sraw + 1023u) & ~1023u;
    uint8_t* sptr = smem_raw + (sbase - sraw);
    TL(2, 0);
    if (blockIdx.x < 4) {
        pdl_launch();
        ffn_block(blockIdx.x, sptr, sbase, &mapG, &mapU, wd_);
        TL(2, 3);
        return;
    }
    const uint32_t bars = sbase + 163840;
    const int head = (blockIdx.x - 4) >> 2, quarter = blockIdx.x & 3;
    const int wg = threadIdx.x >> 7, warp = (threadIdx.x >> 5) & 3, lane = threadIdx.x & 31;
    if (threadIdx.x == 0) {
        for (int c = 0; c < 8; c++) mbar_init(bars + 8 * c, 1);
        fence_barrier_init();
    }
    {
        uint4* ones = reinterpret_cast<uint4*>(sptr + 131072);
        for (int i = threadIdx.x; i < 2048; i += 512) ones[i] = make_uint4(0x3f803f80u, 0x3f803f80u, 0x3f803f80u, 0x3f803f80u);
        fence_proxy_async();
    }
    __syncthreads();
    pdl_wait();
    pdl_launch();
    TL(2, 1);
    if (threadIdx.x == 0) {
        const uint8_t* kp = reinterpret_cast<const uint8_t*>(g_k + head * 4096);
        const uint8_t* vp = reinterpret_cast<const uint8_t*>(g_v + head * 4096);
        for (int c = 0; c < 8; c++) {
            mbar_expect_tx(bars + 8 * c, 16384);
            bulk_g2s(sbase + c * 4096, kp + c * 4096, 4096, bars + 8 * c);
            bulk_g2s(sbase + 32768 + c * 4096, kp + 32768 + c * 4096, 4096, bars + 8 * c);
            bulk_g2s(sbase + 65536 + c * 4096, vp + c * 4096, 4096, bars + 8 * c);
            bulk_g2s(sbase + 98304 + c * 4096, vp + 32768 + c * 4096, 4096, bars + 8 * c);
        }
    }
    const uint64_t kdesc0 = mkdesc(sbase, 32768, 128, 0);
    const uint64_t vdesc0 = mkdesc(sbase + 65536, 128, 32768, 0);
    uint32_t badmask = 0;
#pragma unroll 1
    for (int mt = 0; mt < 2; mt++) {
        const int m64 = quarter * 8 + mt * 4 + wg;
        uint32_t q[4];
        { const uint4 qq = g_q[(head * 128 + m64 * 4 + warp) * 32 + lane]; q[0] = qq.x; q[1] = qq.y; q[2] = qq.z; q[3] = qq.w; }
        float s[32], s2[32], o[12];
#pragma unroll
        for (int i = 0; i < 12; i++) o[i] = 0.f;
        mbar_wait(bars, 0);
        if (mt == 0) TL(2, 2);
        WG_FENCE();
        qk64(s, q, kdesc0);
        WG_COMMIT(); WG_WAIT(0);
        float mx0 = -INFINITY, mx1 = -INFINITY;
#pragma unroll
        for (int i = 0; i < 8; i++) { mx0 = fmaxf(mx0, fmaxf(s[4 * i], s[4 * i + 1])); mx1 = fmaxf(mx1, fmaxf(s[4 * i + 2], s[4 * i + 3])); }
        mx0 = fmaxf(mx0, __shfl_xor_sync(~0u, mx0, 1)); mx0 = fmaxf(mx0, __shfl_xor_sync(~0u, mx0, 2));
        mx1 = fmaxf(mx1, __shfl_xor_sync(~0u, mx1, 1)); mx1 = fmaxf(mx1, __shfl_xor_sync(~0u, mx1, 2));
        float cm0 = -(ceilf(mx0 * QS) + SHIFT), cm1 = -(ceilf(mx1 * QS) + SHIFT);
        float cp0 = (cm0 + 127.f) * sc, cp1 = (cm1 + 127.f) * sc;
        asm volatile("" : "+f"(cm0), "+f"(cm1), "+f"(cp0), "+f"(cp1));
        uint64_t kd = kdesc0, vd = vdesc0;
        auto step = [&](float (&sc_)[32], float (&sn)[32]) {
            kd += 64;
            WG_FENCE();
            qk64(sn, q, kd);
            WG_COMMIT();
#pragma unroll
            for (int kk = 0; kk < 4; kk++) {
                const int i0 = kk * 2, i1 = kk * 2 + 1;
                const uint32_t p0 = packbf(ex2(fmaf(sc_[4 * i0], QS, cm0)), ex2(fmaf(sc_[4 * i0 + 1], QS, cm0)));
                const uint32_t p1 = packbf(ex2(fmaf(sc_[4 * i0 + 2], QS, cm1)), ex2(fmaf(sc_[4 * i0 + 3], QS, cm1)));
                const uint32_t p2 = polyexp(fmaf(sc_[4 * i1], scq, cp0), fmaf(sc_[4 * i1 + 1], scq, cp0));
                const uint32_t p3 = polyexp(fmaf(sc_[4 * i1 + 2], scq, cp1), fmaf(sc_[4 * i1 + 3], scq, cp1));
                WG_FENCE();
                pv24(o, p0, p1, p2, p3, vd);
                vd += 16;
            }
            WG_COMMIT();
            WG_WAIT(1);
        };
#pragma unroll 1
        for (int c = 0; c < 16; c++) {
            if (mt == 0 && (c & 1) == 0 && c < 14) mbar_wait(bars + 4 * c + 8, 0);
            step(s, s2); step(s2, s);
        }
        WG_WAIT(0);
        bool bad = !(o[8] > 0.f) || !(o[10] > 0.f);
#pragma unroll
        for (int i = 0; i < 12; i++) bad = bad || !(fabsf(o[i]) <= 3.0e38f);
        uint32_t anybad;
        asm volatile("{\n.reg .pred p, q;\nsetp.ne.u32 p, %1, 0;\nbarrier.cta.red.or.pred q, %2, 128, p;\nselp.u32 %0, 1, 0, q;\n}"
                     : "=r"(anybad) : "r"((uint32_t)bad), "r"(wg + 1) : "memory");
        badmask |= anybad << mt;
        attn_store(o, head, m64, warp, lane);
    }
#pragma unroll 1
    for (int mt = 0; mt < 2; mt++) {
        if (!((badmask >> mt) & 1)) continue;
        const int m64 = quarter * 8 + mt * 4 + wg;
        uint32_t q[4];
        { const uint4 qq = g_q[(head * 128 + m64 * 4 + warp) * 32 + lane]; q[0] = qq.x; q[1] = qq.y; q[2] = qq.z; q[3] = qq.w; }
        float o[12];
        attn_safe(o, q, mkdesc(sbase, 32768, 128, 0), mkdesc(sbase + 65536, 128, 32768, 0));
        attn_store(o, head, m64, warp, lane);
    }
    TL(2, 3);
}

constexpr int K3_SMEM = 8 * 8192 + 8 * 16384 + 1024 + 128;

__device__ __forceinline__ void wgmma_n64(float (&d)[32], uint64_t da, uint64_t db, int scale_d) {
    asm volatile("{\n.reg .pred p;\nsetp.ne.b32 p, %34, 0;\n"
        "wgmma.mma_async.sync.aligned.m64n64k16.f32.bf16.bf16 "
        "{%0,%1,%2,%3,%4,%5,%6,%7,%8,%9,%10,%11,%12,%13,%14,%15,%16,%17,%18,%19,%20,%21,%22,%23,%24,%25,%26,%27,%28,%29,%30,%31}, "
        "%32, %33, p, 1, 1, 0, 1;\n}"
        : "+f"(d[0]), "+f"(d[1]), "+f"(d[2]), "+f"(d[3]), "+f"(d[4]), "+f"(d[5]), "+f"(d[6]), "+f"(d[7]),
          "+f"(d[8]), "+f"(d[9]), "+f"(d[10]), "+f"(d[11]), "+f"(d[12]), "+f"(d[13]), "+f"(d[14]), "+f"(d[15]),
          "+f"(d[16]), "+f"(d[17]), "+f"(d[18]), "+f"(d[19]), "+f"(d[20]), "+f"(d[21]), "+f"(d[22]), "+f"(d[23]),
          "+f"(d[24]), "+f"(d[25]), "+f"(d[26]), "+f"(d[27]), "+f"(d[28]), "+f"(d[29]), "+f"(d[30]), "+f"(d[31])
        : "l"(da), "l"(db), "r"(scale_d));
}

__global__ void __launch_bounds__(256, 1) oproj_kernel(const __grid_constant__ CUtensorMap mapA, const __grid_constant__ CUtensorMap mapB,
                                                       const __nv_bfloat16* __restrict__ x, __nv_bfloat16* __restrict__ out) {
    extern __shared__ uint8_t smem_raw[];
    const uint32_t sbase = (smem_u32(smem_raw) + 1023u) & ~1023u;
    const uint32_t sA = sbase, sB = sbase + 8 * 8192, bars = sbase + 8 * 8192 + 8 * 16384;
    const int warp = threadIdx.x >> 5, lane = threadIdx.x & 31, wg = warp >> 2;
    const int nb = blockIdx.x & 3, mb = blockIdx.x >> 2;
    TL(3, 0);
    if (threadIdx.x == 0) {
        for (int c = 0; c < 8; c++) mbar_init(bars + 8 * c, 1);
        fence_barrier_init();
        for (int c = 0; c < 8; c++) {
            mbar_expect_tx(bars + 8 * c, 8192 + 16384);
            tma2d(sB + c * 16384, &mapB, bars + 8 * c, nb * 128, c * 64);
            tma2d(sB + c * 16384 + 8192, &mapB, bars + 8 * c, nb * 128 + 64, c * 64);
        }
    }
    const int g = lane >> 2, t = lane & 3;
    const int row0 = mb * 64 + (warp & 3) * 16 + g;
    const int col0 = nb * 128 + wg * 64 + t * 2;
    uint32_t xv[16], nv[16];
#pragma unroll
    for (int i = 0; i < 8; i++) {
        xv[2 * i] = *reinterpret_cast<const uint32_t*>(x + (size_t)row0 * DM + col0 + i * 8);
        xv[2 * i + 1] = *reinterpret_cast<const uint32_t*>(x + (size_t)(row0 + 8) * DM + col0 + i * 8);
        nv[2 * i] = *reinterpret_cast<const uint32_t*>(g_xn + (size_t)row0 * DM + col0 + i * 8);
        nv[2 * i + 1] = *reinterpret_cast<const uint32_t*>(g_xn + (size_t)(row0 + 8) * DM + col0 + i * 8);
    }
    __syncthreads();
    pdl_wait();
    TL(3, 1);
    if (threadIdx.x == 0) {
        for (int c = 0; c < 8; c++) tma2d(sA + c * 8192, &mapA, bars + 8 * c, c * 64, mb * 64);
    }
    float acc[32];
#pragma unroll
    for (int i = 0; i < 32; i++) acc[i] = 0.f;
#pragma unroll 1
    for (int c = 0; c < 8; c++) {
        mbar_wait(bars + 8 * c, 0);
        const uint64_t da = mkdesc(sA + c * 8192, 16, 1024, 1);
        const uint64_t db = mkdesc(sB + c * 16384 + wg * 8192, 8192, 1024, 1);
        WG_FENCE();
#pragma unroll
        for (int k = 0; k < 4; k++) wgmma_n64(acc, da + k * 2, db + k * 128, (c | k) != 0);
        WG_COMMIT();
    }
    const int sel0 = g_sel[0], sel1 = g_sel[1];
    WG_WAIT(0);
    TL(3, 2);
#pragma unroll
    for (int h = 0; h < 2; h++) {
        const int row = row0 + h * 8;
        const int which = row == sel0 ? 0 : (row == sel1 ? 1 : -1);
#pragma unroll
        for (int i = 0; i < 8; i++) {
            const int col = col0 + i * 8;
            float b0 = bf_lo(nv[2 * i + h]), b1 = bf_hi(nv[2 * i + h]);
            if (which >= 0) {
                float y0 = 0.f, y1 = 0.f;
#pragma unroll
                for (int c = 0; c < 4; c++) { y0 += g_ypart[c * 1024 + which * 512 + col]; y1 += g_ypart[c * 1024 + which * 512 + col + 1]; }
                const float gt = g_gate[which];
                b0 = bfr(b0 + bfr(bfr(y0) * gt)); b1 = bfr(b1 + bfr(bfr(y1) * gt));
            }
            const float t0 = bfr(bf_lo(xv[2 * i + h]) + bfr(acc[4 * i + 2 * h]));
            const float t1 = bfr(bf_hi(xv[2 * i + h]) + bfr(acc[4 * i + 2 * h + 1]));
            *reinterpret_cast<uint32_t*>(out + (size_t)row * DM + col) = packbf(t0 + b0, t1 + b1);
        }
    }
    TL(3, 3);
}

typedef CUresult (*EncodeFn)(CUtensorMap*, CUtensorMapDataType, cuuint32_t, void*, const cuuint64_t*, const cuuint64_t*,
                             const cuuint32_t*, const cuuint32_t*, CUtensorMapInterleave, CUtensorMapSwizzle,
                             CUtensorMapL2promotion, CUtensorMapFloatOOBfill);

void make_map(EncodeFn fn, CUtensorMap* m, const void* ptr, uint64_t inner, uint64_t outer, uint32_t box_inner, uint32_t box_outer,
              CUtensorMapSwizzle swz = CU_TENSOR_MAP_SWIZZLE_128B) {
    cuuint64_t dims[2] = {inner, outer};
    cuuint64_t strides[1] = {inner * 2};
    cuuint32_t box[2] = {box_inner, box_outer};
    cuuint32_t es[2] = {1, 1};
    fn(m, CU_TENSOR_MAP_DATA_TYPE_BFLOAT16, 2, const_cast<void*>(ptr), dims, strides, box, es, CU_TENSOR_MAP_INTERLEAVE_NONE,
       swz, CU_TENSOR_MAP_L2_PROMOTION_L2_256B, CU_TENSOR_MAP_FLOAT_OOB_FILL_NONE);
}

template <typename... KArgs, typename... Args>
void launch(void (*kern)(KArgs...), int grid, int block, int smem, bool pdl, Args... args) {
    cudaLaunchConfig_t cfg = {};
    cfg.gridDim = dim3(grid); cfg.blockDim = dim3(block); cfg.dynamicSmemBytes = smem; cfg.stream = cudaStreamPerThread;
    cudaLaunchAttribute at[1];
    at[0].id = cudaLaunchAttributeProgrammaticStreamSerialization;
    at[0].val.programmaticStreamSerializationAllowed = 1;
    cfg.attrs = at; cfg.numAttrs = pdl ? 1 : 0;
    cudaLaunchKernelEx(&cfg, kern, KArgs(args)...);
}

}

extern "C" void kernel_launch(void* const* d_in, const int* in_sizes, int n_in, void* d_out, int out_size) {
    const __nv_bfloat16* x = (const __nv_bfloat16*)d_in[0];
    const __nv_bfloat16* wqkv = (const __nv_bfloat16*)d_in[1];
    const __nv_bfloat16* wo = (const __nv_bfloat16*)d_in[2];
    const __nv_bfloat16* wr = (const __nv_bfloat16*)d_in[4];
    const __nv_bfloat16* wgate = (const __nv_bfloat16*)d_in[5];
    const __nv_bfloat16* wup = (const __nv_bfloat16*)d_in[6];
    const __nv_bfloat16* wdown = (const __nv_bfloat16*)d_in[7];
    __nv_bfloat16* out = (__nv_bfloat16*)d_out;

    static EncodeFn enc = nullptr;
    static void* p_xn = nullptr; static void* p_o = nullptr;
    if (!enc) {
        void* fn = nullptr; cudaDriverEntryPointQueryResult qr;
        cudaGetDriverEntryPoint("cuTensorMapEncodeTiled", &fn, cudaEnableDefault, &qr);
        enc = (EncodeFn)fn;
        cudaGetSymbolAddress(&p_xn, g_xn);
        cudaGetSymbolAddress(&p_o, g_o);
        cudaFuncSetAttribute(qkv_kernel, cudaFuncAttributeMaxDynamicSharedMemorySize, K1_SMEM);
        cudaFuncSetAttribute(attn_kernel, cudaFuncAttributeMaxDynamicSharedMemorySize, K2_SMEM);
        cudaFuncSetAttribute(oproj_kernel, cudaFuncAttributeMaxDynamicSharedMemorySize, K3_SMEM);
    }
    CUtensorMap mXn, mWqkv, mO, mWo, mG, mU;
    make_map(enc, &mG, wgate, FF, DM, 224, 16, CU_TENSOR_MAP_SWIZZLE_NONE);
    make_map(enc, &mU, wup, FF, DM, 224, 16, CU_TENSOR_MAP_SWIZZLE_NONE);
    make_map(enc, &mXn, p_xn, DM, S_LEN, 64, 128);
    make_map(enc, &mWqkv, wqkv, 3 * DM, DM, 64, 64);
    make_map(enc, &mO, p_o, DM, S_LEN, 64, 64);
    make_map(enc, &mWo, wo, DM, DM, 64, 64);

    union { uint32_t u; float f; } scu; scu.u = 128u;

    launch(ln_kernel, S_LEN / 8, 256, 0, false, x, wr);
    launch(qkv_kernel, 128, 288, K1_SMEM, true, mXn, mWqkv);
    launch(attn_kernel, 132, 512, K2_SMEM, true, mG, mU, wdown, scu.f);
    launch(oproj_kernel, 128, 256, K3_SMEM, true, mO, mWo, x, out);
}
```

```cpp
#include <cuda_runtime.h>
#include <cuda_bf16.h>
#include <cuda.h>
#include <stdint.h>
#include <type_traits>

namespace {

constexpr int S_LEN = 2048;
constexpr int DM = 512;
constexpr int NH = 32;
constexpr int FF = 1792;

__device__ __align__(1024) __nv_bfloat16 g_xn[S_LEN * DM];
__device__ __align__(16) float g_r[S_LEN];
__device__ __align__(1024) uint4 g_q[NH * 128 * 32];
__device__ __align__(1024) uint4 g_k[NH * 4096];
__device__ __align__(1024) uint4 g_v[NH * 4096];
__device__ __align__(1024) __nv_bfloat16 g_o[S_LEN * DM];
__device__ float g_ypart[4 * 2 * DM];
__device__ int g_sel[2];
__device__ float g_gate[2];

#define TL(k, slot) do {} while (0)

__device__ __forceinline__ uint32_t smem_u32(const void* p) { return (uint32_t)__cvta_generic_to_shared(p); }
__device__ __forceinline__ void pdl_wait() { asm volatile("griddepcontrol.wait;" ::: "memory"); }
__device__ __forceinline__ void pdl_launch() { asm volatile("griddepcontrol.launch_dependents;" ::: "memory"); }
__device__ __forceinline__ void mbar_init(uint32_t bar, uint32_t cnt) {
    asm volatile("mbarrier.init.shared::cta.b64 [%0], %1;" :: "r"(bar), "r"(cnt) : "memory");
}
__device__ __forceinline__ void mbar_expect_tx(uint32_t bar, uint32_t bytes) {
    asm volatile("mbarrier.arrive.expect_tx.shared::cta.b64 _, [%0], %1;" :: "r"(bar), "r"(bytes) : "memory");
}
__device__ __forceinline__ void mbar_arrive(uint32_t bar) {
    asm volatile("mbarrier.arrive.shared::cta.b64 _, [%0];" :: "r"(bar) : "memory");
}
__device__ __forceinline__ void mbar_wait(uint32_t bar, uint32_t parity) {
    asm volatile("{\n.reg .pred p;\n.reg .u32 n;\nmov.u32 n, 0;\n"
                 "WAIT_%=:\n"
                 "mbarrier.try_wait.parity.shared::cta.b64 p, [%0], %1;\n"
                 "@p bra DONE_%=;\n"
                 "add.u32 n, n, 1;\n"
                 "setp.lt.u32 p, n, 4000000;\n"
                 "@p bra WAIT_%=;\n"
                 "trap;\n"
                 "DONE_%=:\n}"
                 :: "r"(bar), "r"(parity) : "memory");
}
__device__ __forceinline__ void fence_barrier_init() { asm volatile("fence.mbarrier_init.release.cluster;" ::: "memory"); }
__device__ __forceinline__ void fence_proxy_async() { asm volatile("fence.proxy.async.shared::cta;" ::: "memory"); }
__device__ __forceinline__ void tma2d(uint32_t dst, const CUtensorMap* map, uint32_t bar, int c0, int c1) {
    asm volatile("cp.async.bulk.tensor.2d.shared::cluster.global.mbarrier::complete_tx::bytes [%0], [%1, {%3, %4}], [%2];"
                 :: "r"(dst), "l"((uint64_t)map), "r"(bar), "r"(c0), "r"(c1) : "memory");
}
__device__ __forceinline__ void bulk_g2s(uint32_t dst, const void* src, uint32_t bytes, uint32_t bar) {
    asm volatile("cp.async.bulk.shared::cluster.global.mbarrier::complete_tx::bytes [%0], [%1], %2, [%3];"
                 :: "r"(dst), "l"((uint64_t)src), "r"(bytes), "r"(bar) : "memory");
}
__device__ __forceinline__ void l2_prefetch(const void* src, uint32_t bytes) {
    asm volatile("cp.async.bulk.prefetch.L2.global [%0], %1;" :: "l"((uint64_t)src), "r"(bytes) : "memory");
}
__device__ __forceinline__ void map_prefetch(const CUtensorMap* m) {
    asm volatile("prefetch.tensormap [%0];" :: "l"((uint64_t)m) : "memory");
}
__device__ __forceinline__ uint64_t mkdesc(uint32_t addr, uint32_t lbo, uint32_t sbo, uint32_t swz) {
    return (uint64_t)((addr & 0x3FFFF) >> 4) | ((uint64_t)(lbo >> 4) << 16) | ((uint64_t)(sbo >> 4) << 32) | ((uint64_t)swz << 62);
}
#define WG_FENCE() asm volatile("wgmma.fence.sync.aligned;" ::: "memory")
#define WG_COMMIT() asm volatile("wgmma.commit_group.sync.aligned;" ::: "memory")
#define WG_WAIT(n) asm volatile("wgmma.wait_group.sync.aligned %0;" :: "n"(n) : "memory")

__device__ __forceinline__ float ex2(float x) { float y; asm("ex2.approx.ftz.f32 %0, %1;" : "=f"(y) : "f"(x)); return y; }
__device__ __forceinline__ uint32_t packbf(float lo, float hi) {
    uint32_t r; asm("cvt.rn.bf16x2.f32 %0, %1, %2;" : "=r"(r) : "f"(hi), "f"(lo)); return r;
}
__device__ __forceinline__ float bf_lo(uint32_t v) { return __uint_as_float(v << 16); }
__device__ __forceinline__ float bf_hi(uint32_t v) { return __uint_as_float(v & 0xffff0000u); }
__device__ __forceinline__ float bfr(float x) { return __bfloat162float(__float2bfloat16_rn(x)); }

__global__ void __launch_bounds__(256) ln_kernel(const __nv_bfloat16* __restrict__ x, const __nv_bfloat16* __restrict__ wr) {
    TL(0, 0);
    pdl_launch();
    const int warp = threadIdx.x >> 5, lane = threadIdx.x & 31;
    const int row = blockIdx.x * 8 + warp;
    const uint4* xr = reinterpret_cast<const uint4*>(x + (size_t)row * DM);
    uint4 a = xr[lane], b = xr[32 + lane];
    const uint4* wp = reinterpret_cast<const uint4*>(wr);
    uint4 wa = wp[lane], wb = wp[32 + lane];
    uint32_t u[8] = {a.x, a.y, a.z, a.w, b.x, b.y, b.z, b.w};
    uint32_t w[8] = {wa.x, wa.y, wa.z, wa.w, wb.x, wb.y, wb.z, wb.w};
    float f[16];
    float sum = 0.f;
#pragma unroll
    for (int i = 0; i < 8; i++) { f[2 * i] = bf_lo(u[i]); f[2 * i + 1] = bf_hi(u[i]); sum += f[2 * i] + f[2 * i + 1]; }
#pragma unroll
    for (int o = 16; o > 0; o >>= 1) sum += __shfl_xor_sync(~0u, sum, o);
    const float mean = sum * (1.f / DM);
    float sq = 0.f;
#pragma unroll
    for (int i = 0; i < 16; i++) { float d = f[i] - mean; sq = fmaf(d, d, sq); }
#pragma unroll
    for (int o = 16; o > 0; o >>= 1) sq += __shfl_xor_sync(~0u, sq, o);
    const float mb = bfr(mean);
    const float vb = bfr(sq * (1.f / DM));
    const float den = bfr(sqrtf(bfr(vb + 1e-5f)));
    const float rinv = 1.f / den;
    uint32_t o[8];
    float r = 0.f;
#pragma unroll
    for (int i = 0; i < 8; i++) {
        float d0 = bfr(f[2 * i] - mb), d1 = bfr(f[2 * i + 1] - mb);
        o[i] = packbf(d0 * rinv, d1 * rinv);
        r = fmaf(bf_lo(o[i]), bf_lo(w[i]), r);
        r = fmaf(bf_hi(o[i]), bf_hi(w[i]), r);
    }
#pragma unroll
    for (int of = 16; of > 0; of >>= 1) r += __shfl_xor_sync(~0u, r, of);
    uint4* xo = reinterpret_cast<uint4*>(g_xn + (size_t)row * DM);
    xo[lane] = make_uint4(o[0], o[1], o[2], o[3]);
    xo[32 + lane] = make_uint4(o[4], o[5], o[6], o[7]);
    if (lane == 0) g_r[row] = r;
    TL(0, 3);
}

constexpr int K1_ST = 5;
constexpr int K1_STAGE = 16384 + 24576;
constexpr int K1_SMEM = K1_ST * K1_STAGE + 1024 + 128;

__device__ __forceinline__ void wgmma_n192(float (&d)[96], uint64_t da, uint64_t db, int scale_d) {
    asm volatile("{\n.reg .pred p;\nsetp.ne.b32 p, %98, 0;\n"
        "wgmma.mma_async.sync.aligned.m64n192k16.f32.bf16.bf16 "
        "{%0,%1,%2,%3,%4,%5,%6,%7,%8,%9,%10,%11,%12,%13,%14,%15,%16,%17,%18,%19,%20,%21,%22,%23,"
        "%24,%25,%26,%27,%28,%29,%30,%31,%32,%33,%34,%35,%36,%37,%38,%39,%40,%41,%42,%43,%44,%45,%46,%47,"
        "%48,%49,%50,%51,%52,%53,%54,%55,%56,%57,%58,%59,%60,%61,%62,%63,%64,%65,%66,%67,%68,%69,%70,%71,"
        "%72,%73,%74,%75,%76,%77,%78,%79,%80,%81,%82,%83,%84,%85,%86,%87,%88,%89,%90,%91,%92,%93,%94,%95}, "
        "%96, %97, p, 1, 1, 0, 1;\n}"
        : "+f"(d[0]), "+f"(d[1]), "+f"(d[2]), "+f"(d[3]), "+f"(d[4]), "+f"(d[5]), "+f"(d[6]), "+f"(d[7]),
          "+f"(d[8]), "+f"(d[9]), "+f"(d[10]), "+f"(d[11]), "+f"(d[12]), "+f"(d[13]), "+f"(d[14]), "+f"(d[15]),
          "+f"(d[16]), "+f"(d[17]), "+f"(d[18]), "+f"(d[19]), "+f"(d[20]), "+f"(d[21]), "+f"(d[22]), "+f"(d[23]),
          "+f"(d[24]), "+f"(d[25]), "+f"(d[26]), "+f"(d[27]), "+f"(d[28]), "+f"(d[29]), "+f"(d[30]), "+f"(d[31]),
          "+f"(d[32]), "+f"(d[33]), "+f"(d[34]), "+f"(d[35]), "+f"(d[36]), "+f"(d[37]), "+f"(d[38]), "+f"(d[39]),
          "+f"(d[40]), "+f"(d[41]), "+f"(d[42]), "+f"(d[43]), "+f"(d[44]), "+f"(d[45]), "+f"(d[46]), "+f"(d[47]),
          "+f"(d[48]), "+f"(d[49]), "+f"(d[50]), "+f"(d[51]), "+f"(d[52]), "+f"(d[53]), "+f"(d[54]), "+f"(d[55]),
          "+f"(d[56]), "+f"(d[57]), "+f"(d[58]), "+f"(d[59]), "+f"(d[60]), "+f"(d[61]), "+f"(d[62]), "+f"(d[63]),
          "+f"(d[64]), "+f"(d[65]), "+f"(d[66]), "+f"(d[67]), "+f"(d[68]), "+f"(d[69]), "+f"(d[70]), "+f"(d[71]),
          "+f"(d[72]), "+f"(d[73]), "+f"(d[74]), "+f"(d[75]), "+f"(d[76]), "+f"(d[77]), "+f"(d[78]), "+f"(d[79]),
          "+f"(d[80]), "+f"(d[81]), "+f"(d[82]), "+f"(d[83]), "+f"(d[84]), "+f"(d[85]), "+f"(d[86]), "+f"(d[87]),
          "+f"(d[88]), "+f"(d[89]), "+f"(d[90]), "+f"(d[91]), "+f"(d[92]), "+f"(d[93]), "+f"(d[94]), "+f"(d[95])
        : "l"(da), "l"(db), "r"(scale_d));
}

__global__ void __launch_bounds__(288, 1) qkv_kernel(const __grid_constant__ CUtensorMap mapA, const __grid_constant__ CUtensorMap mapB,
                                                     const uint8_t* __restrict__ pwg, const uint8_t* __restrict__ pwu, const uint8_t* __restrict__ pwd,
                                                     const uint8_t* __restrict__ pwo) {
    extern __shared__ uint8_t smem_raw[];
    const uint32_t sbase = (smem_u32(smem_raw) + 1023u) & ~1023u;
    const uint32_t bars = sbase + K1_ST * K1_STAGE;
    const int warp = threadIdx.x >> 5, lane = threadIdx.x & 31;
    const int nb = blockIdx.x & 7, mb = blockIdx.x >> 3;
    TL(1, 0);
    if (threadIdx.x == 0) {
        for (int s = 0; s < K1_ST; s++) { mbar_init(bars + 8 * s, 1); mbar_init(bars + 8 * (K1_ST + s), 2); }
        fence_barrier_init();
    }
    __syncthreads();
    if (warp == 8) {
        if (lane == 0) {
            for (int c = 0; c < K1_ST; c++) {
                const uint32_t st = sbase + c * K1_STAGE;
                mbar_expect_tx(bars + 8 * c, K1_STAGE);
                for (int j = 0; j < 3; j++) tma2d(st + 16384 + j * 8192, &mapB, bars + 8 * c, nb * 192 + j * 64, c * 64);
            }
            map_prefetch(&mapA);
            pdl_wait();
            pdl_launch();
            for (int c = 0; c < K1_ST; c++) tma2d(sbase + c * K1_STAGE, &mapA, bars + 8 * c, c * 64, mb * 128);
            l2_prefetch(pwg + blockIdx.x * 14336, 14336);
            l2_prefetch(pwu + blockIdx.x * 14336, 14336);
            l2_prefetch(pwd + blockIdx.x * 14336, 14336);
            l2_prefetch(pwo + blockIdx.x * 4096, 4096);
            for (int c = K1_ST; c < 8; c++) {
                const int s = c - K1_ST;
                const uint32_t st = sbase + s * K1_STAGE;
                mbar_wait(bars + 8 * (K1_ST + s), 0);
                mbar_expect_tx(bars + 8 * s, K1_STAGE);
                tma2d(st, &mapA, bars + 8 * s, c * 64, mb * 128);
                for (int j = 0; j < 3; j++) tma2d(st + 16384 + j * 8192, &mapB, bars + 8 * s, nb * 192 + j * 64, c * 64);
            }
        }
        return;
    }
    const int wg = warp >> 2;
    float acc[96];
#pragma unroll
    for (int i = 0; i < 96; i++) acc[i] = 0.f;
#pragma unroll 1
    for (int c = 0; c < 8; c++) {
        const int s = c < K1_ST ? c : c - K1_ST;
        const uint32_t st = sbase + s * K1_STAGE;
        mbar_wait(bars + 8 * s, c < K1_ST ? 0 : 1);
        if (c == 0) TL(1, 1);
        const uint64_t da = mkdesc(st + wg * 8192, 16, 1024, 1);
        const uint64_t db = mkdesc(st + 16384, 8192, 1024, 1);
        WG_FENCE();
#pragma unroll
        for (int k = 0; k < 4; k++) wgmma_n192(acc, da + k * 2, db + k * 128, (c | k) != 0);
        WG_COMMIT();
        if (c + K1_ST < 8 + 1) {
            WG_WAIT(1);
            if (c >= 1 && (threadIdx.x & 127) == 0) mbar_arrive(bars + 8 * (K1_ST + c - 1));
        }
    }
    WG_WAIT(0);
    TL(1, 2);
    const int g = lane >> 2, t = lane & 3;
    const int mt = mb * 8 + warp;
#pragma unroll
    for (int hh = 0; hh < 12; hh++) {
        const int gh = nb * 12 + hh;
        const float* a = &acc[hh * 8];
        if (gh < 32) {
            uint4 v;
            v.x = packbf(a[0], a[1]); v.y = packbf(a[2], a[3]);
            v.z = packbf(a[4], a[5]); v.w = packbf(a[6], a[7]);
            g_q[(gh * 128 + mt) * 32 + lane] = v;
        } else {
            uint32_t* dst = reinterpret_cast<uint32_t*>(gh < 64 ? g_k + (gh - 32) * 4096 : g_v + (gh - 64) * 4096);
            const float ks = gh < 64 ? 5.421010862427522e-20f : 1.0f;
            const int off = (mt * 16 + g) * 4 + t;
            dst[off] = packbf(a[0] * ks, a[1] * ks);
            dst[off + 32] = packbf(a[2] * ks, a[3] * ks);
            dst[8192 + off] = packbf(a[4] * ks, a[5] * ks);
            dst[8192 + off + 32] = packbf(a[6] * ks, a[7] * ks);
        }
    }
    TL(1, 3);
}

constexpr float SHIFT = 90.0f;
constexpr float QS = 0.25f * 1.4426950408889634f * 18446744073709551616.0f;
constexpr float scq = 0.25f * 1.4426950408889634f * 3.3087224502121107e-24f;
constexpr int K2_SMEM = 163840 + 1024 + 128;

__device__ __forceinline__ uint32_t polyexp(float lo, float hi) {
    uint32_t w, g, q, h;
    asm("cvt.pack.sat.s16.s32 %0, %1, %2;" : "=r"(w) : "r"(__float_as_uint(hi)), "r"(__float_as_uint(lo)));
    g = w & 0x007F007Fu;
    asm("fma.rn.f16x2 %0, %1, %2, %3;" : "=r"(q) : "r"(g), "r"(0xf940f940u), "r"(0x35513551u));
    asm("mul.rn.f16x2 %0, %1, %2;" : "=r"(h) : "r"(q), "r"(g));
    return w - h;
}
__device__ __forceinline__ void qk64(float (&s)[32], const uint32_t (&q)[4], uint64_t db) {
    asm volatile("wgmma.mma_async.sync.aligned.m64n64k16.f32.bf16.bf16 "
        "{%0,%1,%2,%3,%4,%5,%6,%7,%8,%9,%10,%11,%12,%13,%14,%15,%16,%17,%18,%19,%20,%21,%22,%23,%24,%25,%26,%27,%28,%29,%30,%31}, "
        "{%32,%33,%34,%35}, %36, 0, 1, 1, 0;"
        : "=f"(s[0]), "=f"(s[1]), "=f"(s[2]), "=f"(s[3]), "=f"(s[4]), "=f"(s[5]), "=f"(s[6]), "=f"(s[7]),
          "=f"(s[8]), "=f"(s[9]), "=f"(s[10]), "=f"(s[11]), "=f"(s[12]), "=f"(s[13]), "=f"(s[14]), "=f"(s[15]),
          "=f"(s[16]), "=f"(s[17]), "=f"(s[18]), "=f"(s[19]), "=f"(s[20]), "=f"(s[21]), "=f"(s[22]), "=f"(s[23]),
          "=f"(s[24]), "=f"(s[25]), "=f"(s[26]), "=f"(s[27]), "=f"(s[28]), "=f"(s[29]), "=f"(s[30]), "=f"(s[31])
        : "r"(q[0]), "r"(q[1]), "r"(q[2]), "r"(q[3]), "l"(db));
}
__device__ __forceinline__ void pv24(float (&o)[12], uint32_t a0, uint32_t a1, uint32_t a2, uint32_t a3, uint64_t db) {
    asm volatile("wgmma.mma_async.sync.aligned.m64n24k16.f32.bf16.bf16 "
        "{%0,%1,%2,%3,%4,%5,%6,%7,%8,%9,%10,%11}, {%12,%13,%14,%15}, %16, 1, 1, 1, 1;"
        : "+f"(o[0]), "+f"(o[1]), "+f"(o[2]), "+f"(o[3]), "+f"(o[4]), "+f"(o[5]), "+f"(o[6]), "+f"(o[7]),
          "+f"(o[8]), "+f"(o[9]), "+f"(o[10]), "+f"(o[11])
        : "r"(a0), "r"(a1), "r"(a2), "r"(a3), "l"(db));
}

__device__ __forceinline__ void attn_safe(float (&o)[12], const uint32_t (&q)[4], uint64_t kdesc0, uint64_t vdesc0) {
    float s[32];
    float m0 = -INFINITY, m1 = -INFINITY;
#pragma unroll
    for (int i = 0; i < 12; i++) o[i] = 0.f;
#pragma unroll 1
    for (int j = 0; j < 32; j++) {
        WG_FENCE();
        qk64(s, q, kdesc0 + (uint64_t)(j * 64));
        WG_COMMIT(); WG_WAIT(0);
        float n0 = m0, n1 = m1;
#pragma unroll
        for (int i = 0; i < 8; i++) { n0 = fmaxf(n0, fmaxf(s[4 * i], s[4 * i + 1])); n1 = fmaxf(n1, fmaxf(s[4 * i + 2], s[4 * i + 3])); }
        n0 = fmaxf(n0, __shfl_xor_sync(~0u, n0, 1)); n0 = fmaxf(n0, __shfl_xor_sync(~0u, n0, 2));
        n1 = fmaxf(n1, __shfl_xor_sync(~0u, n1, 1)); n1 = fmaxf(n1, __shfl_xor_sync(~0u, n1, 2));
        const float c0 = ex2((m0 - n0) * QS), c1 = ex2((m1 - n1) * QS);
        m0 = n0; m1 = n1;
#pragma unroll
        for (int i = 0; i < 3; i++) { o[4 * i] *= c0; o[4 * i + 1] *= c0; o[4 * i + 2] *= c1; o[4 * i + 3] *= c1; }
        uint32_t p[16];
#pragma unroll
        for (int i = 0; i < 8; i++) {
            p[2 * i] = packbf(ex2((s[4 * i] - m0) * QS), ex2((s[4 * i + 1] - m0) * QS));
            p[2 * i + 1] = packbf(ex2((s[4 * i + 2] - m1) * QS), ex2((s[4 * i + 3] - m1) * QS));
        }
        WG_FENCE();
#pragma unroll
        for (int kk = 0; kk < 4; kk++) pv24(o, p[4 * kk], p[4 * kk + 1], p[4 * kk + 2], p[4 * kk + 3], vdesc0 + (uint64_t)(j * 64 + kk * 16));
        WG_COMMIT(); WG_WAIT(0);
    }
}

__device__ __forceinline__ void attn_store(const float (&o)[12], int head, int m64, int warp, int lane) {
    const int g = lane >> 2, t = lane & 3;
    const int row = m64 * 64 + warp * 16 + g;
    const float i0 = 1.f / o[8], i1 = 1.f / o[10];
    uint32_t* p0 = reinterpret_cast<uint32_t*>(g_o + (size_t)row * DM + head * 16 + t * 2);
    uint32_t* p1 = reinterpret_cast<uint32_t*>(g_o + (size_t)(row + 8) * DM + head * 16 + t * 2);
    p0[0] = packbf(o[0] * i0, o[1] * i0); p0[4] = packbf(o[4] * i0, o[5] * i0);
    p1[0] = packbf(o[2] * i1, o[3] * i1); p1[4] = packbf(o[6] * i1, o[7] * i1);
}

constexpr int FS_N = 4;
constexpr int FS_BYTES = 28672;
__device__ void ffn_block(int c, uint8_t* smem, uint32_t sbase, const CUtensorMap* mapG, const CUtensorMap* mapU,
                          const __nv_bfloat16* __restrict__ wd) {
    const int tid = threadIdx.x, warp = tid >> 5, lane = tid & 31;
    float* red = reinterpret_cast<float*>(smem + FS_N * FS_BYTES);
    float* sx = reinterpret_cast<float*>(smem + (FS_N + 1) * FS_BYTES);
    float* sh = sx + 1024;
    const uint32_t bars = sbase + (FS_N + 1) * FS_BYTES + 8192;
    __shared__ float tv[32]; __shared__ int ti[32];
    __shared__ int ssel[2];
    auto issue = [&](int item) {
        const int slot = item % FS_N;
        const uint32_t dst = sbase + slot * FS_BYTES, bar = bars + 8 * slot;
        mbar_expect_tx(bar, FS_BYTES);
        if (item < 32) {
            tma2d(dst, mapG, bar, c * 448, item * 16);
            tma2d(dst + 7168, mapG, bar, c * 448 + 224, item * 16);
            tma2d(dst + 14336, mapU, bar, c * 448, item * 16);
            tma2d(dst + 21504, mapU, bar, c * 448 + 224, item * 16);
        } else {
            bulk_g2s(dst, wd + ((size_t)c * 448 + (item - 32) * 28) * DM, FS_BYTES, bar);
        }
    };
    if (tid == 0) {
        for (int i = 0; i < FS_N; i++) mbar_init(bars + 8 * i, 1);
        fence_barrier_init();
        for (int i = 0; i < FS_N; i++) issue(i);
    }
    float b1 = -INFINITY, b2 = -INFINITY; int i1 = 0x7fffffff, i2 = 0x7fffffff;
    auto push = [&](float v, int i) {
        if (v > b1 || (v == b1 && i < i1)) { b2 = b1; i2 = i1; b1 = v; i1 = i; }
        else if (v > b2 || (v == b2 && i < i2)) { b2 = v; i2 = i; }
    };
    {
        const float4 rv = reinterpret_cast<const float4*>(g_r)[tid];
        push(rv.x, 4 * tid); push(rv.y, 4 * tid + 1); push(rv.z, 4 * tid + 2); push(rv.w, 4 * tid + 3);
    }
#pragma unroll
    for (int o = 16; o > 0; o >>= 1) {
        float v1 = __shfl_xor_sync(~0u, b1, o), v2 = __shfl_xor_sync(~0u, b2, o);
        int j1 = __shfl_xor_sync(~0u, i1, o), j2 = __shfl_xor_sync(~0u, i2, o);
        push(v1, j1); push(v2, j2);
    }
    if (lane == 0) { tv[2 * warp] = b1; ti[2 * warp] = i1; tv[2 * warp + 1] = b2; ti[2 * warp + 1] = i2; }
    __syncthreads();
    if (warp == 1) {
        b1 = tv[lane]; i1 = ti[lane]; b2 = -INFINITY; i2 = 0x7fffffff;
#pragma unroll
        for (int o = 16; o > 0; o >>= 1) {
            float v1 = __shfl_xor_sync(~0u, b1, o), v2 = __shfl_xor_sync(~0u, b2, o);
            int j1 = __shfl_xor_sync(~0u, i1, o), j2 = __shfl_xor_sync(~0u, i2, o);
            push(v1, j1); push(v2, j2);
        }
        if (lane == 0) {
            i1 = min(max(i1, 0), S_LEN - 1); i2 = min(max(i2, 0), S_LEN - 1);
            ssel[0] = i1; ssel[1] = i2;
            if (c == 0) {
                g_sel[0] = i1; g_sel[1] = i2;
                g_gate[0] = bfr(1.f / (1.f + __expf(-bfr(b1))));
                g_gate[1] = bfr(1.f / (1.f + __expf(-bfr(b2))));
            }
        }
    }
    __syncthreads();
    {
        const uint32_t v = *reinterpret_cast<const uint32_t*>(g_xn + (size_t)ssel[tid >> 8] * DM + (tid & 255) * 2);
        sx[2 * tid] = bf_lo(v); sx[2 * tid + 1] = bf_hi(v);
    }
    __syncthreads();
    TL(2, 1);
    {
        const int kg = tid / 56, ch = tid % 56;
        float ag[2][8], au[2][8];
#pragma unroll
        for (int j = 0; j < 8; j++) { ag[0][j] = ag[1][j] = au[0][j] = au[1][j] = 0.f; }
#pragma unroll 1
        for (int it = 0; it < 32; it++) {
            const int slot = it % FS_N;
            mbar_wait(bars + 8 * slot, (it / FS_N) & 1);
            if (kg < 8) {
                const uint8_t* base = smem + slot * FS_BYTES + (ch / 28) * 7168 + (ch % 28) * 16;
#pragma unroll
                for (int h = 0; h < 2; h++) {
                    const int r = kg + h * 8;
                    const uint4 vg = *reinterpret_cast<const uint4*>(base + r * 448);
                    const uint4 vu = *reinterpret_cast<const uint4*>(base + 14336 + r * 448);
                    const float x0 = sx[it * 16 + r], x1 = sx[512 + it * 16 + r];
                    const uint32_t gw[4] = {vg.x, vg.y, vg.z, vg.w}, uw[4] = {vu.x, vu.y, vu.z, vu.w};
#pragma unroll
                    for (int j = 0; j < 4; j++) {
                        const float g0 = bf_lo(gw[j]), g1 = bf_hi(gw[j]), u0 = bf_lo(uw[j]), u1 = bf_hi(uw[j]);
                        ag[0][2 * j] = fmaf(x0, g0, ag[0][2 * j]); ag[0][2 * j + 1] = fmaf(x0, g1, ag[0][2 * j + 1]);
                        ag[1][2 * j] = fmaf(x1, g0, ag[1][2 * j]); ag[1][2 * j + 1] = fmaf(x1, g1, ag[1][2 * j + 1]);
                        au[0][2 * j] = fmaf(x0, u0, au[0][2 * j]); au[0][2 * j + 1] = fmaf(x0, u1, au[0][2 * j + 1]);
                        au[1][2 * j] = fmaf(x1, u0, au[1][2 * j]); au[1][2 * j + 1] = fmaf(x1, u1, au[1][2 * j + 1]);
                    }
                }
            }
            __syncthreads();
            if (tid == 0) issue(it + FS_N);
        }
#pragma unroll
        for (int tok = 0; tok < 2; tok++) {
            if (kg < 8) {
#pragma unroll
                for (int j = 0; j < 8; j++) { red[(kg * 2) * 448 + ch * 8 + j] = ag[tok][j]; red[(kg * 2 + 1) * 448 + ch * 8 + j] = au[tok][j]; }
            }
            __syncthreads();
            if (tid < 448) {
                float gs = 0.f, us = 0.f;
#pragma unroll
                for (int q = 0; q < 8; q++) { gs += red[(q * 2) * 448 + tid]; us += red[(q * 2 + 1) * 448 + tid]; }
                gs = bfr(gs); us = bfr(us);
                const float sg = bfr(gs / (1.f + __expf(-gs)));
                sh[tok * 448 + tid] = bfr(sg * us);
            }
            __syncthreads();
        }
    }
    TL(2, 2);
    {
        const int ch = tid & 63, kg = tid >> 6;
        float a[2][8];
#pragma unroll
        for (int j = 0; j < 8; j++) a[0][j] = a[1][j] = 0.f;
#pragma unroll 1
        for (int it = 32; it < 48; it++) {
            const int slot = it % FS_N;
            mbar_wait(bars + 8 * slot, (it / FS_N) & 1);
            const uint8_t* base = smem + slot * FS_BYTES + ch * 16;
#pragma unroll
            for (int h = 0; h < 4; h++) {
                const int r = kg + h * 8;
                if (r < 28) {
                    const uint4 v = *reinterpret_cast<const uint4*>(base + r * 1024);
                    const float h0 = sh[(it - 32) * 28 + r], h1 = sh[448 + (it - 32) * 28 + r];
                    const uint32_t w[4] = {v.x, v.y, v.z, v.w};
#pragma unroll
                    for (int j = 0; j < 4; j++) {
                        const float w0 = bf_lo(w[j]), w1 = bf_hi(w[j]);
                        a[0][2 * j] = fmaf(h0, w0, a[0][2 * j]); a[0][2 * j + 1] = fmaf(h0, w1, a[0][2 * j + 1]);
                        a[1][2 * j] = fmaf(h1, w0, a[1][2 * j]); a[1][2 * j + 1] = fmaf(h1, w1, a[1][2 * j + 1]);
                    }
                }
            }
            __syncthreads();
            if (tid == 0 && it + FS_N < 48) issue(it + FS_N);
        }
        float* red2 = reinterpret_cast<float*>(smem);
#pragma unroll
        for (int j = 0; j < 8; j++) { red2[(kg * 2) * 512 + ch * 8 + j] = a[0][j]; red2[(kg * 2 + 1) * 512 + ch * 8 + j] = a[1][j]; }
        __syncthreads();
        for (int i = tid; i < 1024; i += 512) {
            float sum = 0.f;
#pragma unroll
            for (int q = 0; q < 8; q++) sum += red2[q * 1024 + i];
            g_ypart[c * 1024 + i] = sum;
        }
    }
}

__global__ void __launch_bounds__(512, 1) attn_kernel(const __grid_constant__ CUtensorMap mapG, const __grid_constant__ CUtensorMap mapU,
                                                      const __nv_bfloat16* __restrict__ wd_, float sc) {
    extern __shared__ uint8_t smem_raw[];
    const uint32_t sraw = smem_u32(smem_raw);
    const uint32_t sbase = (sraw + 1023u) & ~1023u;
    uint8_t* sptr = smem_raw + (sbase - sraw);
    TL(2, 0);
    if (blockIdx.x < 4) {
        pdl_launch();
        ffn_block(blockIdx.x, sptr, sbase, &mapG, &mapU, wd_);
        TL(2, 3);
        return;
    }
    const uint32_t bars = sbase + 163840;
    const int head = (blockIdx.x - 4) >> 2, quarter = blockIdx.x & 3;
    const int wg = threadIdx.x >> 7, warp = (threadIdx.x >> 5) & 3, lane = threadIdx.x & 31;
    if (threadIdx.x == 0) {
        for (int c = 0; c < 8; c++) mbar_init(bars + 8 * c, 1);
        fence_barrier_init();
    }
    {
        uint4* ones = reinterpret_cast<uint4*>(sptr + 131072);
        for (int i = threadIdx.x; i < 2048; i += 512) ones[i] = make_uint4(0x3f803f80u, 0x3f803f80u, 0x3f803f80u, 0x3f803f80u);
        fence_proxy_async();
    }
    __syncthreads();
    pdl_wait();
    pdl_launch();
    TL(2, 1);
    if (threadIdx.x == 0) {
        const uint8_t* kp = reinterpret_cast<const uint8_t*>(g_k + head * 4096);
        const uint8_t* vp = reinterpret_cast<const uint8_t*>(g_v + head * 4096);
        for (int c = 0; c < 8; c++) {
            mbar_expect_tx(bars + 8 * c, 16384);
            bulk_g2s(sbase + c * 4096, kp + c * 4096, 4096, bars + 8 * c);
            bulk_g2s(sbase + 32768 + c * 4096, kp + 32768 + c * 4096, 4096, bars + 8 * c);
            bulk_g2s(sbase + 65536 + c * 4096, vp + c * 4096, 4096, bars + 8 * c);
            bulk_g2s(sbase + 98304 + c * 4096, vp + 32768 + c * 4096, 4096, bars + 8 * c);
        }
    }
    const uint64_t kdesc0 = mkdesc(sbase, 32768, 128, 0);
    const uint64_t vdesc0 = mkdesc(sbase + 65536, 128, 32768, 0);
    uint32_t badmask = 0;
#pragma unroll 1
    for (int mt = 0; mt < 2; mt++) {
        const int m64 = quarter * 8 + mt * 4 + wg;
        uint32_t q[4];
        { const uint4 qq = g_q[(head * 128 + m64 * 4 + warp) * 32 + lane]; q[0] = qq.x; q[1] = qq.y; q[2] = qq.z; q[3] = qq.w; }
        float s[32], s2[32], o[12];
#pragma unroll
        for (int i = 0; i < 12; i++) o[i] = 0.f;
        mbar_wait(bars, 0);
        if (mt == 0) TL(2, 2);
        WG_FENCE();
        qk64(s, q, kdesc0);
        WG_COMMIT(); WG_WAIT(0);
        float mx0 = -INFINITY, mx1 = -INFINITY;
#pragma unroll
        for (int i = 0; i < 8; i++) { mx0 = fmaxf(mx0, fmaxf(s[4 * i], s[4 * i + 1])); mx1 = fmaxf(mx1, fmaxf(s[4 * i + 2], s[4 * i + 3])); }
        mx0 = fmaxf(mx0, __shfl_xor_sync(~0u, mx0, 1)); mx0 = fmaxf(mx0, __shfl_xor_sync(~0u, mx0, 2));
        mx1 = fmaxf(mx1, __shfl_xor_sync(~0u, mx1, 1)); mx1 = fmaxf(mx1, __shfl_xor_sync(~0u, mx1, 2));
        float cm0 = -(ceilf(mx0 * QS) + SHIFT), cm1 = -(ceilf(mx1 * QS) + SHIFT);
        float cp0 = (cm0 + 127.f) * sc, cp1 = (cm1 + 127.f) * sc;
        asm volatile("" : "+f"(cm0), "+f"(cm1), "+f"(cp0), "+f"(cp1));
        uint64_t kd = kdesc0, vd = vdesc0;
        auto step = [&](float (&sc_)[32], float (&sn)[32]) {
            kd += 64;
            WG_FENCE();
            qk64(sn, q, kd);
            WG_COMMIT();
#pragma unroll
            for (int kk = 0; kk < 4; kk++) {
                const int i0 = kk * 2, i1 = kk * 2 + 1;
                const uint32_t p0 = packbf(ex2(fmaf(sc_[4 * i0], QS, cm0)), ex2(fmaf(sc_[4 * i0 + 1], QS, cm0)));
                const uint32_t p1 = packbf(ex2(fmaf(sc_[4 * i0 + 2], QS, cm1)), ex2(fmaf(sc_[4 * i0 + 3], QS, cm1)));
                const uint32_t p2 = polyexp(fmaf(sc_[4 * i1], scq, cp0), fmaf(sc_[4 * i1 + 1], scq, cp0));
                const uint32_t p3 = polyexp(fmaf(sc_[4 * i1 + 2], scq, cp1), fmaf(sc_[4 * i1 + 3], scq, cp1));
                WG_FENCE();
                pv24(o, p0, p1, p2, p3, vd);
                vd += 16;
            }
            WG_COMMIT();
            WG_WAIT(1);
        };
#pragma unroll 1
        for (int c = 0; c < 16; c++) {
            if (mt == 0 && (c & 1) == 0 && c < 14) mbar_wait(bars + 4 * c + 8, 0);
            step(s, s2); step(s2, s);
        }
        WG_WAIT(0);
        bool bad = !(o[8] > 0.f) || !(o[10] > 0.f);
#pragma unroll
        for (int i = 0; i < 12; i++) bad = bad || !(fabsf(o[i]) <= 3.0e38f);
        uint32_t anybad;
        asm volatile("{\n.reg .pred p, q;\nsetp.ne.u32 p, %1, 0;\nbarrier.cta.red.or.pred q, %2, 128, p;\nselp.u32 %0, 1, 0, q;\n}"
                     : "=r"(anybad) : "r"((uint32_t)bad), "r"(wg + 1) : "memory");
        badmask |= anybad << mt;
        attn_store(o, head, m64, warp, lane);
    }
#pragma unroll 1
    for (int mt = 0; mt < 2; mt++) {
        if (!((badmask >> mt) & 1)) continue;
        const int m64 = quarter * 8 + mt * 4 + wg;
        uint32_t q[4];
        { const uint4 qq = g_q[(head * 128 + m64 * 4 + warp) * 32 + lane]; q[0] = qq.x; q[1] = qq.y; q[2] = qq.z; q[3] = qq.w; }
        float o[12];
        attn_safe(o, q, mkdesc(sbase, 32768, 128, 0), mkdesc(sbase + 65536, 128, 32768, 0));
        attn_store(o, head, m64, warp, lane);
    }
    TL(2, 3);
}

constexpr int K3_SMEM = 8 * 8192 + 8 * 16384 + 1024 + 128;

__device__ __forceinline__ void wgmma_n64(float (&d)[32], uint64_t da, uint64_t db, int scale_d) {
    asm volatile("{\n.reg .pred p;\nsetp.ne.b32 p, %34, 0;\n"
        "wgmma.mma_async.sync.aligned.m64n64k16.f32.bf16.bf16 "
        "{%0,%1,%2,%3,%4,%5,%6,%7,%8,%9,%10,%11,%12,%13,%14,%15,%16,%17,%18,%19,%20,%21,%22,%23,%24,%25,%26,%27,%28,%29,%30,%31}, "
        "%32, %33, p, 1, 1, 0, 1;\n}"
        : "+f"(d[0]), "+f"(d[1]), "+f"(d[2]), "+f"(d[3]), "+f"(d[4]), "+f"(d[5]), "+f"(d[6]), "+f"(d[7]),
          "+f"(d[8]), "+f"(d[9]), "+f"(d[10]), "+f"(d[11]), "+f"(d[12]), "+f"(d[13]), "+f"(d[14]), "+f"(d[15]),
          "+f"(d[16]), "+f"(d[17]), "+f"(d[18]), "+f"(d[19]), "+f"(d[20]), "+f"(d[21]), "+f"(d[22]), "+f"(d[23]),
          "+f"(d[24]), "+f"(d[25]), "+f"(d[26]), "+f"(d[27]), "+f"(d[28]), "+f"(d[29]), "+f"(d[30]), "+f"(d[31])
        : "l"(da), "l"(db), "r"(scale_d));
}

__global__ void __launch_bounds__(256, 1) oproj_kernel(const __grid_constant__ CUtensorMap mapA, const __grid_constant__ CUtensorMap mapB,
                                                       const __nv_bfloat16* __restrict__ x, __nv_bfloat16* __restrict__ out) {
    extern __shared__ uint8_t smem_raw[];
    const uint32_t sbase = (smem_u32(smem_raw) + 1023u) & ~1023u;
    const uint32_t sA = sbase, sB = sbase + 8 * 8192, bars = sbase + 8 * 8192 + 8 * 16384;
    const int warp = threadIdx.x >> 5, lane = threadIdx.x & 31, wg = warp >> 2;
    const int nb = blockIdx.x & 3, mb = blockIdx.x >> 2;
    TL(3, 0);
    if (threadIdx.x == 0) {
        for (int c = 0; c < 8; c++) mbar_init(bars + 8 * c, 1);
        fence_barrier_init();
        map_prefetch(&mapA);
        for (int c = 0; c < 8; c++) {
            mbar_expect_tx(bars + 8 * c, 8192 + 16384);
            tma2d(sB + c * 16384, &mapB, bars + 8 * c, nb * 128, c * 64);
            tma2d(sB + c * 16384 + 8192, &mapB, bars + 8 * c, nb * 128 + 64, c * 64);
        }
    }
    const int g = lane >> 2, t = lane & 3;
    const int row0 = mb * 64 + (warp & 3) * 16 + g;
    const int col0 = nb * 128 + wg * 64 + t * 2;
    uint32_t xv[16], nv[16];
#pragma unroll
    for (int i = 0; i < 8; i++) {
        xv[2 * i] = *reinterpret_cast<const uint32_t*>(x + (size_t)row0 * DM + col0 + i * 8);
        xv[2 * i + 1] = *reinterpret_cast<const uint32_t*>(x + (size_t)(row0 + 8) * DM + col0 + i * 8);
        nv[2 * i] = *reinterpret_cast<const uint32_t*>(g_xn + (size_t)row0 * DM + col0 + i * 8);
        nv[2 * i + 1] = *reinterpret_cast<const uint32_t*>(g_xn + (size_t)(row0 + 8) * DM + col0 + i * 8);
    }
    __syncthreads();
    pdl_wait();
    TL(3, 1);
    if (threadIdx.x == 0) {
        for (int c = 0; c < 8; c++) tma2d(sA + c * 8192, &mapA, bars + 8 * c, c * 64, mb * 64);
    }
    __shared__ float supd[2][128];
    const int sel0 = g_sel[0], sel1 = g_sel[1];
    {
        const int which = threadIdx.x >> 7, col = nb * 128 + (threadIdx.x & 127);
        const float y = g_ypart[which * 512 + col] + g_ypart[1024 + which * 512 + col] + g_ypart[2048 + which * 512 + col] + g_ypart[3072 + which * 512 + col];
        supd[which][threadIdx.x & 127] = bfr(bfr(y) * g_gate[which]);
    }
    __syncthreads();
    float acc[32];
#pragma unroll
    for (int i = 0; i < 32; i++) acc[i] = 0.f;
#pragma unroll 1
    for (int c = 0; c < 8; c++) {
        mbar_wait(bars + 8 * c, 0);
        const uint64_t da = mkdesc(sA + c * 8192, 16, 1024, 1);
        const uint64_t db = mkdesc(sB + c * 16384 + wg * 8192, 8192, 1024, 1);
        WG_FENCE();
#pragma unroll
        for (int k = 0; k < 4; k++) wgmma_n64(acc, da + k * 2, db + k * 128, (c | k) != 0);
        WG_COMMIT();
    }
    WG_WAIT(0);
    TL(3, 2);
#pragma unroll
    for (int h = 0; h < 2; h++) {
        const int row = row0 + h * 8;
        const int which = row == sel0 ? 0 : (row == sel1 ? 1 : -1);
#pragma unroll
        for (int i = 0; i < 8; i++) {
            const int col = col0 + i * 8;
            float b0 = bf_lo(nv[2 * i + h]), b1 = bf_hi(nv[2 * i + h]);
            if (which >= 0) {
                b0 = bfr(b0 + supd[which][col - nb * 128]); b1 = bfr(b1 + supd[which][col + 1 - nb * 128]);
            }
            const float t0 = bfr(bf_lo(xv[2 * i + h]) + bfr(acc[4 * i + 2 * h]));
            const float t1 = bfr(bf_hi(xv[2 * i + h]) + bfr(acc[4 * i + 2 * h + 1]));
            *reinterpret_cast<uint32_t*>(out + (size_t)row * DM + col) = packbf(t0 + b0, t1 + b1);
        }
    }
    TL(3, 3);
}

typedef CUresult (*EncodeFn)(CUtensorMap*, CUtensorMapDataType, cuuint32_t, void*, const cuuint64_t*, const cuuint64_t*,
                             const cuuint32_t*, const cuuint32_t*, CUtensorMapInterleave, CUtensorMapSwizzle,
                             CUtensorMapL2promotion, CUtensorMapFloatOOBfill);

void make_map(EncodeFn fn, CUtensorMap* m, const void* ptr, uint64_t inner, uint64_t outer, uint32_t box_inner, uint32_t box_outer,
              CUtensorMapSwizzle swz = CU_TENSOR_MAP_SWIZZLE_128B) {
    cuuint64_t dims[2] = {inner, outer};
    cuuint64_t strides[1] = {inner * 2};
    cuuint32_t box[2] = {box_inner, box_outer};
    cuuint32_t es[2] = {1, 1};
    fn(m, CU_TENSOR_MAP_DATA_TYPE_BFLOAT16, 2, const_cast<void*>(ptr), dims, strides, box, es, CU_TENSOR_MAP_INTERLEAVE_NONE,
       swz, CU_TENSOR_MAP_L2_PROMOTION_L2_256B, CU_TENSOR_MAP_FLOAT_OOB_FILL_NONE);
}

template <typename... KArgs, typename... Args>
void launch(void (*kern)(KArgs...), int grid, int block, int smem, bool pdl, Args... args) {
    cudaLaunchConfig_t cfg = {};
    cfg.gridDim = dim3(grid); cfg.blockDim = dim3(block); cfg.dynamicSmemBytes = smem; cfg.stream = cudaStreamPerThread;
    cudaLaunchAttribute at[1];
    at[0].id = cudaLaunchAttributeProgrammaticStreamSerialization;
    at[0].val.programmaticStreamSerializationAllowed = 1;
    cfg.attrs = at; cfg.numAttrs = pdl ? 1 : 0;
    cudaLaunchKernelEx(&cfg, kern, KArgs(args)...);
}

}

extern "C" void kernel_launch(void* const* d_in, const int* in_sizes, int n_in, void* d_out, int out_size) {
    const __nv_bfloat16* x = (const __nv_bfloat16*)d_in[0];
    const __nv_bfloat16* wqkv = (const __nv_bfloat16*)d_in[1];
    const __nv_bfloat16* wo = (const __nv_bfloat16*)d_in[2];
    const __nv_bfloat16* wr = (const __nv_bfloat16*)d_in[4];
    const __nv_bfloat16* wgate = (const __nv_bfloat16*)d_in[5];
    const __nv_bfloat16* wup = (const __nv_bfloat16*)d_in[6];
    const __nv_bfloat16* wdown = (const __nv_bfloat16*)d_in[7];
    __nv_bfloat16* out = (__nv_bfloat16*)d_out;

    static EncodeFn enc = nullptr;
    static void* p_xn = nullptr; static void* p_o = nullptr;
    if (!enc) {
        void* fn = nullptr; cudaDriverEntryPointQueryResult qr;
        cudaGetDriverEntryPoint("cuTensorMapEncodeTiled", &fn, cudaEnableDefault, &qr);
        enc = (EncodeFn)fn;
        cudaGetSymbolAddress(&p_xn, g_xn);
        cudaGetSymbolAddress(&p_o, g_o);
        cudaFuncSetAttribute(qkv_kernel, cudaFuncAttributeMaxDynamicSharedMemorySize, K1_SMEM);
        cudaFuncSetAttribute(attn_kernel, cudaFuncAttributeMaxDynamicSharedMemorySize, K2_SMEM);
        cudaFuncSetAttribute(oproj_kernel, cudaFuncAttributeMaxDynamicSharedMemorySize, K3_SMEM);
    }
    CUtensorMap mXn, mWqkv, mO, mWo, mG, mU;
    make_map(enc, &mG, wgate, FF, DM, 224, 16, CU_TENSOR_MAP_SWIZZLE_NONE);
    make_map(enc, &mU, wup, FF, DM, 224, 16, CU_TENSOR_MAP_SWIZZLE_NONE);
    make_map(enc, &mXn, p_xn, DM, S_LEN, 64, 128);
    make_map(enc, &mWqkv, wqkv, 3 * DM, DM, 64, 64);
    make_map(enc, &mO, p_o, DM, S_LEN, 64, 64);
    make_map(enc, &mWo, wo, DM, DM, 64, 64);

    union { uint32_t u; float f; } scu; scu.u = 128u;

    launch(ln_kernel, S_LEN / 8, 256, 0, false, x, wr);
    launch(qkv_kernel, 128, 288, K1_SMEM, true, mXn, mWqkv, (const uint8_t*)wgate, (const uint8_t*)wup, (const uint8_t*)wdown, (const uint8_t*)wo);
    launch(attn_kernel, 132, 512, K2_SMEM, true, mG, mU, wdown, scu.f);
    launch(oproj_kernel, 128, 256, K3_SMEM, true, mO, mWo, x, out);
}
```

```cpp
#include <cuda_runtime.h>
#include <cuda_bf16.h>
#include <cuda.h>
#include <stdint.h>
#include <type_traits>

namespace {

constexpr int S_LEN = 2048;
constexpr int DM = 512;
constexpr int NH = 32;
constexpr int FF = 1792;

__device__ __align__(1024) __nv_bfloat16 g_xn[S_LEN * DM];
__device__ __align__(16) float g_r[S_LEN];
__device__ __align__(1024) uint4 g_q[NH * 128 * 32];
__device__ __align__(1024) uint4 g_k[NH * 4096];
__device__ __align__(1024) uint4 g_v[NH * 4096];
__device__ __align__(1024) __nv_bfloat16 g_o[S_LEN * DM];
__device__ __align__(16) float g_ypart[4 * 2 * DM];
__device__ int g_sel[2];
__device__ float g_gate[2];

#define TL(k, slot) do {} while (0)

__device__ __forceinline__ uint32_t smem_u32(const void* p) { return (uint32_t)__cvta_generic_to_shared(p); }
__device__ __forceinline__ void pdl_wait() { asm volatile("griddepcontrol.wait;" ::: "memory"); }
__device__ __forceinline__ void pdl_launch() { asm volatile("griddepcontrol.launch_dependents;" ::: "memory"); }
__device__ __forceinline__ void mbar_init(uint32_t bar, uint32_t cnt) {
    asm volatile("mbarrier.init.shared::cta.b64 [%0], %1;" :: "r"(bar), "r"(cnt) : "memory");
}
__device__ __forceinline__ void mbar_expect_tx(uint32_t bar, uint32_t bytes) {
    asm volatile("mbarrier.arrive.expect_tx.shared::cta.b64 _, [%0], %1;" :: "r"(bar), "r"(bytes) : "memory");
}
__device__ __forceinline__ void mbar_arrive(uint32_t bar) {
    asm volatile("mbarrier.arrive.shared::cta.b64 _, [%0];" :: "r"(bar) : "memory");
}
__device__ __forceinline__ void mbar_wait(uint32_t bar, uint32_t parity) {
    asm volatile("{\n.reg .pred p;\n.reg .u32 n;\nmov.u32 n, 0;\n"
                 "WAIT_%=:\n"
                 "mbarrier.try_wait.parity.shared::cta.b64 p, [%0], %1;\n"
                 "@p bra DONE_%=;\n"
                 "add.u32 n, n, 1;\n"
                 "setp.lt.u32 p, n, 4000000;\n"
                 "@p bra WAIT_%=;\n"
                 "trap;\n"
                 "DONE_%=:\n}"
                 :: "r"(bar), "r"(parity) : "memory");
}
__device__ __forceinline__ void fence_barrier_init() { asm volatile("fence.mbarrier_init.release.cluster;" ::: "memory"); }
__device__ __forceinline__ void fence_proxy_async() { asm volatile("fence.proxy.async.shared::cta;" ::: "memory"); }
__device__ __forceinline__ void tma2d(uint32_t dst, const CUtensorMap* map, uint32_t bar, int c0, int c1) {
    asm volatile("cp.async.bulk.tensor.2d.shared::cluster.global.mbarrier::complete_tx::bytes [%0], [%1, {%3, %4}], [%2];"
                 :: "r"(dst), "l"((uint64_t)map), "r"(bar), "r"(c0), "r"(c1) : "memory");
}
__device__ __forceinline__ void bulk_g2s(uint32_t dst, const void* src, uint32_t bytes, uint32_t bar) {
    asm volatile("cp.async.bulk.shared::cluster.global.mbarrier::complete_tx::bytes [%0], [%1], %2, [%3];"
                 :: "r"(dst), "l"((uint64_t)src), "r"(bytes), "r"(bar) : "memory");
}
__device__ __forceinline__ void l2_prefetch(const void* src, uint32_t bytes) {
    asm volatile("cp.async.bulk.prefetch.L2.global [%0], %1;" :: "l"((uint64_t)src), "r"(bytes) : "memory");
}
__device__ __forceinline__ void map_prefetch(const CUtensorMap* m) {
    asm volatile("prefetch.tensormap [%0];" :: "l"((uint64_t)m) : "memory");
}
__device__ __forceinline__ uint64_t mkdesc(uint32_t addr, uint32_t lbo, uint32_t sbo, uint32_t swz) {
    return (uint64_t)((addr & 0x3FFFF) >> 4) | ((uint64_t)(lbo >> 4) << 16) | ((uint64_t)(sbo >> 4) << 32) | ((uint64_t)swz << 62);
}
#define WG_FENCE() asm volatile("wgmma.fence.sync.aligned;" ::: "memory")
#define WG_COMMIT() asm volatile("wgmma.commit_group.sync.aligned;" ::: "memory")
#define WG_WAIT(n) asm volatile("wgmma.wait_group.sync.aligned %0;" :: "n"(n) : "memory")

__device__ __forceinline__ float ex2(float x) { float y; asm("ex2.approx.ftz.f32 %0, %1;" : "=f"(y) : "f"(x)); return y; }
__device__ __forceinline__ uint32_t packbf(float lo, float hi) {
    uint32_t r; asm("cvt.rn.bf16x2.f32 %0, %1, %2;" : "=r"(r) : "f"(hi), "f"(lo)); return r;
}
__device__ __forceinline__ float bf_lo(uint32_t v) { return __uint_as_float(v << 16); }
__device__ __forceinline__ float bf_hi(uint32_t v) { return __uint_as_float(v & 0xffff0000u); }
__device__ __forceinline__ float bfr(float x) { return __bfloat162float(__float2bfloat16_rn(x)); }

__global__ void __launch_bounds__(256) ln_kernel(const __nv_bfloat16* __restrict__ x, const __nv_bfloat16* __restrict__ wr) {
    TL(0, 0);
    pdl_launch();
    const int warp = threadIdx.x >> 5, lane = threadIdx.x & 31;
    const int row = blockIdx.x * 8 + warp;
    const uint4* xr = reinterpret_cast<const uint4*>(x + (size_t)row * DM);
    uint4 a = xr[lane], b = xr[32 + lane];
    const uint4* wp = reinterpret_cast<const uint4*>(wr);
    uint4 wa = wp[lane], wb = wp[32 + lane];
    uint32_t u[8] = {a.x, a.y, a.z, a.w, b.x, b.y, b.z, b.w};
    uint32_t w[8] = {wa.x, wa.y, wa.z, wa.w, wb.x, wb.y, wb.z, wb.w};
    float f[16];
    float sum = 0.f;
#pragma unroll
    for (int i = 0; i < 8; i++) { f[2 * i] = bf_lo(u[i]); f[2 * i + 1] = bf_hi(u[i]); sum += f[2 * i] + f[2 * i + 1]; }
#pragma unroll
    for (int o = 16; o > 0; o >>= 1) sum += __shfl_xor_sync(~0u, sum, o);
    const float mean = sum * (1.f / DM);
    float sq = 0.f;
#pragma unroll
    for (int i = 0; i < 16; i++) { float d = f[i] - mean; sq = fmaf(d, d, sq); }
#pragma unroll
    for (int o = 16; o > 0; o >>= 1) sq += __shfl_xor_sync(~0u, sq, o);
    const float mb = bfr(mean);
    const float vb = bfr(sq * (1.f / DM));
    const float den = bfr(sqrtf(bfr(vb + 1e-5f)));
    const float rinv = 1.f / den;
    uint32_t o[8];
    float r = 0.f;
#pragma unroll
    for (int i = 0; i < 8; i++) {
        float d0 = bfr(f[2 * i] - mb), d1 = bfr(f[2 * i + 1] - mb);
        o[i] = packbf(d0 * rinv, d1 * rinv);
        r = fmaf(bf_lo(o[i]), bf_lo(w[i]), r);
        r = fmaf(bf_hi(o[i]), bf_hi(w[i]), r);
    }
#pragma unroll
    for (int of = 16; of > 0; of >>= 1) r += __shfl_xor_sync(~0u, r, of);
    uint4* xo = reinterpret_cast<uint4*>(g_xn + (size_t)row * DM);
    xo[lane] = make_uint4(o[0], o[1], o[2], o[3]);
    xo[32 + lane] = make_uint4(o[4], o[5], o[6], o[7]);
    if (lane == 0) g_r[row] = r;
    TL(0, 3);
}

constexpr int K1_ST = 5;
constexpr int K1_STAGE = 16384 + 24576;
constexpr int K1_SMEM = K1_ST * K1_STAGE + 1024 + 128;

__device__ __forceinline__ void wgmma_n192(float (&d)[96], uint64_t da, uint64_t db, int scale_d) {
    asm volatile("{\n.reg .pred p;\nsetp.ne.b32 p, %98, 0;\n"
        "wgmma.mma_async.sync.aligned.m64n192k16.f32.bf16.bf16 "
        "{%0,%1,%2,%3,%4,%5,%6,%7,%8,%9,%10,%11,%12,%13,%14,%15,%16,%17,%18,%19,%20,%21,%22,%23,"
        "%24,%25,%26,%27,%28,%29,%30,%31,%32,%33,%34,%35,%36,%37,%38,%39,%40,%41,%42,%43,%44,%45,%46,%47,"
        "%48,%49,%50,%51,%52,%53,%54,%55,%56,%57,%58,%59,%60,%61,%62,%63,%64,%65,%66,%67,%68,%69,%70,%71,"
        "%72,%73,%74,%75,%76,%77,%78,%79,%80,%81,%82,%83,%84,%85,%86,%87,%88,%89,%90,%91,%92,%93,%94,%95}, "
        "%96, %97, p, 1, 1, 0, 1;\n}"
        : "+f"(d[0]), "+f"(d[1]), "+f"(d[2]), "+f"(d[3]), "+f"(d[4]), "+f"(d[5]), "+f"(d[6]), "+f"(d[7]),
          "+f"(d[8]), "+f"(d[9]), "+f"(d[10]), "+f"(d[11]), "+f"(d[12]), "+f"(d[13]), "+f"(d[14]), "+f"(d[15]),
          "+f"(d[16]), "+f"(d[17]), "+f"(d[18]), "+f"(d[19]), "+f"(d[20]), "+f"(d[21]), "+f"(d[22]), "+f"(d[23]),
          "+f"(d[24]), "+f"(d[25]), "+f"(d[26]), "+f"(d[27]), "+f"(d[28]), "+f"(d[29]), "+f"(d[30]), "+f"(d[31]),
          "+f"(d[32]), "+f"(d[33]), "+f"(d[34]), "+f"(d[35]), "+f"(d[36]), "+f"(d[37]), "+f"(d[38]), "+f"(d[39]),
          "+f"(d[40]), "+f"(d[41]), "+f"(d[42]), "+f"(d[43]), "+f"(d[44]), "+f"(d[45]), "+f"(d[46]), "+f"(d[47]),
          "+f"(d[48]), "+f"(d[49]), "+f"(d[50]), "+f"(d[51]), "+f"(d[52]), "+f"(d[53]), "+f"(d[54]), "+f"(d[55]),
          "+f"(d[56]), "+f"(d[57]), "+f"(d[58]), "+f"(d[59]), "+f"(d[60]), "+f"(d[61]), "+f"(d[62]), "+f"(d[63]),
          "+f"(d[64]), "+f"(d[65]), "+f"(d[66]), "+f"(d[67]), "+f"(d[68]), "+f"(d[69]), "+f"(d[70]), "+f"(d[71]),
          "+f"(d[72]), "+f"(d[73]), "+f"(d[74]), "+f"(d[75]), "+f"(d[76]), "+f"(d[77]), "+f"(d[78]), "+f"(d[79]),
          "+f"(d[80]), "+f"(d[81]), "+f"(d[82]), "+f"(d[83]), "+f"(d[84]), "+f"(d[85]), "+f"(d[86]), "+f"(d[87]),
          "+f"(d[88]), "+f"(d[89]), "+f"(d[90]), "+f"(d[91]), "+f"(d[92]), "+f"(d[93]), "+f"(d[94]), "+f"(d[95])
        : "l"(da), "l"(db), "r"(scale_d));
}

__global__ void __launch_bounds__(288, 1) qkv_kernel(const __grid_constant__ CUtensorMap mapA, const __grid_constant__ CUtensorMap mapB,
                                                     const uint8_t* __restrict__ pwg, const uint8_t* __restrict__ pwu, const uint8_t* __restrict__ pwd,
                                                     const uint8_t* __restrict__ pwo) {
    extern __shared__ uint8_t smem_raw[];
    const uint32_t sbase = (smem_u32(smem_raw) + 1023u) & ~1023u;
    const uint32_t bars = sbase + K1_ST * K1_STAGE;
    const int warp = threadIdx.x >> 5, lane = threadIdx.x & 31;
    const int nb = blockIdx.x & 7, mb = blockIdx.x >> 3;
    TL(1, 0);
    if (threadIdx.x == 0) {
        for (int s = 0; s < K1_ST; s++) { mbar_init(bars + 8 * s, 1); mbar_init(bars + 8 * (K1_ST + s), 2); }
        fence_barrier_init();
    }
    __syncthreads();
    if (warp == 8) {
        if (lane == 0) {
            for (int c = 0; c < K1_ST; c++) {
                const uint32_t st = sbase + c * K1_STAGE;
                mbar_expect_tx(bars + 8 * c, K1_STAGE);
                for (int j = 0; j < 3; j++) tma2d(st + 16384 + j * 8192, &mapB, bars + 8 * c, nb * 192 + j * 64, c * 64);
            }
            map_prefetch(&mapA);
            pdl_wait();
            pdl_launch();
            for (int c = 0; c < K1_ST; c++) tma2d(sbase + c * K1_STAGE, &mapA, bars + 8 * c, c * 64, mb * 128);
            l2_prefetch(pwg + blockIdx.x * 14336, 14336);
            l2_prefetch(pwu + blockIdx.x * 14336, 14336);
            l2_prefetch(pwd + blockIdx.x * 14336, 14336);
            l2_prefetch(pwo + blockIdx.x * 4096, 4096);
            for (int c = K1_ST; c < 8; c++) {
                const int s = c - K1_ST;
                const uint32_t st = sbase + s * K1_STAGE;
                mbar_wait(bars + 8 * (K1_ST + s), 0);
                mbar_expect_tx(bars + 8 * s, K1_STAGE);
                tma2d(st, &mapA, bars + 8 * s, c * 64, mb * 128);
                for (int j = 0; j < 3; j++) tma2d(st + 16384 + j * 8192, &mapB, bars + 8 * s, nb * 192 + j * 64, c * 64);
            }
        }
        return;
    }
    const int wg = warp >> 2;
    float acc[96];
#pragma unroll
    for (int i = 0; i < 96; i++) acc[i] = 0.f;
#pragma unroll 1
    for (int c = 0; c < 8; c++) {
        const int s = c < K1_ST ? c : c - K1_ST;
        const uint32_t st = sbase + s * K1_STAGE;
        mbar_wait(bars + 8 * s, c < K1_ST ? 0 : 1);
        if (c == 0) TL(1, 1);
        const uint64_t da = mkdesc(st + wg * 8192, 16, 1024, 1);
        const uint64_t db = mkdesc(st + 16384, 8192, 1024, 1);
        WG_FENCE();
#pragma unroll
        for (int k = 0; k < 4; k++) wgmma_n192(acc, da + k * 2, db + k * 128, (c | k) != 0);
        WG_COMMIT();
        if (c + K1_ST < 8 + 1) {
            WG_WAIT(1);
            if (c >= 1 && (threadIdx.x & 127) == 0) mbar_arrive(bars + 8 * (K1_ST + c - 1));
        }
    }
    WG_WAIT(0);
    TL(1, 2);
    const int g = lane >> 2, t = lane & 3;
    const int mt = mb * 8 + warp;
#pragma unroll
    for (int hh = 0; hh < 12; hh++) {
        const int gh = nb * 12 + hh;
        const float* a = &acc[hh * 8];
        if (gh < 32) {
            uint4 v;
            v.x = packbf(a[0], a[1]); v.y = packbf(a[2], a[3]);
            v.z = packbf(a[4], a[5]); v.w = packbf(a[6], a[7]);
            g_q[(gh * 128 + mt) * 32 + lane] = v;
        } else {
            uint32_t* dst = reinterpret_cast<uint32_t*>(gh < 64 ? g_k + (gh - 32) * 4096 : g_v + (gh - 64) * 4096);
            const float ks = gh < 64 ? 5.421010862427522e-20f : 1.0f;
            const int off = (mt * 16 + g) * 4 + t;
            dst[off] = packbf(a[0] * ks, a[1] * ks);
            dst[off + 32] = packbf(a[2] * ks, a[3] * ks);
            dst[8192 + off] = packbf(a[4] * ks, a[5] * ks);
            dst[8192 + off + 32] = packbf(a[6] * ks, a[7] * ks);
        }
    }
    TL(1, 3);
}

constexpr float SHIFT = 90.0f;
constexpr float QS = 0.25f * 1.4426950408889634f * 18446744073709551616.0f;
constexpr float scq = 0.25f * 1.4426950408889634f * 3.3087224502121107e-24f;
constexpr int K2_SMEM = 163840 + 1024 + 128;

__device__ __forceinline__ uint32_t polyexp(float lo, float hi) {
    uint32_t w, g, q, h;
    asm("cvt.pack.sat.s16.s32 %0, %1, %2;" : "=r"(w) : "r"(__float_as_uint(hi)), "r"(__float_as_uint(lo)));
    g = w & 0x007F007Fu;
    asm("fma.rn.f16x2 %0, %1, %2, %3;" : "=r"(q) : "r"(g), "r"(0xf940f940u), "r"(0x35513551u));
    asm("mul.rn.f16x2 %0, %1, %2;" : "=r"(h) : "r"(q), "r"(g));
    return w - h;
}
__device__ __forceinline__ void qk64(float (&s)[32], const uint32_t (&q)[4], uint64_t db) {
    asm volatile("wgmma.mma_async.sync.aligned.m64n64k16.f32.bf16.bf16 "
        "{%0,%1,%2,%3,%4,%5,%6,%7,%8,%9,%10,%11,%12,%13,%14,%15,%16,%17,%18,%19,%20,%21,%22,%23,%24,%25,%26,%27,%28,%29,%30,%31}, "
        "{%32,%33,%34,%35}, %36, 0, 1, 1, 0;"
        : "=f"(s[0]), "=f"(s[1]), "=f"(s[2]), "=f"(s[3]), "=f"(s[4]), "=f"(s[5]), "=f"(s[6]), "=f"(s[7]),
          "=f"(s[8]), "=f"(s[9]), "=f"(s[10]), "=f"(s[11]), "=f"(s[12]), "=f"(s[13]), "=f"(s[14]), "=f"(s[15]),
          "=f"(s[16]), "=f"(s[17]), "=f"(s[18]), "=f"(s[19]), "=f"(s[20]), "=f"(s[21]), "=f"(s[22]), "=f"(s[23]),
          "=f"(s[24]), "=f"(s[25]), "=f"(s[26]), "=f"(s[27]), "=f"(s[28]), "=f"(s[29]), "=f"(s[30]), "=f"(s[31])
        : "r"(q[0]), "r"(q[1]), "r"(q[2]), "r"(q[3]), "l"(db));
}
__device__ __forceinline__ void pv24(float (&o)[12], uint32_t a0, uint32_t a1, uint32_t a2, uint32_t a3, uint64_t db) {
    asm volatile("wgmma.mma_async.sync.aligned.m64n24k16.f32.bf16.bf16 "
        "{%0,%1,%2,%3,%4,%5,%6,%7,%8,%9,%10,%11}, {%12,%13,%14,%15}, %16, 1, 1, 1, 1;"
        : "+f"(o[0]), "+f"(o[1]), "+f"(o[2]), "+f"(o[3]), "+f"(o[4]), "+f"(o[5]), "+f"(o[6]), "+f"(o[7]),
          "+f"(o[8]), "+f"(o[9]), "+f"(o[10]), "+f"(o[11])
        : "r"(a0), "r"(a1), "r"(a2), "r"(a3), "l"(db));
}

__device__ __forceinline__ void attn_safe(float (&o)[12], const uint32_t (&q)[4], uint64_t kdesc0, uint64_t vdesc0) {
    float s[32];
    float m0 = -INFINITY, m1 = -INFINITY;
#pragma unroll
    for (int i = 0; i < 12; i++) o[i] = 0.f;
#pragma unroll 1
    for (int j = 0; j < 32; j++) {
        WG_FENCE();
        qk64(s, q, kdesc0 + (uint64_t)(j * 64));
        WG_COMMIT(); WG_WAIT(0);
        float n0 = m0, n1 = m1;
#pragma unroll
        for (int i = 0; i < 8; i++) { n0 = fmaxf(n0, fmaxf(s[4 * i], s[4 * i + 1])); n1 = fmaxf(n1, fmaxf(s[4 * i + 2], s[4 * i + 3])); }
        n0 = fmaxf(n0, __shfl_xor_sync(~0u, n0, 1)); n0 = fmaxf(n0, __shfl_xor_sync(~0u, n0, 2));
        n1 = fmaxf(n1, __shfl_xor_sync(~0u, n1, 1)); n1 = fmaxf(n1, __shfl_xor_sync(~0u, n1, 2));
        const float c0 = ex2((m0 - n0) * QS), c1 = ex2((m1 - n1) * QS);
        m0 = n0; m1 = n1;
#pragma unroll
        for (int i = 0; i < 3; i++) { o[4 * i] *= c0; o[4 * i + 1] *= c0; o[4 * i + 2] *= c1; o[4 * i + 3] *= c1; }
        uint32_t p[16];
#pragma unroll
        for (int i = 0; i < 8; i++) {
            p[2 * i] = packbf(ex2((s[4 * i] - m0) * QS), ex2((s[4 * i + 1] - m0) * QS));
            p[2 * i + 1] = packbf(ex2((s[4 * i + 2] - m1) * QS), ex2((s[4 * i + 3] - m1) * QS));
        }
        WG_FENCE();
#pragma unroll
        for (int kk = 0; kk < 4; kk++) pv24(o, p[4 * kk], p[4 * kk + 1], p[4 * kk + 2], p[4 * kk + 3], vdesc0 + (uint64_t)(j * 64 + kk * 16));
        WG_COMMIT(); WG_WAIT(0);
    }
}

__device__ __forceinline__ void attn_store(const float (&o)[12], int head, int m64, int warp, int lane) {
    const int g = lane >> 2, t = lane & 3;
    const int row = m64 * 64 + warp * 16 + g;
    const float i0 = 1.f / o[8], i1 = 1.f / o[10];
    uint32_t* p0 = reinterpret_cast<uint32_t*>(g_o + (size_t)row * DM + head * 16 + t * 2);
    uint32_t* p1 = reinterpret_cast<uint32_t*>(g_o + (size_t)(row + 8) * DM + head * 16 + t * 2);
    p0[0] = packbf(o[0] * i0, o[1] * i0); p0[4] = packbf(o[4] * i0, o[5] * i0);
    p1[0] = packbf(o[2] * i1, o[3] * i1); p1[4] = packbf(o[6] * i1, o[7] * i1);
}

constexpr int FS_N = 4;
constexpr int FS_BYTES = 32768;
__device__ __forceinline__ void ldsm4t(uint32_t& r0, uint32_t& r1, uint32_t& r2, uint32_t& r3, uint32_t addr) {
    asm volatile("ldmatrix.sync.aligned.m8n8.x4.trans.shared.b16 {%0,%1,%2,%3}, [%4];" : "=r"(r0), "=r"(r1), "=r"(r2), "=r"(r3) : "r"(addr) : "memory");
}
__device__ __forceinline__ void mma16816(float (&d)[4], uint32_t a0, uint32_t a2, uint32_t b0, uint32_t b1) {
    asm volatile("mma.sync.aligned.m16n8k16.row.col.f32.bf16.bf16.f32 {%0,%1,%2,%3}, {%4,%5,%6,%5}, {%7,%8}, {%0,%1,%2,%3};"
                 : "+f"(d[0]), "+f"(d[1]), "+f"(d[2]), "+f"(d[3]) : "r"(a0), "r"(0u), "r"(a2), "r"(b0), "r"(b1));
}
__device__ void ffn_block(int c, uint8_t* smem, uint32_t sbase, const CUtensorMap* mapG, const CUtensorMap* mapU, const CUtensorMap* mapD) {
    const int tid = threadIdx.x, warp = tid >> 5, lane = tid & 31;
    uint32_t* sx = reinterpret_cast<uint32_t*>(smem + FS_N * FS_BYTES);
    __nv_bfloat16* sh = reinterpret_cast<__nv_bfloat16*>(sx + 512);
    const uint32_t bars = sbase + FS_N * FS_BYTES + 8192;
    __shared__ float tv[32]; __shared__ int ti[32];
    __shared__ int ssel[2];
    auto issue = [&](int item) {
        const int slot = item % FS_N;
        const uint32_t dst = sbase + slot * FS_BYTES, bar = bars + 8 * slot;
        if (item < 32) {
            mbar_expect_tx(bar, 28672);
            for (int j = 0; j < 7; j++) {
                tma2d(dst + j * 2048, mapG, bar, c * 448 + j * 64, item * 16);
                tma2d(dst + 14336 + j * 2048, mapU, bar, c * 448 + j * 64, item * 16);
            }
        } else {
            mbar_expect_tx(bar, 32768);
            for (int j = 0; j < 8; j++) tma2d(dst + j * 4096, mapD, bar, j * 64, c * 448 + (item - 32) * 32);
        }
    };
    if (tid == 0) {
        for (int i = 0; i < FS_N; i++) mbar_init(bars + 8 * i, 1);
        fence_barrier_init();
        for (int i = 0; i < FS_N; i++) issue(i);
    }
    float b1 = -INFINITY, b2 = -INFINITY; int i1 = 0x7fffffff, i2 = 0x7fffffff;
    auto push = [&](float v, int i) {
        if (v > b1 || (v == b1 && i < i1)) { b2 = b1; i2 = i1; b1 = v; i1 = i; }
        else if (v > b2 || (v == b2 && i < i2)) { b2 = v; i2 = i; }
    };
    {
        const float4 rv = reinterpret_cast<const float4*>(g_r)[tid];
        push(rv.x, 4 * tid); push(rv.y, 4 * tid + 1); push(rv.z, 4 * tid + 2); push(rv.w, 4 * tid + 3);
    }
#pragma unroll
    for (int o = 16; o > 0; o >>= 1) {
        float v1 = __shfl_xor_sync(~0u, b1, o), v2 = __shfl_xor_sync(~0u, b2, o);
        int j1 = __shfl_xor_sync(~0u, i1, o), j2 = __shfl_xor_sync(~0u, i2, o);
        push(v1, j1); push(v2, j2);
    }
    if (lane == 0) { tv[2 * warp] = b1; ti[2 * warp] = i1; tv[2 * warp + 1] = b2; ti[2 * warp + 1] = i2; }
    __syncthreads();
    if (warp == 1) {
        b1 = tv[lane]; i1 = ti[lane]; b2 = -INFINITY; i2 = 0x7fffffff;
#pragma unroll
        for (int o = 16; o > 0; o >>= 1) {
            float v1 = __shfl_xor_sync(~0u, b1, o), v2 = __shfl_xor_sync(~0u, b2, o);
            int j1 = __shfl_xor_sync(~0u, i1, o), j2 = __shfl_xor_sync(~0u, i2, o);
            push(v1, j1); push(v2, j2);
        }
        if (lane == 0) {
            i1 = min(max(i1, 0), S_LEN - 1); i2 = min(max(i2, 0), S_LEN - 1);
            ssel[0] = i1; ssel[1] = i2;
            if (c == 0) {
                g_sel[0] = i1; g_sel[1] = i2;
                g_gate[0] = bfr(1.f / (1.f + __expf(-bfr(b1))));
                g_gate[1] = bfr(1.f / (1.f + __expf(-bfr(b2))));
            }
        }
    }
    __syncthreads();
    sx[tid] = *reinterpret_cast<const uint32_t*>(g_xn + (size_t)ssel[tid >> 8] * DM + (tid & 255) * 2);
    __syncthreads();
    TL(2, 1);
    const int g = lane >> 2, t = lane & 3;
    const int lrow = lane & 15, lsel = lane >> 4;
    {
        float ag[4][4], au[4][4];
#pragma unroll
        for (int j = 0; j < 4; j++) { ag[j][0] = ag[j][1] = ag[j][2] = ag[j][3] = 0.f; au[j][0] = au[j][1] = au[j][2] = au[j][3] = 0.f; }
#pragma unroll 1
        for (int it = 0; it < 32; it++) {
            const int slot = it % FS_N;
            const uint32_t a0 = g < 2 ? sx[g * 256 + it * 8 + t] : 0u, a2 = g < 2 ? sx[g * 256 + it * 8 + 4 + t] : 0u;
            mbar_wait(bars + 8 * slot, (it / FS_N) & 1);
            const uint32_t base = sbase + slot * FS_BYTES + lsel * 14336 + lrow * 128;
#pragma unroll
            for (int j = 0; j < 4; j++) {
                const int nt = warp + j * 16;
                if (nt < 56) {
                    uint32_t b0, b1, b2, b3;
                    ldsm4t(b0, b1, b2, b3, base + (nt >> 3) * 2048 + (((nt & 7) ^ (lrow & 7)) << 4));
                    mma16816(ag[j], a0, a2, b0, b1);
                    mma16816(au[j], a0, a2, b2, b3);
                }
            }
            __syncthreads();
            if (tid == 0) issue(it + FS_N);
        }
        if (g < 2) {
#pragma unroll
            for (int j = 0; j < 4; j++) {
                const int nt = warp + j * 16;
                if (nt < 56) {
#pragma unroll
                    for (int e = 0; e < 2; e++) {
                        const float gs = bfr(ag[j][e]), us = bfr(au[j][e]);
                        const float sg = bfr(gs / (1.f + __expf(-gs)));
                        sh[g * 448 + nt * 8 + t * 2 + e] = __float2bfloat16_rn(sg * us);
                    }
                }
            }
        }
        __syncthreads();
    }
    TL(2, 2);
    {
        const uint32_t* shw = reinterpret_cast<const uint32_t*>(sh);
        float a[4][4];
#pragma unroll
        for (int j = 0; j < 4; j++) a[j][0] = a[j][1] = a[j][2] = a[j][3] = 0.f;
#pragma unroll 1
        for (int it = 32; it < 46; it++) {
            const int slot = it % FS_N;
            uint32_t af[4];
#pragma unroll
            for (int q = 0; q < 4; q++) af[q] = g < 2 ? shw[g * 224 + (it - 32) * 16 + q * 4 + t] : 0u;
            mbar_wait(bars + 8 * slot, (it / FS_N) & 1);
            const uint32_t base = sbase + slot * FS_BYTES + (warp >> 1) * 4096 + lane * 128;
#pragma unroll
            for (int j = 0; j < 4; j++) {
                const int u = (warp & 1) * 4 + j;
                uint32_t b0, b1, b2, b3;
                ldsm4t(b0, b1, b2, b3, base + ((u ^ (lane & 7)) << 4));
                mma16816(a[j], af[0], af[1], b0, b1);
                mma16816(a[j], af[2], af[3], b2, b3);
            }
            __syncthreads();
            if (tid == 0 && it + FS_N < 46) issue(it + FS_N);
        }
        if (g < 2) {
#pragma unroll
            for (int j = 0; j < 4; j++)
                *reinterpret_cast<float2*>(&g_ypart[c * 1024 + g * 512 + (warp * 4 + j) * 8 + t * 2]) = make_float2(a[j][0], a[j][1]);
        }
    }
}

__global__ void __launch_bounds__(512, 1) attn_kernel(const __grid_constant__ CUtensorMap mapG, const __grid_constant__ CUtensorMap mapU,
                                                      const __grid_constant__ CUtensorMap mapD, float sc) {
    extern __shared__ uint8_t smem_raw[];
    const uint32_t sraw = smem_u32(smem_raw);
    const uint32_t sbase = (sraw + 1023u) & ~1023u;
    uint8_t* sptr = smem_raw + (sbase - sraw);
    TL(2, 0);
    if (blockIdx.x < 4) {
        pdl_launch();
        ffn_block(blockIdx.x, sptr, sbase, &mapG, &mapU, &mapD);
        TL(2, 3);
        return;
    }
    const uint32_t bars = sbase + 163840;
    const int head = (blockIdx.x - 4) >> 2, quarter = blockIdx.x & 3;
    const int wg = threadIdx.x >> 7, warp = (threadIdx.x >> 5) & 3, lane = threadIdx.x & 31;
    if (threadIdx.x == 0) {
        for (int c = 0; c < 8; c++) mbar_init(bars + 8 * c, 1);
        fence_barrier_init();
    }
    {
        uint4* ones = reinterpret_cast<uint4*>(sptr + 131072);
        for (int i = threadIdx.x; i < 2048; i += 512) ones[i] = make_uint4(0x3f803f80u, 0x3f803f80u, 0x3f803f80u, 0x3f803f80u);
        fence_proxy_async();
    }
    __syncthreads();
    pdl_wait();
    pdl_launch();
    TL(2, 1);
    if (threadIdx.x == 0) {
        const uint8_t* kp = reinterpret_cast<const uint8_t*>(g_k + head * 4096);
        const uint8_t* vp = reinterpret_cast<const uint8_t*>(g_v + head * 4096);
        for (int c = 0; c < 8; c++) {
            mbar_expect_tx(bars + 8 * c, 16384);
            bulk_g2s(sbase + c * 4096, kp + c * 4096, 4096, bars + 8 * c);
            bulk_g2s(sbase + 32768 + c * 4096, kp + 32768 + c * 4096, 4096, bars + 8 * c);
            bulk_g2s(sbase + 65536 + c * 4096, vp + c * 4096, 4096, bars + 8 * c);
            bulk_g2s(sbase + 98304 + c * 4096, vp + 32768 + c * 4096, 4096, bars + 8 * c);
        }
    }
    const uint64_t kdesc0 = mkdesc(sbase, 32768, 128, 0);
    const uint64_t vdesc0 = mkdesc(sbase + 65536, 128, 32768, 0);
    uint32_t badmask = 0;
#pragma unroll 1
    for (int mt = 0; mt < 2; mt++) {
        const int m64 = quarter * 8 + mt * 4 + wg;
        uint32_t q[4];
        { const uint4 qq = g_q[(head * 128 + m64 * 4 + warp) * 32 + lane]; q[0] = qq.x; q[1] = qq.y; q[2] = qq.z; q[3] = qq.w; }
        float s[32], s2[32], o[12];
#pragma unroll
        for (int i = 0; i < 12; i++) o[i] = 0.f;
        mbar_wait(bars, 0);
        if (mt == 0) TL(2, 2);
        WG_FENCE();
        qk64(s, q, kdesc0);
        WG_COMMIT(); WG_WAIT(0);
        float mx0 = -INFINITY, mx1 = -INFINITY;
#pragma unroll
        for (int i = 0; i < 8; i++) { mx0 = fmaxf(mx0, fmaxf(s[4 * i], s[4 * i + 1])); mx1 = fmaxf(mx1, fmaxf(s[4 * i + 2], s[4 * i + 3])); }
        mx0 = fmaxf(mx0, __shfl_xor_sync(~0u, mx0, 1)); mx0 = fmaxf(mx0, __shfl_xor_sync(~0u, mx0, 2));
        mx1 = fmaxf(mx1, __shfl_xor_sync(~0u, mx1, 1)); mx1 = fmaxf(mx1, __shfl_xor_sync(~0u, mx1, 2));
        float cm0 = -(ceilf(mx0 * QS) + SHIFT), cm1 = -(ceilf(mx1 * QS) + SHIFT);
        float cp0 = (cm0 + 127.f) * sc, cp1 = (cm1 + 127.f) * sc;
        asm volatile("" : "+f"(cm0), "+f"(cm1), "+f"(cp0), "+f"(cp1));
        uint64_t kd = kdesc0, vd = vdesc0;
        auto step = [&](float (&sc_)[32], float (&sn)[32]) {
            kd += 64;
            WG_FENCE();
            qk64(sn, q, kd);
            WG_COMMIT();
#pragma unroll
            for (int kk = 0; kk < 4; kk++) {
                const int i0 = kk * 2, i1 = kk * 2 + 1;
                const uint32_t p0 = packbf(ex2(fmaf(sc_[4 * i0], QS, cm0)), ex2(fmaf(sc_[4 * i0 + 1], QS, cm0)));
                const uint32_t p1 = packbf(ex2(fmaf(sc_[4 * i0 + 2], QS, cm1)), ex2(fmaf(sc_[4 * i0 + 3], QS, cm1)));
                const uint32_t p2 = polyexp(fmaf(sc_[4 * i1], scq, cp0), fmaf(sc_[4 * i1 + 1], scq, cp0));
                const uint32_t p3 = polyexp(fmaf(sc_[4 * i1 + 2], scq, cp1), fmaf(sc_[4 * i1 + 3], scq, cp1));
                WG_FENCE();
                pv24(o, p0, p1, p2, p3, vd);
                vd += 16;
            }
            WG_COMMIT();
            WG_WAIT(1);
        };
#pragma unroll 1
        for (int c = 0; c < 16; c++) {
            if (mt == 0 && (c & 1) == 0 && c < 14) mbar_wait(bars + 4 * c + 8, 0);
            step(s, s2); step(s2, s);
        }
        WG_WAIT(0);
        bool bad = !(o[8] > 0.f) || !(o[10] > 0.f);
#pragma unroll
        for (int i = 0; i < 12; i++) bad = bad || !(fabsf(o[i]) <= 3.0e38f);
        uint32_t anybad;
        asm volatile("{\n.reg .pred p, q;\nsetp.ne.u32 p, %1, 0;\nbarrier.cta.red.or.pred q, %2, 128, p;\nselp.u32 %0, 1, 0, q;\n}"
                     : "=r"(anybad) : "r"((uint32_t)bad), "r"(wg + 1) : "memory");
        badmask |= anybad << mt;
        attn_store(o, head, m64, warp, lane);
    }
#pragma unroll 1
    for (int mt = 0; mt < 2; mt++) {
        if (!((badmask >> mt) & 1)) continue;
        const int m64 = quarter * 8 + mt * 4 + wg;
        uint32_t q[4];
        { const uint4 qq = g_q[(head * 128 + m64 * 4 + warp) * 32 + lane]; q[0] = qq.x; q[1] = qq.y; q[2] = qq.z; q[3] = qq.w; }
        float o[12];
        attn_safe(o, q, mkdesc(sbase, 32768, 128, 0), mkdesc(sbase + 65536, 128, 32768, 0));
        attn_store(o, head, m64, warp, lane);
    }
    TL(2, 3);
}

constexpr int K3_SMEM = 8 * 8192 + 8 * 16384 + 1024 + 128;

__device__ __forceinline__ void wgmma_n64(float (&d)[32], uint64_t da, uint64_t db, int scale_d) {
    asm volatile("{\n.reg .pred p;\nsetp.ne.b32 p, %34, 0;\n"
        "wgmma.mma_async.sync.aligned.m64n64k16.f32.bf16.bf16 "
        "{%0,%1,%2,%3,%4,%5,%6,%7,%8,%9,%10,%11,%12,%13,%14,%15,%16,%17,%18,%19,%20,%21,%22,%23,%24,%25,%26,%27,%28,%29,%30,%31}, "
        "%32, %33, p, 1, 1, 0, 1;\n}"
        : "+f"(d[0]), "+f"(d[1]), "+f"(d[2]), "+f"(d[3]), "+f"(d[4]), "+f"(d[5]), "+f"(d[6]), "+f"(d[7]),
          "+f"(d[8]), "+f"(d[9]), "+f"(d[10]), "+f"(d[11]), "+f"(d[12]), "+f"(d[13]), "+f"(d[14]), "+f"(d[15]),
          "+f"(d[16]), "+f"(d[17]), "+f"(d[18]), "+f"(d[19]), "+f"(d[20]), "+f"(d[21]), "+f"(d[22]), "+f"(d[23]),
          "+f"(d[24]), "+f"(d[25]), "+f"(d[26]), "+f"(d[27]), "+f"(d[28]), "+f"(d[29]), "+f"(d[30]), "+f"(d[31])
        : "l"(da), "l"(db), "r"(scale_d));
}

__global__ void __launch_bounds__(256, 1) oproj_kernel(const __grid_constant__ CUtensorMap mapA, const __grid_constant__ CUtensorMap mapB,
                                                       const __nv_bfloat16* __restrict__ x, __nv_bfloat16* __restrict__ out) {
    extern __shared__ uint8_t smem_raw[];
    const uint32_t sbase = (smem_u32(smem_raw) + 1023u) & ~1023u;
    const uint32_t sA = sbase, sB = sbase + 8 * 8192, bars = sbase + 8 * 8192 + 8 * 16384;
    const int warp = threadIdx.x >> 5, lane = threadIdx.x & 31, wg = warp >> 2;
    const int nb = blockIdx.x & 3, mb = blockIdx.x >> 2;
    TL(3, 0);
    if (threadIdx.x == 0) {
        for (int c = 0; c < 8; c++) mbar_init(bars + 8 * c, 1);
        fence_barrier_init();
        map_prefetch(&mapA);
        for (int c = 0; c < 8; c++) {
            mbar_expect_tx(bars + 8 * c, 8192 + 16384);
            tma2d(sB + c * 16384, &mapB, bars + 8 * c, nb * 128, c * 64);
            tma2d(sB + c * 16384 + 8192, &mapB, bars + 8 * c, nb * 128 + 64, c * 64);
        }
    }
    const int g = lane >> 2, t = lane & 3;
    const int row0 = mb * 64 + (warp & 3) * 16 + g;
    const int col0 = nb * 128 + wg * 64 + t * 2;
    uint32_t xv[16], nv[16];
#pragma unroll
    for (int i = 0; i < 8; i++) {
        xv[2 * i] = *reinterpret_cast<const uint32_t*>(x + (size_t)row0 * DM + col0 + i * 8);
        xv[2 * i + 1] = *reinterpret_cast<const uint32_t*>(x + (size_t)(row0 + 8) * DM + col0 + i * 8);
        nv[2 * i] = *reinterpret_cast<const uint32_t*>(g_xn + (size_t)row0 * DM + col0 + i * 8);
        nv[2 * i + 1] = *reinterpret_cast<const uint32_t*>(g_xn + (size_t)(row0 + 8) * DM + col0 + i * 8);
    }
    __syncthreads();
    pdl_wait();
    TL(3, 1);
    if (threadIdx.x == 0) {
        for (int c = 0; c < 8; c++) tma2d(sA + c * 8192, &mapA, bars + 8 * c, c * 64, mb * 64);
    }
    __shared__ float supd[2][128];
    const int sel0 = g_sel[0], sel1 = g_sel[1];
    {
        const int which = threadIdx.x >> 7, col = nb * 128 + (threadIdx.x & 127);
        const float y = g_ypart[which * 512 + col] + g_ypart[1024 + which * 512 + col] + g_ypart[2048 + which * 512 + col] + g_ypart[3072 + which * 512 + col];
        supd[which][threadIdx.x & 127] = bfr(bfr(y) * g_gate[which]);
    }
    __syncthreads();
    float acc[32];
#pragma unroll
    for (int i = 0; i < 32; i++) acc[i] = 0.f;
#pragma unroll 1
    for (int c = 0; c < 8; c++) {
        mbar_wait(bars + 8 * c, 0);
        const uint64_t da = mkdesc(sA + c * 8192, 16, 1024, 1);
        const uint64_t db = mkdesc(sB + c * 16384 + wg * 8192, 8192, 1024, 1);
        WG_FENCE();
#pragma unroll
        for (int k = 0; k < 4; k++) wgmma_n64(acc, da + k * 2, db + k * 128, (c | k) != 0);
        WG_COMMIT();
    }
    WG_WAIT(0);
    TL(3, 2);
#pragma unroll
    for (int h = 0; h < 2; h++) {
        const int row = row0 + h * 8;
        const int which = row == sel0 ? 0 : (row == sel1 ? 1 : -1);
#pragma unroll
        for (int i = 0; i < 8; i++) {
            const int col = col0 + i * 8;
            float b0 = bf_lo(nv[2 * i + h]), b1 = bf_hi(nv[2 * i + h]);
            if (which >= 0) {
                b0 = bfr(b0 + supd[which][col - nb * 128]); b1 = bfr(b1 + supd[which][col + 1 - nb * 128]);
            }
            const float t0 = bfr(bf_lo(xv[2 * i + h]) + bfr(acc[4 * i + 2 * h]));
            const float t1 = bfr(bf_hi(xv[2 * i + h]) + bfr(acc[4 * i + 2 * h + 1]));
            *reinterpret_cast<uint32_t*>(out + (size_t)row * DM + col) = packbf(t0 + b0, t1 + b1);
        }
    }
    TL(3, 3);
}

typedef CUresult (*EncodeFn)(CUtensorMap*, CUtensorMapDataType, cuuint32_t, void*, const cuuint64_t*, const cuuint64_t*,
                             const cuuint32_t*, const cuuint32_t*, CUtensorMapInterleave, CUtensorMapSwizzle,
                             CUtensorMapL2promotion, CUtensorMapFloatOOBfill);

void make_map(EncodeFn fn, CUtensorMap* m, const void* ptr, uint64_t inner, uint64_t outer, uint32_t box_inner, uint32_t box_outer,
              CUtensorMapSwizzle swz = CU_TENSOR_MAP_SWIZZLE_128B) {
    cuuint64_t dims[2] = {inner, outer};
    cuuint64_t strides[1] = {inner * 2};
    cuuint32_t box[2] = {box_inner, box_outer};
    cuuint32_t es[2] = {1, 1};
    fn(m, CU_TENSOR_MAP_DATA_TYPE_BFLOAT16, 2, const_cast<void*>(ptr), dims, strides, box, es, CU_TENSOR_MAP_INTERLEAVE_NONE,
       swz, CU_TENSOR_MAP_L2_PROMOTION_L2_256B, CU_TENSOR_MAP_FLOAT_OOB_FILL_NONE);
}

template <typename... KArgs, typename... Args>
void launch(void (*kern)(KArgs...), int grid, int block, int smem, bool pdl, Args... args) {
    cudaLaunchConfig_t cfg = {};
    cfg.gridDim = dim3(grid); cfg.blockDim = dim3(block); cfg.dynamicSmemBytes = smem; cfg.stream = cudaStreamPerThread;
    cudaLaunchAttribute at[1];
    at[0].id = cudaLaunchAttributeProgrammaticStreamSerialization;
    at[0].val.programmaticStreamSerializationAllowed = 1;
    cfg.attrs = at; cfg.numAttrs = pdl ? 1 : 0;
    cudaLaunchKernelEx(&cfg, kern, KArgs(args)...);
}

}

extern "C" void kernel_launch(void* const* d_in, const int* in_sizes, int n_in, void* d_out, int out_size) {
    const __nv_bfloat16* x = (const __nv_bfloat16*)d_in[0];
    const __nv_bfloat16* wqkv = (const __nv_bfloat16*)d_in[1];
    const __nv_bfloat16* wo = (const __nv_bfloat16*)d_in[2];
    const __nv_bfloat16* wr = (const __nv_bfloat16*)d_in[4];
    const __nv_bfloat16* wgate = (const __nv_bfloat16*)d_in[5];
    const __nv_bfloat16* wup = (const __nv_bfloat16*)d_in[6];
    const __nv_bfloat16* wdown = (const __nv_bfloat16*)d_in[7];
    __nv_bfloat16* out = (__nv_bfloat16*)d_out;

    static EncodeFn enc = nullptr;
    static void* p_xn = nullptr; static void* p_o = nullptr;
    if (!enc) {
        void* fn = nullptr; cudaDriverEntryPointQueryResult qr;
        cudaGetDriverEntryPoint("cuTensorMapEncodeTiled", &fn, cudaEnableDefault, &qr);
        enc = (EncodeFn)fn;
        cudaGetSymbolAddress(&p_xn, g_xn);
        cudaGetSymbolAddress(&p_o, g_o);
        cudaFuncSetAttribute(qkv_kernel, cudaFuncAttributeMaxDynamicSharedMemorySize, K1_SMEM);
        cudaFuncSetAttribute(attn_kernel, cudaFuncAttributeMaxDynamicSharedMemorySize, K2_SMEM);
        cudaFuncSetAttribute(oproj_kernel, cudaFuncAttributeMaxDynamicSharedMemorySize, K3_SMEM);
    }
    CUtensorMap mXn, mWqkv, mO, mWo, mG, mU, mD;
    make_map(enc, &mG, wgate, FF, DM, 64, 16);
    make_map(enc, &mU, wup, FF, DM, 64, 16);
    make_map(enc, &mD, wdown, DM, FF, 64, 32);
    make_map(enc, &mXn, p_xn, DM, S_LEN, 64, 128);
    make_map(enc, &mWqkv, wqkv, 3 * DM, DM, 64, 64);
    make_map(enc, &mO, p_o, DM, S_LEN, 64, 64);
    make_map(enc, &mWo, wo, DM, DM, 64, 64);

    union { uint32_t u; float f; } scu; scu.u = 128u;

    launch(ln_kernel, S_LEN / 8, 256, 0, false, x, wr);
    launch(qkv_kernel, 128, 288, K1_SMEM, true, mXn, mWqkv, (const uint8_t*)wgate, (const uint8_t*)wup, (const uint8_t*)wdown, (const uint8_t*)wo);
    launch(attn_kernel, 132, 512, K2_SMEM, true, mG, mU, mD, scu.f);
    launch(oproj_kernel, 128, 256, K3_SMEM, true, mO, mWo, x, out);
}
```

```cpp
#include <cuda_runtime.h>
#include <cuda_bf16.h>
#include <cuda.h>
#include <stdint.h>
#include <type_traits>

namespace {

constexpr int S_LEN = 2048;
constexpr int DM = 512;
constexpr int NH = 32;
constexpr int FF = 1792;

__device__ __align__(1024) __nv_bfloat16 g_xn[S_LEN * DM];
__device__ __align__(16) float g_r[S_LEN];
__device__ __align__(1024) uint4 g_q[NH * 128 * 32];
__device__ __align__(1024) uint4 g_k[NH * 4096];
__device__ __align__(1024) uint4 g_v[NH * 4096];
__device__ __align__(1024) __nv_bfloat16 g_o[S_LEN * DM];
__device__ __align__(16) float g_ypart[4 * 2 * DM];
__device__ int g_sel[2];
__device__ float g_gate[2];

#define TL(k, slot) do {} while (0)

__device__ __forceinline__ uint32_t smem_u32(const void* p) { return (uint32_t)__cvta_generic_to_shared(p); }
__device__ __forceinline__ void pdl_wait() { asm volatile("griddepcontrol.wait;" ::: "memory"); }
__device__ __forceinline__ void pdl_launch() { asm volatile("griddepcontrol.launch_dependents;" ::: "memory"); }
__device__ __forceinline__ void mbar_init(uint32_t bar, uint32_t cnt) {
    asm volatile("mbarrier.init.shared::cta.b64 [%0], %1;" :: "r"(bar), "r"(cnt) : "memory");
}
__device__ __forceinline__ void mbar_expect_tx(uint32_t bar, uint32_t bytes) {
    asm volatile("mbarrier.arrive.expect_tx.shared::cta.b64 _, [%0], %1;" :: "r"(bar), "r"(bytes) : "memory");
}
__device__ __forceinline__ void mbar_arrive(uint32_t bar) {
    asm volatile("mbarrier.arrive.shared::cta.b64 _, [%0];" :: "r"(bar) : "memory");
}
__device__ __forceinline__ void mbar_wait(uint32_t bar, uint32_t parity) {
    asm volatile("{\n.reg .pred p;\n.reg .u32 n;\nmov.u32 n, 0;\n"
                 "WAIT_%=:\n"
                 "mbarrier.try_wait.parity.shared::cta.b64 p, [%0], %1;\n"
                 "@p bra DONE_%=;\n"
                 "add.u32 n, n, 1;\n"
                 "setp.lt.u32 p, n, 4000000;\n"
                 "@p bra WAIT_%=;\n"
                 "trap;\n"
                 "DONE_%=:\n}"
                 :: "r"(bar), "r"(parity) : "memory");
}
__device__ __forceinline__ void fence_barrier_init() { asm volatile("fence.mbarrier_init.release.cluster;" ::: "memory"); }
__device__ __forceinline__ void fence_proxy_async() { asm volatile("fence.proxy.async.shared::cta;" ::: "memory"); }
__device__ __forceinline__ void tma3d(uint32_t dst, const CUtensorMap* map, uint32_t bar, int row, int chunk) {
    asm volatile("cp.async.bulk.tensor.3d.shared::cluster.global.mbarrier::complete_tx::bytes [%0], [%1, {%3, %4, %5}], [%2];"
                 :: "r"(dst), "l"((uint64_t)map), "r"(bar), "r"(0), "r"(row), "r"(chunk) : "memory");
}
__device__ __forceinline__ void bulk_g2s(uint32_t dst, const void* src, uint32_t bytes, uint32_t bar) {
    asm volatile("cp.async.bulk.shared::cluster.global.mbarrier::complete_tx::bytes [%0], [%1], %2, [%3];"
                 :: "r"(dst), "l"((uint64_t)src), "r"(bytes), "r"(bar) : "memory");
}
__device__ __forceinline__ void l2_prefetch(const void* src, uint32_t bytes) {
    asm volatile("cp.async.bulk.prefetch.L2.global [%0], %1;" :: "l"((uint64_t)src), "r"(bytes) : "memory");
}
__device__ __forceinline__ void map_prefetch(const CUtensorMap* m) {
    asm volatile("prefetch.tensormap [%0];" :: "l"((uint64_t)m) : "memory");
}
__device__ __forceinline__ uint64_t mkdesc(uint32_t addr, uint32_t lbo, uint32_t sbo, uint32_t swz) {
    return (uint64_t)((addr & 0x3FFFF) >> 4) | ((uint64_t)(lbo >> 4) << 16) | ((uint64_t)(sbo >> 4) << 32) | ((uint64_t)swz << 62);
}
#define WG_FENCE() asm volatile("wgmma.fence.sync.aligned;" ::: "memory")
#define WG_COMMIT() asm volatile("wgmma.commit_group.sync.aligned;" ::: "memory")
#define WG_WAIT(n) asm volatile("wgmma.wait_group.sync.aligned %0;" :: "n"(n) : "memory")

__device__ __forceinline__ float ex2(float x) { float y; asm("ex2.approx.ftz.f32 %0, %1;" : "=f"(y) : "f"(x)); return y; }
__device__ __forceinline__ uint32_t packbf(float lo, float hi) {
    uint32_t r; asm("cvt.rn.bf16x2.f32 %0, %1, %2;" : "=r"(r) : "f"(hi), "f"(lo)); return r;
}
__device__ __forceinline__ float bf_lo(uint32_t v) { return __uint_as_float(v << 16); }
__device__ __forceinline__ float bf_hi(uint32_t v) { return __uint_as_float(v & 0xffff0000u); }
__device__ __forceinline__ float bfr(float x) { return __bfloat162float(__float2bfloat16_rn(x)); }

__global__ void __launch_bounds__(256) ln_kernel(const __nv_bfloat16* __restrict__ x, const __nv_bfloat16* __restrict__ wr) {
    TL(0, 0);
    pdl_launch();
    const int warp = threadIdx.x >> 5, lane = threadIdx.x & 31;
    const int row = blockIdx.x * 8 + warp;
    const uint4* xr = reinterpret_cast<const uint4*>(x + (size_t)row * DM);
    uint4 a = xr[lane], b = xr[32 + lane];
    const uint4* wp = reinterpret_cast<const uint4*>(wr);
    uint4 wa = wp[lane], wb = wp[32 + lane];
    uint32_t u[8] = {a.x, a.y, a.z, a.w, b.x, b.y, b.z, b.w};
    uint32_t w[8] = {wa.x, wa.y, wa.z, wa.w, wb.x, wb.y, wb.z, wb.w};
    float f[16];
    float sum = 0.f;
#pragma unroll
    for (int i = 0; i < 8; i++) { f[2 * i] = bf_lo(u[i]); f[2 * i + 1] = bf_hi(u[i]); sum += f[2 * i] + f[2 * i + 1]; }
#pragma unroll
    for (int o = 16; o > 0; o >>= 1) sum += __shfl_xor_sync(~0u, sum, o);
    const float mean = sum * (1.f / DM);
    float sq = 0.f;
#pragma unroll
    for (int i = 0; i < 16; i++) { float d = f[i] - mean; sq = fmaf(d, d, sq); }
#pragma unroll
    for (int o = 16; o > 0; o >>= 1) sq += __shfl_xor_sync(~0u, sq, o);
    const float mb = bfr(mean);
    const float vb = bfr(sq * (1.f / DM));
    const float den = bfr(sqrtf(bfr(vb + 1e-5f)));
    const float rinv = 1.f / den;
    uint32_t o[8];
    float r = 0.f;
#pragma unroll
    for (int i = 0; i < 8; i++) {
        float d0 = bfr(f[2 * i] - mb), d1 = bfr(f[2 * i + 1] - mb);
        o[i] = packbf(d0 * rinv, d1 * rinv);
        r = fmaf(bf_lo(o[i]), bf_lo(w[i]), r);
        r = fmaf(bf_hi(o[i]), bf_hi(w[i]), r);
    }
#pragma unroll
    for (int of = 16; of > 0; of >>= 1) r += __shfl_xor_sync(~0u, r, of);
    uint4* xo = reinterpret_cast<uint4*>(g_xn + (size_t)row * DM);
    xo[lane] = make_uint4(o[0], o[1], o[2], o[3]);
    xo[32 + lane] = make_uint4(o[4], o[5], o[6], o[7]);
    if (lane == 0) g_r[row] = r;
    TL(0, 3);
}

constexpr int K1_ST = 5;
constexpr int K1_STAGE = 16384 + 24576;
constexpr int K1_SMEM = K1_ST * K1_STAGE + 1024 + 128;

__device__ __forceinline__ void wgmma_n192(float (&d)[96], uint64_t da, uint64_t db, int scale_d) {
    asm volatile("{\n.reg .pred p;\nsetp.ne.b32 p, %98, 0;\n"
        "wgmma.mma_async.sync.aligned.m64n192k16.f32.bf16.bf16 "
        "{%0,%1,%2,%3,%4,%5,%6,%7,%8,%9,%10,%11,%12,%13,%14,%15,%16,%17,%18,%19,%20,%21,%22,%23,"
        "%24,%25,%26,%27,%28,%29,%30,%31,%32,%33,%34,%35,%36,%37,%38,%39,%40,%41,%42,%43,%44,%45,%46,%47,"
        "%48,%49,%50,%51,%52,%53,%54,%55,%56,%57,%58,%59,%60,%61,%62,%63,%64,%65,%66,%67,%68,%69,%70,%71,"
        "%72,%73,%74,%75,%76,%77,%78,%79,%80,%81,%82,%83,%84,%85,%86,%87,%88,%89,%90,%91,%92,%93,%94,%95}, "
        "%96, %97, p, 1, 1, 0, 1;\n}"
        : "+f"(d[0]), "+f"(d[1]), "+f"(d[2]), "+f"(d[3]), "+f"(d[4]), "+f"(d[5]), "+f"(d[6]), "+f"(d[7]),
          "+f"(d[8]), "+f"(d[9]), "+f"(d[10]), "+f"(d[11]), "+f"(d[12]), "+f"(d[13]), "+f"(d[14]), "+f"(d[15]),
          "+f"(d[16]), "+f"(d[17]), "+f"(d[18]), "+f"(d[19]), "+f"(d[20]), "+f"(d[21]), "+f"(d[22]), "+f"(d[23]),
          "+f"(d[24]), "+f"(d[25]), "+f"(d[26]), "+f"(d[27]), "+f"(d[28]), "+f"(d[29]), "+f"(d[30]), "+f"(d[31]),
          "+f"(d[32]), "+f"(d[33]), "+f"(d[34]), "+f"(d[35]), "+f"(d[36]), "+f"(d[37]), "+f"(d[38]), "+f"(d[39]),
          "+f"(d[40]), "+f"(d[41]), "+f"(d[42]), "+f"(d[43]), "+f"(d[44]), "+f"(d[45]), "+f"(d[46]), "+f"(d[47]),
          "+f"(d[48]), "+f"(d[49]), "+f"(d[50]), "+f"(d[51]), "+f"(d[52]), "+f"(d[53]), "+f"(d[54]), "+f"(d[55]),
          "+f"(d[56]), "+f"(d[57]), "+f"(d[58]), "+f"(d[59]), "+f"(d[60]), "+f"(d[61]), "+f"(d[62]), "+f"(d[63]),
          "+f"(d[64]), "+f"(d[65]), "+f"(d[66]), "+f"(d[67]), "+f"(d[68]), "+f"(d[69]), "+f"(d[70]), "+f"(d[71]),
          "+f"(d[72]), "+f"(d[73]), "+f"(d[74]), "+f"(d[75]), "+f"(d[76]), "+f"(d[77]), "+f"(d[78]), "+f"(d[79]),
          "+f"(d[80]), "+f"(d[81]), "+f"(d[82]), "+f"(d[83]), "+f"(d[84]), "+f"(d[85]), "+f"(d[86]), "+f"(d[87]),
          "+f"(d[88]), "+f"(d[89]), "+f"(d[90]), "+f"(d[91]), "+f"(d[92]), "+f"(d[93]), "+f"(d[94]), "+f"(d[95])
        : "l"(da), "l"(db), "r"(scale_d));
}

__global__ void __launch_bounds__(320, 1) qkv_kernel(const __grid_constant__ CUtensorMap mapA, const __grid_constant__ CUtensorMap mapB,
                                                     const uint8_t* __restrict__ pwg, const uint8_t* __restrict__ pwu, const uint8_t* __restrict__ pwd,
                                                     const uint8_t* __restrict__ pwo) {
    extern __shared__ uint8_t smem_raw[];
    const uint32_t sbase = (smem_u32(smem_raw) + 1023u) & ~1023u;
    const uint32_t bars = sbase + K1_ST * K1_STAGE;
    const int warp = threadIdx.x >> 5, lane = threadIdx.x & 31;
    const int nb = blockIdx.x & 7, mb = blockIdx.x >> 3;
    TL(1, 0);
    if (threadIdx.x == 0) {
        for (int s = 0; s < K1_ST; s++) { mbar_init(bars + 8 * s, 2); mbar_init(bars + 8 * (K1_ST + s), 2); }
        fence_barrier_init();
    }
    __syncthreads();
    if (warp == 8) {
        if (lane == 0) {
            for (int c = 0; c < 8; c++) {
                const int s = c < K1_ST ? c : c - K1_ST;
                if (c >= K1_ST) mbar_wait(bars + 8 * (K1_ST + s), 0);
                mbar_expect_tx(bars + 8 * s, 24576);
                tma3d(sbase + s * K1_STAGE + 16384, &mapB, bars + 8 * s, c * 64, nb * 3);
            }
        }
        return;
    }
    if (warp == 9) {
        if (lane == 0) {
            map_prefetch(&mapA);
            pdl_wait();
            pdl_launch();
            for (int c = 0; c < 8; c++) {
                const int s = c < K1_ST ? c : c - K1_ST;
                if (c == K1_ST) {
                    l2_prefetch(pwg + blockIdx.x * 14336, 14336);
                    l2_prefetch(pwu + blockIdx.x * 14336, 14336);
                    l2_prefetch(pwd + blockIdx.x * 14336, 14336);
                    l2_prefetch(pwo + blockIdx.x * 4096, 4096);
                }
                if (c >= K1_ST) mbar_wait(bars + 8 * (K1_ST + s), 0);
                mbar_expect_tx(bars + 8 * s, 16384);
                tma3d(sbase + s * K1_STAGE, &mapA, bars + 8 * s, mb * 128, c);
            }
        }
        return;
    }
    const int wg = warp >> 2;
    float acc[96];
#pragma unroll
    for (int i = 0; i < 96; i++) acc[i] = 0.f;
#pragma unroll 1
    for (int c = 0; c < 8; c++) {
        const int s = c < K1_ST ? c : c - K1_ST;
        const uint32_t st = sbase + s * K1_STAGE;
        mbar_wait(bars + 8 * s, c < K1_ST ? 0 : 1);
        if (c == 0) TL(1, 1);
        const uint64_t da = mkdesc(st + wg * 8192, 16, 1024, 1);
        const uint64_t db = mkdesc(st + 16384, 8192, 1024, 1);
        WG_FENCE();
#pragma unroll
        for (int k = 0; k < 4; k++) wgmma_n192(acc, da + k * 2, db + k * 128, (c | k) != 0);
        WG_COMMIT();
        if (c + K1_ST < 8 + 1) {
            WG_WAIT(1);
            if (c >= 1 && (threadIdx.x & 127) == 0) mbar_arrive(bars + 8 * (K1_ST + c - 1));
        }
    }
    WG_WAIT(0);
    TL(1, 2);
    const int g = lane >> 2, t = lane & 3;
    const int mt = mb * 8 + warp;
#pragma unroll
    for (int hh = 0; hh < 12; hh++) {
        const int gh = nb * 12 + hh;
        const float* a = &acc[hh * 8];
        if (gh < 32) {
            uint4 v;
            v.x = packbf(a[0], a[1]); v.y = packbf(a[2], a[3]);
            v.z = packbf(a[4], a[5]); v.w = packbf(a[6], a[7]);
            g_q[(gh * 128 + mt) * 32 + lane] = v;
        } else {
            uint32_t* dst = reinterpret_cast<uint32_t*>(gh < 64 ? g_k + (gh - 32) * 4096 : g_v + (gh - 64) * 4096);
            const float ks = gh < 64 ? 5.421010862427522e-20f : 1.0f;
            const int off = (mt * 16 + g) * 4 + t;
            dst[off] = packbf(a[0] * ks, a[1] * ks);
            dst[off + 32] = packbf(a[2] * ks, a[3] * ks);
            dst[8192 + off] = packbf(a[4] * ks, a[5] * ks);
            dst[8192 + off + 32] = packbf(a[6] * ks, a[7] * ks);
        }
    }
    TL(1, 3);
}

constexpr float SHIFT = 90.0f;
constexpr float QS = 0.25f * 1.4426950408889634f * 18446744073709551616.0f;
constexpr float scq = 0.25f * 1.4426950408889634f * 3.3087224502121107e-24f;
constexpr int K2_SMEM = 163840 + 1024 + 128;

__device__ __forceinline__ uint32_t polyexp(float lo, float hi) {
    uint32_t w, g, q, h;
    asm("cvt.pack.sat.s16.s32 %0, %1, %2;" : "=r"(w) : "r"(__float_as_uint(hi)), "r"(__float_as_uint(lo)));
    g = w & 0x007F007Fu;
    asm("fma.rn.f16x2 %0, %1, %2, %3;" : "=r"(q) : "r"(g), "r"(0xf940f940u), "r"(0x35513551u));
    asm("mul.rn.f16x2 %0, %1, %2;" : "=r"(h) : "r"(q), "r"(g));
    return w - h;
}
__device__ __forceinline__ void qk64(float (&s)[32], const uint32_t (&q)[4], uint64_t db) {
    asm volatile("wgmma.mma_async.sync.aligned.m64n64k16.f32.bf16.bf16 "
        "{%0,%1,%2,%3,%4,%5,%6,%7,%8,%9,%10,%11,%12,%13,%14,%15,%16,%17,%18,%19,%20,%21,%22,%23,%24,%25,%26,%27,%28,%29,%30,%31}, "
        "{%32,%33,%34,%35}, %36, 0, 1, 1, 0;"
        : "=f"(s[0]), "=f"(s[1]), "=f"(s[2]), "=f"(s[3]), "=f"(s[4]), "=f"(s[5]), "=f"(s[6]), "=f"(s[7]),
          "=f"(s[8]), "=f"(s[9]), "=f"(s[10]), "=f"(s[11]), "=f"(s[12]), "=f"(s[13]), "=f"(s[14]), "=f"(s[15]),
          "=f"(s[16]), "=f"(s[17]), "=f"(s[18]), "=f"(s[19]), "=f"(s[20]), "=f"(s[21]), "=f"(s[22]), "=f"(s[23]),
          "=f"(s[24]), "=f"(s[25]), "=f"(s[26]), "=f"(s[27]), "=f"(s[28]), "=f"(s[29]), "=f"(s[30]), "=f"(s[31])
        : "r"(q[0]), "r"(q[1]), "r"(q[2]), "r"(q[3]), "l"(db));
}
__device__ __forceinline__ void pv24(float (&o)[12], uint32_t a0, uint32_t a1, uint32_t a2, uint32_t a3, uint64_t db) {
    asm volatile("wgmma.mma_async.sync.aligned.m64n24k16.f32.bf16.bf16 "
        "{%0,%1,%2,%3,%4,%5,%6,%7,%8,%9,%10,%11}, {%12,%13,%14,%15}, %16, 1, 1, 1, 1;"
        : "+f"(o[0]), "+f"(o[1]), "+f"(o[2]), "+f"(o[3]), "+f"(o[4]), "+f"(o[5]), "+f"(o[6]), "+f"(o[7]),
          "+f"(o[8]), "+f"(o[9]), "+f"(o[10]), "+f"(o[11])
        : "r"(a0), "r"(a1), "r"(a2), "r"(a3), "l"(db));
}

__device__ __forceinline__ void attn_safe(float (&o)[12], const uint32_t (&q)[4], uint64_t kdesc0, uint64_t vdesc0) {
    float s[32];
    float m0 = -INFINITY, m1 = -INFINITY;
#pragma unroll
    for (int i = 0; i < 12; i++) o[i] = 0.f;
#pragma unroll 1
    for (int j = 0; j < 32; j++) {
        WG_FENCE();
        qk64(s, q, kdesc0 + (uint64_t)(j * 64));
        WG_COMMIT(); WG_WAIT(0);
        float n0 = m0, n1 = m1;
#pragma unroll
        for (int i = 0; i < 8; i++) { n0 = fmaxf(n0, fmaxf(s[4 * i], s[4 * i + 1])); n1 = fmaxf(n1, fmaxf(s[4 * i + 2], s[4 * i + 3])); }
        n0 = fmaxf(n0, __shfl_xor_sync(~0u, n0, 1)); n0 = fmaxf(n0, __shfl_xor_sync(~0u, n0, 2));
        n1 = fmaxf(n1, __shfl_xor_sync(~0u, n1, 1)); n1 = fmaxf(n1, __shfl_xor_sync(~0u, n1, 2));
        const float c0 = ex2((m0 - n0) * QS), c1 = ex2((m1 - n1) * QS);
        m0 = n0; m1 = n1;
#pragma unroll
        for (int i = 0; i < 3; i++) { o[4 * i] *= c0; o[4 * i + 1] *= c0; o[4 * i + 2] *= c1; o[4 * i + 3] *= c1; }
        uint32_t p[16];
#pragma unroll
        for (int i = 0; i < 8; i++) {
            p[2 * i] = packbf(ex2((s[4 * i] - m0) * QS), ex2((s[4 * i + 1] - m0) * QS));
            p[2 * i + 1] = packbf(ex2((s[4 * i + 2] - m1) * QS), ex2((s[4 * i + 3] - m1) * QS));
        }
        WG_FENCE();
#pragma unroll
        for (int kk = 0; kk < 4; kk++) pv24(o, p[4 * kk], p[4 * kk + 1], p[4 * kk + 2], p[4 * kk + 3], vdesc0 + (uint64_t)(j * 64 + kk * 16));
        WG_COMMIT(); WG_WAIT(0);
    }
}

__device__ __forceinline__ void attn_store(const float (&o)[12], int head, int m64, int warp, int lane) {
    const int g = lane >> 2, t = lane & 3;
    const int row = m64 * 64 + warp * 16 + g;
    const float i0 = 1.f / o[8], i1 = 1.f / o[10];
    uint32_t* p0 = reinterpret_cast<uint32_t*>(g_o + (size_t)row * DM + head * 16 + t * 2);
    uint32_t* p1 = reinterpret_cast<uint32_t*>(g_o + (size_t)(row + 8) * DM + head * 16 + t * 2);
    p0[0] = packbf(o[0] * i0, o[1] * i0); p0[4] = packbf(o[4] * i0, o[5] * i0);
    p1[0] = packbf(o[2] * i1, o[3] * i1); p1[4] = packbf(o[6] * i1, o[7] * i1);
}

constexpr int FS_N = 4;
constexpr int FS_BYTES = 32768;
__device__ __forceinline__ void ldsm4t(uint32_t& r0, uint32_t& r1, uint32_t& r2, uint32_t& r3, uint32_t addr) {
    asm volatile("ldmatrix.sync.aligned.m8n8.x4.trans.shared.b16 {%0,%1,%2,%3}, [%4];" : "=r"(r0), "=r"(r1), "=r"(r2), "=r"(r3) : "r"(addr) : "memory");
}
__device__ __forceinline__ void mma16816(float (&d)[4], uint32_t a0, uint32_t a2, uint32_t b0, uint32_t b1) {
    asm volatile("mma.sync.aligned.m16n8k16.row.col.f32.bf16.bf16.f32 {%0,%1,%2,%3}, {%4,%5,%6,%5}, {%7,%8}, {%0,%1,%2,%3};"
                 : "+f"(d[0]), "+f"(d[1]), "+f"(d[2]), "+f"(d[3]) : "r"(a0), "r"(0u), "r"(a2), "r"(b0), "r"(b1));
}
__device__ void ffn_block(int c, uint8_t* smem, uint32_t sbase, const CUtensorMap* mapG, const CUtensorMap* mapU, const CUtensorMap* mapD) {
    const int tid = threadIdx.x, warp = tid >> 5, lane = tid & 31;
    uint32_t* sx = reinterpret_cast<uint32_t*>(smem + FS_N * FS_BYTES);
    __nv_bfloat16* sh = reinterpret_cast<__nv_bfloat16*>(sx + 512);
    const uint32_t bars = sbase + FS_N * FS_BYTES + 8192;
    __shared__ float tv[32]; __shared__ int ti[32];
    __shared__ int ssel[2];
    auto issue = [&](int item) {
        const int slot = item % FS_N;
        const uint32_t dst = sbase + slot * FS_BYTES, bar = bars + 8 * slot;
        mbar_expect_tx(bar, item < 32 ? 28672 : 32768);
        if (item < 32) {
            tma3d(dst, mapG, bar, item * 16, c * 7);
            tma3d(dst + 14336, mapU, bar, item * 16, c * 7);
        } else {
            tma3d(dst, mapD, bar, c * 448 + (item - 32) * 32, 0);
        }
    };
    if (tid == 0) {
        for (int i = 0; i < FS_N; i++) mbar_init(bars + 8 * i, 1);
        fence_barrier_init();
        for (int i = 0; i < FS_N; i++) issue(i);
    }
    float b1 = -INFINITY, b2 = -INFINITY; int i1 = 0x7fffffff, i2 = 0x7fffffff;
    auto push = [&](float v, int i) {
        if (v > b1 || (v == b1 && i < i1)) { b2 = b1; i2 = i1; b1 = v; i1 = i; }
        else if (v > b2 || (v == b2 && i < i2)) { b2 = v; i2 = i; }
    };
    {
        const float4 rv = reinterpret_cast<const float4*>(g_r)[tid];
        push(rv.x, 4 * tid); push(rv.y, 4 * tid + 1); push(rv.z, 4 * tid + 2); push(rv.w, 4 * tid + 3);
    }
#pragma unroll
    for (int o = 16; o > 0; o >>= 1) {
        float v1 = __shfl_xor_sync(~0u, b1, o), v2 = __shfl_xor_sync(~0u, b2, o);
        int j1 = __shfl_xor_sync(~0u, i1, o), j2 = __shfl_xor_sync(~0u, i2, o);
        push(v1, j1); push(v2, j2);
    }
    if (lane == 0) { tv[2 * warp] = b1; ti[2 * warp] = i1; tv[2 * warp + 1] = b2; ti[2 * warp + 1] = i2; }
    __syncthreads();
    if (warp == 1) {
        b1 = tv[lane]; i1 = ti[lane]; b2 = -INFINITY; i2 = 0x7fffffff;
#pragma unroll
        for (int o = 16; o > 0; o >>= 1) {
            float v1 = __shfl_xor_sync(~0u, b1, o), v2 = __shfl_xor_sync(~0u, b2, o);
            int j1 = __shfl_xor_sync(~0u, i1, o), j2 = __shfl_xor_sync(~0u, i2, o);
            push(v1, j1); push(v2, j2);
        }
        if (lane == 0) {
            i1 = min(max(i1, 0), S_LEN - 1); i2 = min(max(i2, 0), S_LEN - 1);
            ssel[0] = i1; ssel[1] = i2;
            if (c == 0) {
                g_sel[0] = i1; g_sel[1] = i2;
                g_gate[0] = bfr(1.f / (1.f + __expf(-bfr(b1))));
                g_gate[1] = bfr(1.f / (1.f + __expf(-bfr(b2))));
            }
        }
    }
    __syncthreads();
    sx[tid] = *reinterpret_cast<const uint32_t*>(g_xn + (size_t)ssel[tid >> 8] * DM + (tid & 255) * 2);
    __syncthreads();
    TL(2, 1);
    const int g = lane >> 2, t = lane & 3;
    const int lrow = lane & 15, lsel = lane >> 4;
    {
        float ag[4][4], au[4][4];
#pragma unroll
        for (int j = 0; j < 4; j++) { ag[j][0] = ag[j][1] = ag[j][2] = ag[j][3] = 0.f; au[j][0] = au[j][1] = au[j][2] = au[j][3] = 0.f; }
#pragma unroll 1
        for (int it = 0; it < 32; it++) {
            const int slot = it % FS_N;
            const uint32_t a0 = g < 2 ? sx[g * 256 + it * 8 + t] : 0u, a2 = g < 2 ? sx[g * 256 + it * 8 + 4 + t] : 0u;
            mbar_wait(bars + 8 * slot, (it / FS_N) & 1);
            const uint32_t base = sbase + slot * FS_BYTES + lsel * 14336 + lrow * 128;
#pragma unroll
            for (int j = 0; j < 4; j++) {
                const int nt = warp + j * 16;
                if (nt < 56) {
                    uint32_t b0, b1, b2, b3;
                    ldsm4t(b0, b1, b2, b3, base + (nt >> 3) * 2048 + (((nt & 7) ^ (lrow & 7)) << 4));
                    mma16816(ag[j], a0, a2, b0, b1);
                    mma16816(au[j], a0, a2, b2, b3);
                }
            }
            __syncthreads();
            if (tid == 480) issue(it + FS_N);
        }
        if (g < 2) {
#pragma unroll
            for (int j = 0; j < 4; j++) {
                const int nt = warp + j * 16;
                if (nt < 56) {
#pragma unroll
                    for (int e = 0; e < 2; e++) {
                        const float gs = bfr(ag[j][e]), us = bfr(au[j][e]);
                        const float sg = bfr(gs / (1.f + __expf(-gs)));
                        sh[g * 448 + nt * 8 + t * 2 + e] = __float2bfloat16_rn(sg * us);
                    }
                }
            }
        }
        __syncthreads();
    }
    TL(2, 2);
    {
        const uint32_t* shw = reinterpret_cast<const uint32_t*>(sh);
        float a[4][4];
#pragma unroll
        for (int j = 0; j < 4; j++) a[j][0] = a[j][1] = a[j][2] = a[j][3] = 0.f;
#pragma unroll 1
        for (int it = 32; it < 46; it++) {
            const int slot = it % FS_N;
            uint32_t af[4];
#pragma unroll
            for (int q = 0; q < 4; q++) af[q] = g < 2 ? shw[g * 224 + (it - 32) * 16 + q * 4 + t] : 0u;
            mbar_wait(bars + 8 * slot, (it / FS_N) & 1);
            const uint32_t base = sbase + slot * FS_BYTES + (warp >> 1) * 4096 + lane * 128;
#pragma unroll
            for (int j = 0; j < 4; j++) {
                const int u = (warp & 1) * 4 + j;
                uint32_t b0, b1, b2, b3;
                ldsm4t(b0, b1, b2, b3, base + ((u ^ (lane & 7)) << 4));
                mma16816(a[j], af[0], af[1], b0, b1);
                mma16816(a[j], af[2], af[3], b2, b3);
            }
            __syncthreads();
            if (tid == 480 && it + FS_N < 46) issue(it + FS_N);
        }
        if (g < 2) {
#pragma unroll
            for (int j = 0; j < 4; j++)
                *reinterpret_cast<float2*>(&g_ypart[c * 1024 + g * 512 + (warp * 4 + j) * 8 + t * 2]) = make_float2(a[j][0], a[j][1]);
        }
    }
}

__global__ void __launch_bounds__(512, 1) attn_kernel(const __grid_constant__ CUtensorMap mapG, const __grid_constant__ CUtensorMap mapU,
                                                      const __grid_constant__ CUtensorMap mapD, float sc) {
    extern __shared__ uint8_t smem_raw[];
    const uint32_t sraw = smem_u32(smem_raw);
    const uint32_t sbase = (sraw + 1023u) & ~1023u;
    uint8_t* sptr = smem_raw + (sbase - sraw);
    TL(2, 0);
    if (blockIdx.x < 4) {
        pdl_launch();
        ffn_block(blockIdx.x, sptr, sbase, &mapG, &mapU, &mapD);
        TL(2, 3);
        return;
    }
    const uint32_t bars = sbase + 163840;
    const int head = (blockIdx.x - 4) >> 2, quarter = blockIdx.x & 3;
    const int wg = threadIdx.x >> 7, warp = (threadIdx.x >> 5) & 3, lane = threadIdx.x & 31;
    if (threadIdx.x == 0) {
        for (int c = 0; c < 8; c++) mbar_init(bars + 8 * c, 1);
        fence_barrier_init();
    }
    {
        uint4* ones = reinterpret_cast<uint4*>(sptr + 131072);
        for (int i = threadIdx.x; i < 2048; i += 512) ones[i] = make_uint4(0x3f803f80u, 0x3f803f80u, 0x3f803f80u, 0x3f803f80u);
        fence_proxy_async();
    }
    __syncthreads();
    pdl_wait();
    pdl_launch();
    TL(2, 1);
    if (threadIdx.x == 0) {
        const uint8_t* kp = reinterpret_cast<const uint8_t*>(g_k + head * 4096);
        const uint8_t* vp = reinterpret_cast<const uint8_t*>(g_v + head * 4096);
        for (int c = 0; c < 8; c++) {
            mbar_expect_tx(bars + 8 * c, 16384);
            bulk_g2s(sbase + c * 4096, kp + c * 4096, 4096, bars + 8 * c);
            bulk_g2s(sbase + 32768 + c * 4096, kp + 32768 + c * 4096, 4096, bars + 8 * c);
            bulk_g2s(sbase + 65536 + c * 4096, vp + c * 4096, 4096, bars + 8 * c);
            bulk_g2s(sbase + 98304 + c * 4096, vp + 32768 + c * 4096, 4096, bars + 8 * c);
        }
    }
    const uint64_t kdesc0 = mkdesc(sbase, 32768, 128, 0);
    const uint64_t vdesc0 = mkdesc(sbase + 65536, 128, 32768, 0);
    uint32_t badmask = 0;
#pragma unroll 1
    for (int mt = 0; mt < 2; mt++) {
        const int m64 = quarter * 8 + mt * 4 + wg;
        uint32_t q[4];
        { const uint4 qq = g_q[(head * 128 + m64 * 4 + warp) * 32 + lane]; q[0] = qq.x; q[1] = qq.y; q[2] = qq.z; q[3] = qq.w; }
        float s[32], s2[32], o[12];
#pragma unroll
        for (int i = 0; i < 12; i++) o[i] = 0.f;
        mbar_wait(bars, 0);
        if (mt == 0) TL(2, 2);
        WG_FENCE();
        qk64(s, q, kdesc0);
        WG_COMMIT(); WG_WAIT(0);
        float mx0 = -INFINITY, mx1 = -INFINITY;
#pragma unroll
        for (int i = 0; i < 8; i++) { mx0 = fmaxf(mx0, fmaxf(s[4 * i], s[4 * i + 1])); mx1 = fmaxf(mx1, fmaxf(s[4 * i + 2], s[4 * i + 3])); }
        mx0 = fmaxf(mx0, __shfl_xor_sync(~0u, mx0, 1)); mx0 = fmaxf(mx0, __shfl_xor_sync(~0u, mx0, 2));
        mx1 = fmaxf(mx1, __shfl_xor_sync(~0u, mx1, 1)); mx1 = fmaxf(mx1, __shfl_xor_sync(~0u, mx1, 2));
        float cm0 = -(ceilf(mx0 * QS) + SHIFT), cm1 = -(ceilf(mx1 * QS) + SHIFT);
        float cp0 = (cm0 + 127.f) * sc, cp1 = (cm1 + 127.f) * sc;
        asm volatile("" : "+f"(cm0), "+f"(cm1), "+f"(cp0), "+f"(cp1));
        uint64_t kd = kdesc0, vd = vdesc0;
        auto step = [&](float (&sc_)[32], float (&sn)[32]) {
            kd += 64;
            WG_FENCE();
            qk64(sn, q, kd);
            WG_COMMIT();
#pragma unroll
            for (int kk = 0; kk < 4; kk++) {
                const int i0 = kk * 2, i1 = kk * 2 + 1;
                const uint32_t p0 = packbf(ex2(fmaf(sc_[4 * i0], QS, cm0)), ex2(fmaf(sc_[4 * i0 + 1], QS, cm0)));
                const uint32_t p1 = packbf(ex2(fmaf(sc_[4 * i0 + 2], QS, cm1)), ex2(fmaf(sc_[4 * i0 + 3], QS, cm1)));
                const uint32_t p2 = polyexp(fmaf(sc_[4 * i1], scq, cp0), fmaf(sc_[4 * i1 + 1], scq, cp0));
                const uint32_t p3 = polyexp(fmaf(sc_[4 * i1 + 2], scq, cp1), fmaf(sc_[4 * i1 + 3], scq, cp1));
                WG_FENCE();
                pv24(o, p0, p1, p2, p3, vd);
                vd += 16;
            }
            WG_COMMIT();
            WG_WAIT(1);
        };
#pragma unroll 1
        for (int c = 0; c < 16; c++) {
            if (mt == 0 && (c & 1) == 0 && c < 14) mbar_wait(bars + 4 * c + 8, 0);
            step(s, s2); step(s2, s);
        }
        WG_WAIT(0);
        bool bad = !(o[8] > 0.f) || !(o[10] > 0.f);
#pragma unroll
        for (int i = 0; i < 12; i++) bad = bad || !(fabsf(o[i]) <= 3.0e38f);
        uint32_t anybad;
        asm volatile("{\n.reg .pred p, q;\nsetp.ne.u32 p, %1, 0;\nbarrier.cta.red.or.pred q, %2, 128, p;\nselp.u32 %0, 1, 0, q;\n}"
                     : "=r"(anybad) : "r"((uint32_t)bad), "r"(wg + 1) : "memory");
        badmask |= anybad << mt;
        attn_store(o, head, m64, warp, lane);
    }
#pragma unroll 1
    for (int mt = 0; mt < 2; mt++) {
        if (!((badmask >> mt) & 1)) continue;
        const int m64 = quarter * 8 + mt * 4 + wg;
        uint32_t q[4];
        { const uint4 qq = g_q[(head * 128 + m64 * 4 + warp) * 32 + lane]; q[0] = qq.x; q[1] = qq.y; q[2] = qq.z; q[3] = qq.w; }
        float o[12];
        attn_safe(o, q, mkdesc(sbase, 32768, 128, 0), mkdesc(sbase + 65536, 128, 32768, 0));
        attn_store(o, head, m64, warp, lane);
    }
    TL(2, 3);
}

constexpr int K3_SMEM = 8 * 8192 + 8 * 16384 + 1024 + 128;

__device__ __forceinline__ void wgmma_n64(float (&d)[32], uint64_t da, uint64_t db, int scale_d) {
    asm volatile("{\n.reg .pred p;\nsetp.ne.b32 p, %34, 0;\n"
        "wgmma.mma_async.sync.aligned.m64n64k16.f32.bf16.bf16 "
        "{%0,%1,%2,%3,%4,%5,%6,%7,%8,%9,%10,%11,%12,%13,%14,%15,%16,%17,%18,%19,%20,%21,%22,%23,%24,%25,%26,%27,%28,%29,%30,%31}, "
        "%32, %33, p, 1, 1, 0, 1;\n}"
        : "+f"(d[0]), "+f"(d[1]), "+f"(d[2]), "+f"(d[3]), "+f"(d[4]), "+f"(d[5]), "+f"(d[6]), "+f"(d[7]),
          "+f"(d[8]), "+f"(d[9]), "+f"(d[10]), "+f"(d[11]), "+f"(d[12]), "+f"(d[13]), "+f"(d[14]), "+f"(d[15]),
          "+f"(d[16]), "+f"(d[17]), "+f"(d[18]), "+f"(d[19]), "+f"(d[20]), "+f"(d[21]), "+f"(d[22]), "+f"(d[23]),
          "+f"(d[24]), "+f"(d[25]), "+f"(d[26]), "+f"(d[27]), "+f"(d[28]), "+f"(d[29]), "+f"(d[30]), "+f"(d[31])
        : "l"(da), "l"(db), "r"(scale_d));
}

__global__ void __launch_bounds__(256, 1) oproj_kernel(const __grid_constant__ CUtensorMap mapA, const __grid_constant__ CUtensorMap mapB,
                                                       const __nv_bfloat16* __restrict__ x, __nv_bfloat16* __restrict__ out) {
    extern __shared__ uint8_t smem_raw[];
    const uint32_t sbase = (smem_u32(smem_raw) + 1023u) & ~1023u;
    const uint32_t sA = sbase, sB = sbase + 8 * 8192, bars = sbase + 8 * 8192 + 8 * 16384;
    const int warp = threadIdx.x >> 5, lane = threadIdx.x & 31, wg = warp >> 2;
    const int nb = blockIdx.x & 3, mb = blockIdx.x >> 2;
    TL(3, 0);
    if (threadIdx.x == 0) {
        for (int c = 0; c < 8; c++) mbar_init(bars + 8 * c, 1);
        fence_barrier_init();
        map_prefetch(&mapA);
        for (int h = 0; h < 2; h++) {
            mbar_expect_tx(bars + 8 * (4 + h), 65536);
            tma3d(sB + h * 65536, &mapB, bars + 8 * (4 + h), h * 256, nb * 2);
        }
    }
    const int g = lane >> 2, t = lane & 3;
    const int row0 = mb * 64 + (warp & 3) * 16 + g;
    const int col0 = nb * 128 + wg * 64 + t * 2;
    uint32_t xv[16], nv[16];
#pragma unroll
    for (int i = 0; i < 8; i++) {
        xv[2 * i] = *reinterpret_cast<const uint32_t*>(x + (size_t)row0 * DM + col0 + i * 8);
        xv[2 * i + 1] = *reinterpret_cast<const uint32_t*>(x + (size_t)(row0 + 8) * DM + col0 + i * 8);
        nv[2 * i] = *reinterpret_cast<const uint32_t*>(g_xn + (size_t)row0 * DM + col0 + i * 8);
        nv[2 * i + 1] = *reinterpret_cast<const uint32_t*>(g_xn + (size_t)(row0 + 8) * DM + col0 + i * 8);
    }
    __syncthreads();
    pdl_wait();
    TL(3, 1);
    if (threadIdx.x == 0) {
        for (int c = 0; c < 4; c++) {
            mbar_expect_tx(bars + 8 * c, 16384);
            tma3d(sA + c * 16384, &mapA, bars + 8 * c, mb * 64, c * 2);
        }
    }
    __shared__ float supd[2][128];
    const int sel0 = g_sel[0], sel1 = g_sel[1];
    {
        const int which = threadIdx.x >> 7, col = nb * 128 + (threadIdx.x & 127);
        const float y = g_ypart[which * 512 + col] + g_ypart[1024 + which * 512 + col] + g_ypart[2048 + which * 512 + col] + g_ypart[3072 + which * 512 + col];
        supd[which][threadIdx.x & 127] = bfr(bfr(y) * g_gate[which]);
    }
    __syncthreads();
    float acc[32];
#pragma unroll
    for (int i = 0; i < 32; i++) acc[i] = 0.f;
#pragma unroll 1
    for (int c = 0; c < 8; c++) {
        if ((c & 3) == 0) mbar_wait(bars + 8 * (4 + (c >> 2)), 0);
        if ((c & 1) == 0) mbar_wait(bars + 8 * (c >> 1), 0);
        const uint64_t da = mkdesc(sA + c * 8192, 16, 1024, 1);
        const uint64_t db = mkdesc(sB + (c >> 2) * 65536 + wg * 32768 + (c & 3) * 8192, 8192, 1024, 1);
        WG_FENCE();
#pragma unroll
        for (int k = 0; k < 4; k++) wgmma_n64(acc, da + k * 2, db + k * 128, (c | k) != 0);
        WG_COMMIT();
    }
    WG_WAIT(0);
    TL(3, 2);
#pragma unroll
    for (int h = 0; h < 2; h++) {
        const int row = row0 + h * 8;
        const int which = row == sel0 ? 0 : (row == sel1 ? 1 : -1);
#pragma unroll
        for (int i = 0; i < 8; i++) {
            const int col = col0 + i * 8;
            float b0 = bf_lo(nv[2 * i + h]), b1 = bf_hi(nv[2 * i + h]);
            if (which >= 0) {
                b0 = bfr(b0 + supd[which][col - nb * 128]); b1 = bfr(b1 + supd[which][col + 1 - nb * 128]);
            }
            const float t0 = bfr(bf_lo(xv[2 * i + h]) + bfr(acc[4 * i + 2 * h]));
            const float t1 = bfr(bf_hi(xv[2 * i + h]) + bfr(acc[4 * i + 2 * h + 1]));
            *reinterpret_cast<uint32_t*>(out + (size_t)row * DM + col) = packbf(t0 + b0, t1 + b1);
        }
    }
    TL(3, 3);
}

typedef CUresult (*EncodeFn)(CUtensorMap*, CUtensorMapDataType, cuuint32_t, void*, const cuuint64_t*, const cuuint64_t*,
                             const cuuint32_t*, const cuuint32_t*, CUtensorMapInterleave, CUtensorMapSwizzle,
                             CUtensorMapL2promotion, CUtensorMapFloatOOBfill);

void make_map(EncodeFn fn, CUtensorMap* m, const void* ptr, uint64_t cols, uint64_t rows, uint32_t box_rows, uint32_t box_chunks) {
    cuuint64_t dims[3] = {64, rows, cols / 64};
    cuuint64_t strides[2] = {cols * 2, 128};
    cuuint32_t box[3] = {64, box_rows, box_chunks};
    cuuint32_t es[3] = {1, 1, 1};
    fn(m, CU_TENSOR_MAP_DATA_TYPE_BFLOAT16, 3, const_cast<void*>(ptr), dims, strides, box, es, CU_TENSOR_MAP_INTERLEAVE_NONE,
       CU_TENSOR_MAP_SWIZZLE_128B, CU_TENSOR_MAP_L2_PROMOTION_L2_256B, CU_TENSOR_MAP_FLOAT_OOB_FILL_NONE);
}

template <typename... KArgs, typename... Args>
void launch(void (*kern)(KArgs...), int grid, int block, int smem, bool pdl, Args... args) {
    cudaLaunchConfig_t cfg = {};
    cfg.gridDim = dim3(grid); cfg.blockDim = dim3(block); cfg.dynamicSmemBytes = smem; cfg.stream = cudaStreamPerThread;
    cudaLaunchAttribute at[1];
    at[0].id = cudaLaunchAttributeProgrammaticStreamSerialization;
    at[0].val.programmaticStreamSerializationAllowed = 1;
    cfg.attrs = at; cfg.numAttrs = pdl ? 1 : 0;
    cudaLaunchKernelEx(&cfg, kern, KArgs(args)...);
}

}

extern "C" void kernel_launch(void* const* d_in, const int* in_sizes, int n_in, void* d_out, int out_size) {
    const __nv_bfloat16* x = (const __nv_bfloat16*)d_in[0];
    const __nv_bfloat16* wqkv = (const __nv_bfloat16*)d_in[1];
    const __nv_bfloat16* wo = (const __nv_bfloat16*)d_in[2];
    const __nv_bfloat16* wr = (const __nv_bfloat16*)d_in[4];
    const __nv_bfloat16* wgate = (const __nv_bfloat16*)d_in[5];
    const __nv_bfloat16* wup = (const __nv_bfloat16*)d_in[6];
    const __nv_bfloat16* wdown = (const __nv_bfloat16*)d_in[7];
    __nv_bfloat16* out = (__nv_bfloat16*)d_out;

    static EncodeFn enc = nullptr;
    static void* p_xn = nullptr; static void* p_o = nullptr;
    if (!enc) {
        void* fn = nullptr; cudaDriverEntryPointQueryResult qr;
        cudaGetDriverEntryPoint("cuTensorMapEncodeTiled", &fn, cudaEnableDefault, &qr);
        enc = (EncodeFn)fn;
        cudaGetSymbolAddress(&p_xn, g_xn);
        cudaGetSymbolAddress(&p_o, g_o);
        cudaFuncSetAttribute(qkv_kernel, cudaFuncAttributeMaxDynamicSharedMemorySize, K1_SMEM);
        cudaFuncSetAttribute(attn_kernel, cudaFuncAttributeMaxDynamicSharedMemorySize, K2_SMEM);
        cudaFuncSetAttribute(oproj_kernel, cudaFuncAttributeMaxDynamicSharedMemorySize, K3_SMEM);
    }
    CUtensorMap mXn, mWqkv, mO, mWo, mG, mU, mD;
    make_map(enc, &mG, wgate, FF, DM, 16, 7);
    make_map(enc, &mU, wup, FF, DM, 16, 7);
    make_map(enc, &mD, wdown, DM, FF, 32, 8);
    make_map(enc, &mXn, p_xn, DM, S_LEN, 128, 1);
    make_map(enc, &mWqkv, wqkv, 3 * DM, DM, 64, 3);
    make_map(enc, &mO, p_o, DM, S_LEN, 64, 2);
    make_map(enc, &mWo, wo, DM, DM, 256, 2);

    union { uint32_t u; float f; } scu; scu.u = 128u;

    launch(ln_kernel, S_LEN / 8, 256, 0, false, x, wr);
    launch(qkv_kernel, 128, 320, K1_SMEM, true, mXn, mWqkv, (const uint8_t*)wgate, (const uint8_t*)wup, (const uint8_t*)wdown, (const uint8_t*)wo);
    launch(attn_kernel, 132, 512, K2_SMEM, true, mG, mU, mD, scu.f);
    launch(oproj_kernel, 128, 256, K3_SMEM, true, mO, mWo, x, out);
}
```

```cpp
#include <cuda_runtime.h>
#include <cuda_bf16.h>
#include <cuda.h>
#include <stdint.h>
#include <type_traits>

namespace {

constexpr int S_LEN = 2048;
constexpr int DM = 512;
constexpr int NH = 32;
constexpr int FF = 1792;

__device__ __align__(1024) __nv_bfloat16 g_xn[S_LEN * DM];
__device__ __align__(16) float g_r[S_LEN];
__device__ __align__(1024) uint4 g_q[NH * 128 * 32];
__device__ __align__(1024) uint4 g_k[NH * 4096];
__device__ __align__(1024) uint4 g_v[NH * 4096];
__device__ __align__(1024) __nv_bfloat16 g_o[S_LEN * DM];
__device__ __align__(16) float g_ypart[4 * 2 * DM];
__device__ int g_sel[2];
__device__ float g_gate[2];
constexpr int C_LN = 0, C_QKV = 16, C_O = 24, C_FFN = 56, C_EXIT = 57, C_NUM = 58;
__device__ unsigned g_cnt[C_NUM * 32];

#define TL(slot) do {} while (0)

__device__ __forceinline__ uint32_t smem_u32(const void* p) { return (uint32_t)__cvta_generic_to_shared(p); }
__device__ __forceinline__ void warp_arrive(int idx) {
    asm volatile("fence.proxy.async.global;" ::: "memory");
    __syncwarp();
    if ((threadIdx.x & 31) == 0) {
        __threadfence();
        asm volatile("red.release.gpu.global.add.u32 [%0], 1;" :: "l"(g_cnt + idx * 32) : "memory");
    }
}
__device__ __forceinline__ void flag_wait(int idx, unsigned target) {
    unsigned v, n = 0;
    do {
        asm volatile("ld.acquire.gpu.global.u32 %0, [%1];" : "=r"(v) : "l"(g_cnt + idx * 32) : "memory");
        if (v >= target) return;
    } while (++n < (1u << 24));
    __trap();
}
__device__ __forceinline__ void fence_proxy_async_all() { asm volatile("fence.proxy.async;" ::: "memory"); }
__device__ __forceinline__ void mbar_init(uint32_t bar, uint32_t cnt) {
    asm volatile("mbarrier.init.shared::cta.b64 [%0], %1;" :: "r"(bar), "r"(cnt) : "memory");
}
__device__ __forceinline__ void mbar_expect_tx(uint32_t bar, uint32_t bytes) {
    asm volatile("mbarrier.arrive.expect_tx.shared::cta.b64 _, [%0], %1;" :: "r"(bar), "r"(bytes) : "memory");
}
__device__ __forceinline__ void mbar_arrive(uint32_t bar) {
    asm volatile("mbarrier.arrive.shared::cta.b64 _, [%0];" :: "r"(bar) : "memory");
}
__device__ __forceinline__ void mbar_wait(uint32_t bar, uint32_t parity) {
    asm volatile("{\n.reg .pred p;\n.reg .u32 n;\nmov.u32 n, 0;\n"
                 "WAIT_%=:\n"
                 "mbarrier.try_wait.parity.shared::cta.b64 p, [%0], %1;\n"
                 "@p bra DONE_%=;\n"
                 "add.u32 n, n, 1;\n"
                 "setp.lt.u32 p, n, 4000000;\n"
                 "@p bra WAIT_%=;\n"
                 "trap;\n"
                 "DONE_%=:\n}"
                 :: "r"(bar), "r"(parity) : "memory");
}
__device__ __forceinline__ void fence_barrier_init() { asm volatile("fence.mbarrier_init.release.cluster;" ::: "memory"); }
__device__ __forceinline__ void fence_proxy_async() { asm volatile("fence.proxy.async.shared::cta;" ::: "memory"); }
__device__ __forceinline__ void tma3d(uint32_t dst, const CUtensorMap* map, uint32_t bar, int row, int chunk) {
    asm volatile("cp.async.bulk.tensor.3d.shared::cluster.global.mbarrier::complete_tx::bytes [%0], [%1, {%3, %4, %5}], [%2];"
                 :: "r"(dst), "l"((uint64_t)map), "r"(bar), "r"(0), "r"(row), "r"(chunk) : "memory");
}
__device__ __forceinline__ void bulk_g2s(uint32_t dst, const void* src, uint32_t bytes, uint32_t bar) {
    asm volatile("cp.async.bulk.shared::cluster.global.mbarrier::complete_tx::bytes [%0], [%1], %2, [%3];"
                 :: "r"(dst), "l"((uint64_t)src), "r"(bytes), "r"(bar) : "memory");
}
__device__ __forceinline__ void l2_prefetch(const void* src, uint32_t bytes) {
    asm volatile("cp.async.bulk.prefetch.L2.global [%0], %1;" :: "l"((uint64_t)src), "r"(bytes) : "memory");
}
__device__ __forceinline__ void map_prefetch(const CUtensorMap* m) {
    asm volatile("prefetch.tensormap [%0];" :: "l"((uint64_t)m) : "memory");
}
__device__ __forceinline__ uint64_t mkdesc(uint32_t addr, uint32_t lbo, uint32_t sbo, uint32_t swz) {
    return (uint64_t)((addr & 0x3FFFF) >> 4) | ((uint64_t)(lbo >> 4) << 16) | ((uint64_t)(sbo >> 4) << 32) | ((uint64_t)swz << 62);
}
#define WG_FENCE() asm volatile("wgmma.fence.sync.aligned;" ::: "memory")
#define WG_COMMIT() asm volatile("wgmma.commit_group.sync.aligned;" ::: "memory")
#define WG_WAIT(n) asm volatile("wgmma.wait_group.sync.aligned %0;" :: "n"(n) : "memory")

__device__ __forceinline__ float ex2(float x) { float y; asm("ex2.approx.ftz.f32 %0, %1;" : "=f"(y) : "f"(x)); return y; }
__device__ __forceinline__ uint32_t packbf(float lo, float hi) {
    uint32_t r; asm("cvt.rn.bf16x2.f32 %0, %1, %2;" : "=r"(r) : "f"(hi), "f"(lo)); return r;
}
__device__ __forceinline__ float bf_lo(uint32_t v) { return __uint_as_float(v << 16); }
__device__ __forceinline__ float bf_hi(uint32_t v) { return __uint_as_float(v & 0xffff0000u); }
__device__ __forceinline__ float bfr(float x) { return __bfloat162float(__float2bfloat16_rn(x)); }

__device__ __forceinline__ void wgmma_n192(float (&d)[96], uint64_t da, uint64_t db, int scale_d) {
    asm volatile("{\n.reg .pred p;\nsetp.ne.b32 p, %98, 0;\n"
        "wgmma.mma_async.sync.aligned.m64n192k16.f32.bf16.bf16 "
        "{%0,%1,%2,%3,%4,%5,%6,%7,%8,%9,%10,%11,%12,%13,%14,%15,%16,%17,%18,%19,%20,%21,%22,%23,"
        "%24,%25,%26,%27,%28,%29,%30,%31,%32,%33,%34,%35,%36,%37,%38,%39,%40,%41,%42,%43,%44,%45,%46,%47,"
        "%48,%49,%50,%51,%52,%53,%54,%55,%56,%57,%58,%59,%60,%61,%62,%63,%64,%65,%66,%67,%68,%69,%70,%71,"
        "%72,%73,%74,%75,%76,%77,%78,%79,%80,%81,%82,%83,%84,%85,%86,%87,%88,%89,%90,%91,%92,%93,%94,%95}, "
        "%96, %97, p, 1, 1, 0, 1;\n}"
        : "+f"(d[0]), "+f"(d[1]), "+f"(d[2]), "+f"(d[3]), "+f"(d[4]), "+f"(d[5]), "+f"(d[6]), "+f"(d[7]),
          "+f"(d[8]), "+f"(d[9]), "+f"(d[10]), "+f"(d[11]), "+f"(d[12]), "+f"(d[13]), "+f"(d[14]), "+f"(d[15]),
          "+f"(d[16]), "+f"(d[17]), "+f"(d[18]), "+f"(d[19]), "+f"(d[20]), "+f"(d[21]), "+f"(d[22]), "+f"(d[23]),
          "+f"(d[24]), "+f"(d[25]), "+f"(d[26]), "+f"(d[27]), "+f"(d[28]), "+f"(d[29]), "+f"(d[30]), "+f"(d[31]),
          "+f"(d[32]), "+f"(d[33]), "+f"(d[34]), "+f"(d[35]), "+f"(d[36]), "+f"(d[37]), "+f"(d[38]), "+f"(d[39]),
          "+f"(d[40]), "+f"(d[41]), "+f"(d[42]), "+f"(d[43]), "+f"(d[44]), "+f"(d[45]), "+f"(d[46]), "+f"(d[47]),
          "+f"(d[48]), "+f"(d[49]), "+f"(d[50]), "+f"(d[51]), "+f"(d[52]), "+f"(d[53]), "+f"(d[54]), "+f"(d[55]),
          "+f"(d[56]), "+f"(d[57]), "+f"(d[58]), "+f"(d[59]), "+f"(d[60]), "+f"(d[61]), "+f"(d[62]), "+f"(d[63]),
          "+f"(d[64]), "+f"(d[65]), "+f"(d[66]), "+f"(d[67]), "+f"(d[68]), "+f"(d[69]), "+f"(d[70]), "+f"(d[71]),
          "+f"(d[72]), "+f"(d[73]), "+f"(d[74]), "+f"(d[75]), "+f"(d[76]), "+f"(d[77]), "+f"(d[78]), "+f"(d[79]),
          "+f"(d[80]), "+f"(d[81]), "+f"(d[82]), "+f"(d[83]), "+f"(d[84]), "+f"(d[85]), "+f"(d[86]), "+f"(d[87]),
          "+f"(d[88]), "+f"(d[89]), "+f"(d[90]), "+f"(d[91]), "+f"(d[92]), "+f"(d[93]), "+f"(d[94]), "+f"(d[95])
        : "l"(da), "l"(db), "r"(scale_d));
}

constexpr float SHIFT = 90.0f;
constexpr float QS = 0.25f * 1.4426950408889634f * 18446744073709551616.0f;
constexpr float scq = 0.25f * 1.4426950408889634f * 3.3087224502121107e-24f;

__device__ __forceinline__ uint32_t polyexp(float lo, float hi) {
    uint32_t w, g, q, h;
    asm("cvt.pack.sat.s16.s32 %0, %1, %2;" : "=r"(w) : "r"(__float_as_uint(hi)), "r"(__float_as_uint(lo)));
    g = w & 0x007F007Fu;
    asm("fma.rn.f16x2 %0, %1, %2, %3;" : "=r"(q) : "r"(g), "r"(0xf940f940u), "r"(0x35513551u));
    asm("mul.rn.f16x2 %0, %1, %2;" : "=r"(h) : "r"(q), "r"(g));
    return w - h;
}
__device__ __forceinline__ void qk64(float (&s)[32], const uint32_t (&q)[4], uint64_t db) {
    asm volatile("wgmma.mma_async.sync.aligned.m64n64k16.f32.bf16.bf16 "
        "{%0,%1,%2,%3,%4,%5,%6,%7,%8,%9,%10,%11,%12,%13,%14,%15,%16,%17,%18,%19,%20,%21,%22,%23,%24,%25,%26,%27,%28,%29,%30,%31}, "
        "{%32,%33,%34,%35}, %36, 0, 1, 1, 0;"
        : "=f"(s[0]), "=f"(s[1]), "=f"(s[2]), "=f"(s[3]), "=f"(s[4]), "=f"(s[5]), "=f"(s[6]), "=f"(s[7]),
          "=f"(s[8]), "=f"(s[9]), "=f"(s[10]), "=f"(s[11]), "=f"(s[12]), "=f"(s[13]), "=f"(s[14]), "=f"(s[15]),
          "=f"(s[16]), "=f"(s[17]), "=f"(s[18]), "=f"(s[19]), "=f"(s[20]), "=f"(s[21]), "=f"(s[22]), "=f"(s[23]),
          "=f"(s[24]), "=f"(s[25]), "=f"(s[26]), "=f"(s[27]), "=f"(s[28]), "=f"(s[29]), "=f"(s[30]), "=f"(s[31])
        : "r"(q[0]), "r"(q[1]), "r"(q[2]), "r"(q[3]), "l"(db));
}
__device__ __forceinline__ void pv24(float (&o)[12], uint32_t a0, uint32_t a1, uint32_t a2, uint32_t a3, uint64_t db) {
    asm volatile("wgmma.mma_async.sync.aligned.m64n24k16.f32.bf16.bf16 "
        "{%0,%1,%2,%3,%4,%5,%6,%7,%8,%9,%10,%11}, {%12,%13,%14,%15}, %16, 1, 1, 1, 1;"
        : "+f"(o[0]), "+f"(o[1]), "+f"(o[2]), "+f"(o[3]), "+f"(o[4]), "+f"(o[5]), "+f"(o[6]), "+f"(o[7]),
          "+f"(o[8]), "+f"(o[9]), "+f"(o[10]), "+f"(o[11])
        : "r"(a0), "r"(a1), "r"(a2), "r"(a3), "l"(db));
}

__device__ __forceinline__ void attn_safe(float (&o)[12], const uint32_t (&q)[4], uint64_t kdesc0, uint64_t vdesc0) {
    float s[32];
    float m0 = -INFINITY, m1 = -INFINITY;
#pragma unroll
    for (int i = 0; i < 12; i++) o[i] = 0.f;
#pragma unroll 1
    for (int j = 0; j < 32; j++) {
        WG_FENCE();
        qk64(s, q, kdesc0 + (uint64_t)(j * 64));
        WG_COMMIT(); WG_WAIT(0);
        float n0 = m0, n1 = m1;
#pragma unroll
        for (int i = 0; i < 8; i++) { n0 = fmaxf(n0, fmaxf(s[4 * i], s[4 * i + 1])); n1 = fmaxf(n1, fmaxf(s[4 * i + 2], s[4 * i + 3])); }
        n0 = fmaxf(n0, __shfl_xor_sync(~0u, n0, 1)); n0 = fmaxf(n0, __shfl_xor_sync(~0u, n0, 2));
        n1 = fmaxf(n1, __shfl_xor_sync(~0u, n1, 1)); n1 = fmaxf(n1, __shfl_xor_sync(~0u, n1, 2));
        const float c0 = ex2((m0 - n0) * QS), c1 = ex2((m1 - n1) * QS);
        m0 = n0; m1 = n1;
#pragma unroll
        for (int i = 0; i < 3; i++) { o[4 * i] *= c0; o[4 * i + 1] *= c0; o[4 * i + 2] *= c1; o[4 * i + 3] *= c1; }
        uint32_t p[16];
#pragma unroll
        for (int i = 0; i < 8; i++) {
            p[2 * i] = packbf(ex2((s[4 * i] - m0) * QS), ex2((s[4 * i + 1] - m0) * QS));
            p[2 * i + 1] = packbf(ex2((s[4 * i + 2] - m1) * QS), ex2((s[4 * i + 3] - m1) * QS));
        }
        WG_FENCE();
#pragma unroll
        for (int kk = 0; kk < 4; kk++) pv24(o, p[4 * kk], p[4 * kk + 1], p[4 * kk + 2], p[4 * kk + 3], vdesc0 + (uint64_t)(j * 64 + kk * 16));
        WG_COMMIT(); WG_WAIT(0);
    }
}

__device__ __forceinline__ void attn_store(const float (&o)[12], int head, int m64, int warp, int lane) {
    const int g = lane >> 2, t = lane & 3;
    const int row = m64 * 64 + warp * 16 + g;
    const float i0 = 1.f / o[8], i1 = 1.f / o[10];
    uint32_t* p0 = reinterpret_cast<uint32_t*>(g_o + (size_t)row * DM + head * 16 + t * 2);
    uint32_t* p1 = reinterpret_cast<uint32_t*>(g_o + (size_t)(row + 8) * DM + head * 16 + t * 2);
    p0[0] = packbf(o[0] * i0, o[1] * i0); p0[4] = packbf(o[4] * i0, o[5] * i0);
    p1[0] = packbf(o[2] * i1, o[3] * i1); p1[4] = packbf(o[6] * i1, o[7] * i1);
}

constexpr int FS_N = 4;
constexpr int FS_BYTES = 32768;
__device__ __forceinline__ void ldsm4t(uint32_t& r0, uint32_t& r1, uint32_t& r2, uint32_t& r3, uint32_t addr) {
    asm volatile("ldmatrix.sync.aligned.m8n8.x4.trans.shared.b16 {%0,%1,%2,%3}, [%4];" : "=r"(r0), "=r"(r1), "=r"(r2), "=r"(r3) : "r"(addr) : "memory");
}
__device__ __forceinline__ void mma16816(float (&d)[4], uint32_t a0, uint32_t a2, uint32_t b0, uint32_t b1) {
    asm volatile("mma.sync.aligned.m16n8k16.row.col.f32.bf16.bf16.f32 {%0,%1,%2,%3}, {%4,%5,%6,%5}, {%7,%8}, {%0,%1,%2,%3};"
                 : "+f"(d[0]), "+f"(d[1]), "+f"(d[2]), "+f"(d[3]) : "r"(a0), "r"(0u), "r"(a2), "r"(b0), "r"(b1));
}
__device__ void ffn_block(int c, uint8_t* smem, uint32_t sbase, const CUtensorMap* mapG, const CUtensorMap* mapU, const CUtensorMap* mapD) {
    const int tid = threadIdx.x, warp = tid >> 5, lane = tid & 31;
    uint32_t* sx = reinterpret_cast<uint32_t*>(smem + FS_N * FS_BYTES);
    __nv_bfloat16* sh = reinterpret_cast<__nv_bfloat16*>(sx + 512);
    const uint32_t bars = sbase + FS_N * FS_BYTES + 8192;
    float* tv = reinterpret_cast<float*>(smem + FS_N * FS_BYTES + 4096);
    int* ti = reinterpret_cast<int*>(tv + 32);
    int* ssel = ti + 32;
    auto issue = [&](int item) {
        const int slot = item % FS_N;
        const uint32_t dst = sbase + slot * FS_BYTES, bar = bars + 8 * slot;
        mbar_expect_tx(bar, item < 32 ? 28672 : 32768);
        if (item < 32) {
            tma3d(dst, mapG, bar, item * 16, c * 7);
            tma3d(dst + 14336, mapU, bar, item * 16, c * 7);
        } else {
            tma3d(dst, mapD, bar, c * 448 + (item - 32) * 32, 0);
        }
    };
    if (tid == 0) {
        for (int i = 0; i < FS_N; i++) mbar_init(bars + 8 * i, 1);
        fence_barrier_init();
        for (int i = 0; i < FS_N; i++) issue(i);
    }
    if (lane == 0) flag_wait(C_LN + warp, 128);
    __syncthreads();
    float b1 = -INFINITY, b2 = -INFINITY; int i1 = 0x7fffffff, i2 = 0x7fffffff;
    auto push = [&](float v, int i) {
        if (v > b1 || (v == b1 && i < i1)) { b2 = b1; i2 = i1; b1 = v; i1 = i; }
        else if (v > b2 || (v == b2 && i < i2)) { b2 = v; i2 = i; }
    };
    {
        const float4 rv = __ldcg(reinterpret_cast<const float4*>(g_r) + tid);
        push(rv.x, 4 * tid); push(rv.y, 4 * tid + 1); push(rv.z, 4 * tid + 2); push(rv.w, 4 * tid + 3);
    }
#pragma unroll
    for (int o = 16; o > 0; o >>= 1) {
        float v1 = __shfl_xor_sync(~0u, b1, o), v2 = __shfl_xor_sync(~0u, b2, o);
        int j1 = __shfl_xor_sync(~0u, i1, o), j2 = __shfl_xor_sync(~0u, i2, o);
        push(v1, j1); push(v2, j2);
    }
    if (lane == 0) { tv[2 * warp] = b1; ti[2 * warp] = i1; tv[2 * warp + 1] = b2; ti[2 * warp + 1] = i2; }
    __syncthreads();
    if (warp == 1) {
        b1 = tv[lane]; i1 = ti[lane]; b2 = -INFINITY; i2 = 0x7fffffff;
#pragma unroll
        for (int o = 16; o > 0; o >>= 1) {
            float v1 = __shfl_xor_sync(~0u, b1, o), v2 = __shfl_xor_sync(~0u, b2, o);
            int j1 = __shfl_xor_sync(~0u, i1, o), j2 = __shfl_xor_sync(~0u, i2, o);
            push(v1, j1); push(v2, j2);
        }
        if (lane == 0) {
            i1 = min(max(i1, 0), S_LEN - 1); i2 = min(max(i2, 0), S_LEN - 1);
            ssel[0] = i1; ssel[1] = i2;
            if (c == 0) {
                g_sel[0] = i1; g_sel[1] = i2;
                g_gate[0] = bfr(1.f / (1.f + __expf(-bfr(b1))));
                g_gate[1] = bfr(1.f / (1.f + __expf(-bfr(b2))));
            }
        }
    }
    __syncthreads();
    sx[tid] = __ldcg(reinterpret_cast<const uint32_t*>(g_xn + (size_t)ssel[tid >> 8] * DM + (tid & 255) * 2));
    __syncthreads();
    TL(1);
    const int g = lane >> 2, t = lane & 3;
    const int lrow = lane & 15, lsel = lane >> 4;
    {
        float ag[4][4], au[4][4];
#pragma unroll
        for (int j = 0; j < 4; j++) { ag[j][0] = ag[j][1] = ag[j][2] = ag[j][3] = 0.f; au[j][0] = au[j][1] = au[j][2] = au[j][3] = 0.f; }
#pragma unroll 1
        for (int it = 0; it < 32; it++) {
            const int slot = it % FS_N;
            const uint32_t a0 = g < 2 ? sx[g * 256 + it * 8 + t] : 0u, a2 = g < 2 ? sx[g * 256 + it * 8 + 4 + t] : 0u;
            mbar_wait(bars + 8 * slot, (it / FS_N) & 1);
            const uint32_t base = sbase + slot * FS_BYTES + lsel * 14336 + lrow * 128;
#pragma unroll
            for (int j = 0; j < 4; j++) {
                const int nt = warp + j * 16;
                if (nt < 56) {
                    uint32_t b0, b1, b2, b3;
                    ldsm4t(b0, b1, b2, b3, base + (nt >> 3) * 2048 + (((nt & 7) ^ (lrow & 7)) << 4));
                    mma16816(ag[j], a0, a2, b0, b1);
                    mma16816(au[j], a0, a2, b2, b3);
                }
            }
            __syncthreads();
            if (tid == 480) issue(it + FS_N);
        }
        if (g < 2) {
#pragma unroll
            for (int j = 0; j < 4; j++) {
                const int nt = warp + j * 16;
                if (nt < 56) {
#pragma unroll
                    for (int e = 0; e < 2; e++) {
                        const float gs = bfr(ag[j][e]), us = bfr(au[j][e]);
                        const float sg = bfr(gs / (1.f + __expf(-gs)));
                        sh[g * 448 + nt * 8 + t * 2 + e] = __float2bfloat16_rn(sg * us);
                    }
                }
            }
        }
        __syncthreads();
    }
    TL(2);
    {
        const uint32_t* shw = reinterpret_cast<const uint32_t*>(sh);
        float a[4][4];
#pragma unroll
        for (int j = 0; j < 4; j++) a[j][0] = a[j][1] = a[j][2] = a[j][3] = 0.f;
#pragma unroll 1
        for (int it = 32; it < 46; it++) {
            const int slot = it % FS_N;
            uint32_t af[4];
#pragma unroll
            for (int q = 0; q < 4; q++) af[q] = g < 2 ? shw[g * 224 + (it - 32) * 16 + q * 4 + t] : 0u;
            mbar_wait(bars + 8 * slot, (it / FS_N) & 1);
            const uint32_t base = sbase + slot * FS_BYTES + (warp >> 1) * 4096 + lane * 128;
#pragma unroll
            for (int j = 0; j < 4; j++) {
                const int u = (warp & 1) * 4 + j;
                uint32_t b0, b1, b2, b3;
                ldsm4t(b0, b1, b2, b3, base + ((u ^ (lane & 7)) << 4));
                mma16816(a[j], af[0], af[1], b0, b1);
                mma16816(a[j], af[2], af[3], b2, b3);
            }
            __syncthreads();
            if (tid == 480 && it + FS_N < 46) issue(it + FS_N);
        }
        if (g < 2) {
#pragma unroll
            for (int j = 0; j < 4; j++)
                *reinterpret_cast<float2*>(&g_ypart[c * 1024 + g * 512 + (warp * 4 + j) * 8 + t * 2]) = make_float2(a[j][0], a[j][1]);
        }
    }
    warp_arrive(C_FFN);
}

__device__ __forceinline__ void wgmma_n64(float (&d)[32], uint64_t da, uint64_t db, int scale_d) {
    asm volatile("{\n.reg .pred p;\nsetp.ne.b32 p, %34, 0;\n"
        "wgmma.mma_async.sync.aligned.m64n64k16.f32.bf16.bf16 "
        "{%0,%1,%2,%3,%4,%5,%6,%7,%8,%9,%10,%11,%12,%13,%14,%15,%16,%17,%18,%19,%20,%21,%22,%23,%24,%25,%26,%27,%28,%29,%30,%31}, "
        "%32, %33, p, 1, 1, 0, 1;\n}"
        : "+f"(d[0]), "+f"(d[1]), "+f"(d[2]), "+f"(d[3]), "+f"(d[4]), "+f"(d[5]), "+f"(d[6]), "+f"(d[7]),
          "+f"(d[8]), "+f"(d[9]), "+f"(d[10]), "+f"(d[11]), "+f"(d[12]), "+f"(d[13]), "+f"(d[14]), "+f"(d[15]),
          "+f"(d[16]), "+f"(d[17]), "+f"(d[18]), "+f"(d[19]), "+f"(d[20]), "+f"(d[21]), "+f"(d[22]), "+f"(d[23]),
          "+f"(d[24]), "+f"(d[25]), "+f"(d[26]), "+f"(d[27]), "+f"(d[28]), "+f"(d[29]), "+f"(d[30]), "+f"(d[31])
        : "l"(da), "l"(db), "r"(scale_d));
}

constexpr int G_ST = 4;
constexpr int G_STAGE = 16384 + 24576;
constexpr int SM_K = 65536, SM_V = 131072, SM_ONES = 196608, SM_MISC = 229376;
constexpr int FUSED_SMEM = SM_MISC + 2048;
constexpr int B_FULL = 0, B_EMPTY = 4, B_KV = 8, B_WO = 16, B_OA = 18, B_NUM = 22;

struct Maps { CUtensorMap xn, wqkv, o, wo, g, u, d; };

__global__ void __launch_bounds__(512, 1) fused_kernel(const __grid_constant__ Maps maps, const __nv_bfloat16* __restrict__ x,
                                                       const __nv_bfloat16* __restrict__ wr, __nv_bfloat16* __restrict__ out, float sc) {
    extern __shared__ __align__(1024) uint8_t smem[];
    const uint32_t sbase = smem_u32(smem);
    const int tid = threadIdx.x, warp = tid >> 5, lane = tid & 31;
    const uint32_t bars = sbase + SM_MISC;
    TL(0);
    if (sbase & 1023u) __trap();
    if (blockIdx.x < 4) {
        ffn_block(blockIdx.x, smem, sbase, &maps.g, &maps.u, &maps.d);
        TL(3);
    } else {
        const int idx = blockIdx.x - 4;
        const int wg = warp >> 2;
        {
            const int nb = idx & 7;
            if (tid == 480) {
                for (int s = 0; s < G_ST; s++) { mbar_init(bars + 8 * (B_FULL + s), 2); mbar_init(bars + 8 * (B_EMPTY + s), 2); }
                for (int c = B_KV; c < B_NUM; c++) mbar_init(bars + 8 * c, 1);
                fence_barrier_init();
                for (int c = 0; c < G_ST; c++) {
                    mbar_expect_tx(bars + 8 * (B_FULL + c), 24576);
                    tma3d(sbase + c * G_STAGE + 16384, &maps.wqkv, bars + 8 * (B_FULL + c), c * 64, nb * 3);
                }
                map_prefetch(&maps.xn);
            }
        }
        {
            const int row = idx * 16 + warp;
            const uint4* xr = reinterpret_cast<const uint4*>(x + (size_t)row * DM);
            const uint4 a = xr[lane], b = xr[32 + lane];
            const uint4* wp = reinterpret_cast<const uint4*>(wr);
            const uint4 wa = wp[lane], wb = wp[32 + lane];
            {
                uint4* ones = reinterpret_cast<uint4*>(smem + SM_ONES);
#pragma unroll
                for (int i = 0; i < 4; i++) ones[tid + i * 512] = make_uint4(0x3f803f80u, 0x3f803f80u, 0x3f803f80u, 0x3f803f80u);
                fence_proxy_async();
            }
            const uint32_t u[8] = {a.x, a.y, a.z, a.w, b.x, b.y, b.z, b.w};
            const uint32_t w[8] = {wa.x, wa.y, wa.z, wa.w, wb.x, wb.y, wb.z, wb.w};
            float f[16];
            float sum = 0.f;
#pragma unroll
            for (int i = 0; i < 8; i++) { f[2 * i] = bf_lo(u[i]); f[2 * i + 1] = bf_hi(u[i]); sum += f[2 * i] + f[2 * i + 1]; }
#pragma unroll
            for (int o = 16; o > 0; o >>= 1) sum += __shfl_xor_sync(~0u, sum, o);
            const float mean = sum * (1.f / DM);
            float sq = 0.f;
#pragma unroll
            for (int i = 0; i < 16; i++) { const float d = f[i] - mean; sq = fmaf(d, d, sq); }
#pragma unroll
            for (int o = 16; o > 0; o >>= 1) sq += __shfl_xor_sync(~0u, sq, o);
            const float mb_ = bfr(mean);
            const float vb = bfr(sq * (1.f / DM));
            const float rinv = 1.f / bfr(sqrtf(bfr(vb + 1e-5f)));
            uint32_t o[8];
            float r = 0.f;
#pragma unroll
            for (int i = 0; i < 8; i++) {
                const float d0 = bfr(f[2 * i] - mb_), d1 = bfr(f[2 * i + 1] - mb_);
                o[i] = packbf(d0 * rinv, d1 * rinv);
                r = fmaf(bf_lo(o[i]), bf_lo(w[i]), r);
                r = fmaf(bf_hi(o[i]), bf_hi(w[i]), r);
            }
            uint4* xo = reinterpret_cast<uint4*>(g_xn + (size_t)row * DM);
            xo[lane] = make_uint4(o[0], o[1], o[2], o[3]);
            xo[32 + lane] = make_uint4(o[4], o[5], o[6], o[7]);
#pragma unroll
            for (int of = 16; of > 0; of >>= 1) r += __shfl_xor_sync(~0u, r, of);
            if (lane == 0) g_r[row] = r;
            warp_arrive(C_LN + (idx >> 3));
        }
        __syncthreads();
        TL(1);
        {
            const int nb = idx & 7, mb = idx >> 3;
            if (tid == 480) {
                for (int c = G_ST; c < 8; c++) {
                    const int s = c - G_ST;
                    mbar_wait(bars + 8 * (B_EMPTY + s), 0);
                    mbar_expect_tx(bars + 8 * (B_FULL + s), 24576);
                    tma3d(sbase + s * G_STAGE + 16384, &maps.wqkv, bars + 8 * (B_FULL + s), c * 64, nb * 3);
                }
            } else if (tid == 448) {
                flag_wait(C_LN + mb, 128);
                fence_proxy_async_all();
                for (int c = 0; c < 8; c++) {
                    const int s = c & (G_ST - 1);
                    if (c >= G_ST) mbar_wait(bars + 8 * (B_EMPTY + s), 0);
                    mbar_expect_tx(bars + 8 * (B_FULL + s), 16384);
                    tma3d(sbase + s * G_STAGE, &maps.xn, bars + 8 * (B_FULL + s), mb * 128, c);
                }
            } else if (wg < 2) {
                float acc[96];
#pragma unroll
                for (int i = 0; i < 96; i++) acc[i] = 0.f;
#pragma unroll 1
                for (int c = 0; c < 8; c++) {
                    const int s = c & (G_ST - 1);
                    const uint32_t st = sbase + s * G_STAGE;
                    mbar_wait(bars + 8 * (B_FULL + s), c >> 2);
                    if (c == 0) TL(2);
                    const uint64_t da = mkdesc(st + wg * 8192, 16, 1024, 1);
                    const uint64_t db = mkdesc(st + 16384, 8192, 1024, 1);
                    WG_FENCE();
#pragma unroll
                    for (int k = 0; k < 4; k++) wgmma_n192(acc, da + k * 2, db + k * 128, (c | k) != 0);
                    WG_COMMIT();
                    if (c <= G_ST) {
                        WG_WAIT(1);
                        if (c >= 1 && (tid & 127) == 0) mbar_arrive(bars + 8 * (B_EMPTY + c - 1));
                    }
                }
                WG_WAIT(0);
                TL(3);
                const int g = lane >> 2, t = lane & 3;
                const int mt = mb * 8 + warp;
#pragma unroll
                for (int hh = 0; hh < 12; hh++) {
                    const int gh = nb * 12 + hh;
                    const float* a = &acc[hh * 8];
                    if (gh < 32) {
                        g_q[(gh * 128 + mt) * 32 + lane] = make_uint4(packbf(a[0], a[1]), packbf(a[2], a[3]), packbf(a[4], a[5]), packbf(a[6], a[7]));
                    } else {
                        uint32_t* dst = reinterpret_cast<uint32_t*>(gh < 64 ? g_k + (gh - 32) * 4096 : g_v + (gh - 64) * 4096);
                        const float ks = gh < 64 ? 5.421010862427522e-20f : 1.0f;
                        const int off = (mt * 16 + g) * 4 + t;
                        dst[off] = packbf(a[0] * ks, a[1] * ks);
                        dst[off + 32] = packbf(a[2] * ks, a[3] * ks);
                        dst[8192 + off] = packbf(a[4] * ks, a[5] * ks);
                        dst[8192 + off + 32] = packbf(a[6] * ks, a[7] * ks);
                    }
                }
                warp_arrive(C_QKV + nb);
            }
        }
        __syncthreads();
        TL(4);
        uint32_t badmask = 0;
        const int head = idx >> 2, quarter = idx & 3, w4 = warp & 3;
        {
            if (tid == 480) {
                flag_wait(C_QKV + (32 + head) / 12, 128);
                flag_wait(C_QKV + (64 + head) / 12, 128);
                fence_proxy_async_all();
                const uint8_t* kp = reinterpret_cast<const uint8_t*>(g_k + head * 4096);
                const uint8_t* vp = reinterpret_cast<const uint8_t*>(g_v + head * 4096);
                for (int c = 0; c < 8; c++) {
                    const uint32_t bar = bars + 8 * (B_KV + c);
                    mbar_expect_tx(bar, 16384);
                    bulk_g2s(sbase + SM_K + c * 4096, kp + c * 4096, 4096, bar);
                    bulk_g2s(sbase + SM_K + 32768 + c * 4096, kp + 32768 + c * 4096, 4096, bar);
                    bulk_g2s(sbase + SM_V + c * 4096, vp + c * 4096, 4096, bar);
                    bulk_g2s(sbase + SM_V + 32768 + c * 4096, vp + 32768 + c * 4096, 4096, bar);
                }
                mbar_expect_tx(bars + 8 * B_WO, 65536);
                tma3d(sbase, &maps.wo, bars + 8 * B_WO, 0, (idx & 3) * 2);
                map_prefetch(&maps.o);
            }
            if (lane == 0) flag_wait(C_QKV + head / 12, 128);
            __syncwarp();
            const uint64_t kdesc0 = mkdesc(sbase + SM_K, 32768, 128, 0);
            const uint64_t vdesc0 = mkdesc(sbase + SM_V, 128, 32768, 0);
#pragma unroll 1
            for (int mt = 0; mt < 2; mt++) {
                const int m64 = quarter * 8 + mt * 4 + wg;
                uint32_t q[4];
                { const uint4 qq = __ldcg(&g_q[(head * 128 + m64 * 4 + w4) * 32 + lane]); q[0] = qq.x; q[1] = qq.y; q[2] = qq.z; q[3] = qq.w; }
                float s[32], s2[32], o[12];
#pragma unroll
                for (int i = 0; i < 12; i++) o[i] = 0.f;
                mbar_wait(bars + 8 * B_KV, 0);
                if (mt == 0) TL(5);
                WG_FENCE();
                qk64(s, q, kdesc0);
                WG_COMMIT(); WG_WAIT(0);
                float mx0 = -INFINITY, mx1 = -INFINITY;
#pragma unroll
                for (int i = 0; i < 8; i++) { mx0 = fmaxf(mx0, fmaxf(s[4 * i], s[4 * i + 1])); mx1 = fmaxf(mx1, fmaxf(s[4 * i + 2], s[4 * i + 3])); }
                mx0 = fmaxf(mx0, __shfl_xor_sync(~0u, mx0, 1)); mx0 = fmaxf(mx0, __shfl_xor_sync(~0u, mx0, 2));
                mx1 = fmaxf(mx1, __shfl_xor_sync(~0u, mx1, 1)); mx1 = fmaxf(mx1, __shfl_xor_sync(~0u, mx1, 2));
                float cm0 = -(ceilf(mx0 * QS) + SHIFT), cm1 = -(ceilf(mx1 * QS) + SHIFT);
                float cp0 = (cm0 + 127.f) * sc, cp1 = (cm1 + 127.f) * sc;
                asm volatile("" : "+f"(cm0), "+f"(cm1), "+f"(cp0), "+f"(cp1));
                uint64_t kd = kdesc0, vd = vdesc0;
                auto step = [&](float (&sc_)[32], float (&sn)[32]) {
                    kd += 64;
                    WG_FENCE();
                    qk64(sn, q, kd);
                    WG_COMMIT();
#pragma unroll
                    for (int kk = 0; kk < 4; kk++) {
                        const int i0 = kk * 2, i1 = kk * 2 + 1;
                        const uint32_t p0 = packbf(ex2(fmaf(sc_[4 * i0], QS, cm0)), ex2(fmaf(sc_[4 * i0 + 1], QS, cm0)));
                        const uint32_t p1 = packbf(ex2(fmaf(sc_[4 * i0 + 2], QS, cm1)), ex2(fmaf(sc_[4 * i0 + 3], QS, cm1)));
                        const uint32_t p2 = polyexp(fmaf(sc_[4 * i1], scq, cp0), fmaf(sc_[4 * i1 + 1], scq, cp0));
                        const uint32_t p3 = polyexp(fmaf(sc_[4 * i1 + 2], scq, cp1), fmaf(sc_[4 * i1 + 3], scq, cp1));
                        WG_FENCE();
                        pv24(o, p0, p1, p2, p3, vd);
                        vd += 16;
                    }
                    WG_COMMIT();
                    WG_WAIT(1);
                };
#pragma unroll 1
                for (int c = 0; c < 16; c++) {
                    if (mt == 0 && (c & 1) == 0 && c < 14) mbar_wait(bars + 8 * B_KV + 4 * c + 8, 0);
                    step(s, s2); step(s2, s);
                }
                WG_WAIT(0);
                bool bad = !(o[8] > 0.f) || !(o[10] > 0.f);
#pragma unroll
                for (int i = 0; i < 12; i++) bad = bad || !(fabsf(o[i]) <= 3.0e38f);
                uint32_t anybad;
                asm volatile("{\n.reg .pred p, q;\nsetp.ne.u32 p, %1, 0;\nbarrier.cta.red.or.pred q, %2, 128, p;\nselp.u32 %0, 1, 0, q;\n}"
                             : "=r"(anybad) : "r"((uint32_t)bad), "r"(wg + 1) : "memory");
                badmask |= anybad << mt;
                if (!anybad) {
                    attn_store(o, head, m64, w4, lane);
                    warp_arrive(C_O + m64);
                }
            }
        }
#pragma unroll 1
        for (int mt = 0; mt < 2; mt++) {
            if (!((badmask >> mt) & 1)) continue;
            const int m64 = quarter * 8 + mt * 4 + wg;
            uint32_t q[4];
            { const uint4 qq = __ldcg(&g_q[(head * 128 + m64 * 4 + w4) * 32 + lane]); q[0] = qq.x; q[1] = qq.y; q[2] = qq.z; q[3] = qq.w; }
            float o[12];
            attn_safe(o, q, mkdesc(sbase + SM_K, 32768, 128, 0), mkdesc(sbase + SM_V, 128, 32768, 0));
            attn_store(o, head, m64, w4, lane);
            warp_arrive(C_O + m64);
        }
        __syncthreads();
        TL(6);
        {
            const int nb = idx & 3, mb = idx >> 2;
            float* supd = reinterpret_cast<float*>(smem + SM_MISC + 512);
            if (tid == 480) {
                mbar_expect_tx(bars + 8 * (B_WO + 1), 65536);
                tma3d(sbase + 65536, &maps.wo, bars + 8 * (B_WO + 1), 256, nb * 2);
                flag_wait(C_O + mb, 128);
                fence_proxy_async_all();
                for (int c = 0; c < 4; c++) {
                    mbar_expect_tx(bars + 8 * (B_OA + c), 16384);
                    tma3d(sbase + SM_V + c * 16384, &maps.o, bars + 8 * (B_OA + c), mb * 64, c * 2);
                }
            }
            if (wg < 2) {
                const int g = lane >> 2, t = lane & 3;
                const int row0 = mb * 64 + w4 * 16 + g;
                const int col0 = nb * 128 + wg * 64 + t * 2;
                if (lane == 0) { flag_wait(C_LN + (mb >> 1), 128); flag_wait(C_FFN, 64); }
                __syncwarp();
                uint32_t xv[16], nv[16];
#pragma unroll
                for (int i = 0; i < 8; i++) {
                    xv[2 * i] = *reinterpret_cast<const uint32_t*>(x + (size_t)row0 * DM + col0 + i * 8);
                    xv[2 * i + 1] = *reinterpret_cast<const uint32_t*>(x + (size_t)(row0 + 8) * DM + col0 + i * 8);
                    nv[2 * i] = __ldcg(reinterpret_cast<const uint32_t*>(g_xn + (size_t)row0 * DM + col0 + i * 8));
                    nv[2 * i + 1] = __ldcg(reinterpret_cast<const uint32_t*>(g_xn + (size_t)(row0 + 8) * DM + col0 + i * 8));
                }
                const int sel0 = __ldcg(&g_sel[0]), sel1 = __ldcg(&g_sel[1]);
                {
                    const int which = tid >> 7, col = nb * 128 + (tid & 127);
                    const float y = __ldcg(&g_ypart[which * 512 + col]) + __ldcg(&g_ypart[1024 + which * 512 + col]) +
                                    __ldcg(&g_ypart[2048 + which * 512 + col]) + __ldcg(&g_ypart[3072 + which * 512 + col]);
                    supd[tid] = bfr(bfr(y) * __ldcg(&g_gate[which]));
                }
                asm volatile("bar.sync 5, 256;" ::: "memory");
                float acc[32];
#pragma unroll
                for (int i = 0; i < 32; i++) acc[i] = 0.f;
#pragma unroll 1
                for (int c = 0; c < 8; c++) {
                    if ((c & 3) == 0) mbar_wait(bars + 8 * (B_WO + (c >> 2)), 0);
                    if ((c & 1) == 0) mbar_wait(bars + 8 * (B_OA + (c >> 1)), 0);
                    if (c == 0) TL(7);
                    const uint64_t da = mkdesc(sbase + SM_V + c * 8192, 16, 1024, 1);
                    const uint64_t db = mkdesc(sbase + (c >> 2) * 65536 + wg * 32768 + (c & 3) * 8192, 8192, 1024, 1);
                    WG_FENCE();
#pragma unroll
                    for (int k = 0; k < 4; k++) wgmma_n64(acc, da + k * 2, db + k * 128, (c | k) != 0);
                    WG_COMMIT();
                }
                WG_WAIT(0);
                TL(8);
#pragma unroll
                for (int h = 0; h < 2; h++) {
                    const int row = row0 + h * 8;
                    const int which = row == sel0 ? 0 : (row == sel1 ? 1 : -1);
#pragma unroll
                    for (int i = 0; i < 8; i++) {
                        const int col = col0 + i * 8;
                        float b0 = bf_lo(nv[2 * i + h]), b1 = bf_hi(nv[2 * i + h]);
                        if (which >= 0) {
                            b0 = bfr(b0 + supd[which * 128 + col - nb * 128]); b1 = bfr(b1 + supd[which * 128 + col + 1 - nb * 128]);
                        }
                        const float t0 = bfr(bf_lo(xv[2 * i + h]) + bfr(acc[4 * i + 2 * h]));
                        const float t1 = bfr(bf_hi(xv[2 * i + h]) + bfr(acc[4 * i + 2 * h + 1]));
                        *reinterpret_cast<uint32_t*>(out + (size_t)row * DM + col) = packbf(t0 + b0, t1 + b1);
                    }
                }
            }
        }
        TL(9);
    }
    __syncthreads();
    if (tid == 0) {
        __threadfence();
        const unsigned tk = atomicAdd(&g_cnt[C_EXIT * 32], 1u);
        if (tk == gridDim.x - 1) {
            for (int i = 0; i < C_NUM; i++) g_cnt[i * 32] = 0u;
            __threadfence();
        }
    }
}

typedef CUresult (*EncodeFn)(CUtensorMap*, CUtensorMapDataType, cuuint32_t, void*, const cuuint64_t*, const cuuint64_t*,
                             const cuuint32_t*, const cuuint32_t*, CUtensorMapInterleave, CUtensorMapSwizzle,
                             CUtensorMapL2promotion, CUtensorMapFloatOOBfill);

void make_map(EncodeFn fn, CUtensorMap* m, const void* ptr, uint64_t cols, uint64_t rows, uint32_t box_rows, uint32_t box_chunks) {
    cuuint64_t dims[3] = {64, rows, cols / 64};
    cuuint64_t strides[2] = {cols * 2, 128};
    cuuint32_t box[3] = {64, box_rows, box_chunks};
    cuuint32_t es[3] = {1, 1, 1};
    fn(m, CU_TENSOR_MAP_DATA_TYPE_BFLOAT16, 3, const_cast<void*>(ptr), dims, strides, box, es, CU_TENSOR_MAP_INTERLEAVE_NONE,
       CU_TENSOR_MAP_SWIZZLE_128B, CU_TENSOR_MAP_L2_PROMOTION_L2_256B, CU_TENSOR_MAP_FLOAT_OOB_FILL_NONE);
}

}

extern "C" void kernel_launch(void* const* d_in, const int* in_sizes, int n_in, void* d_out, int out_size) {
    const __nv_bfloat16* x = (const __nv_bfloat16*)d_in[0];
    const __nv_bfloat16* wqkv = (const __nv_bfloat16*)d_in[1];
    const __nv_bfloat16* wo = (const __nv_bfloat16*)d_in[2];
    const __nv_bfloat16* wr = (const __nv_bfloat16*)d_in[4];
    const __nv_bfloat16* wgate = (const __nv_bfloat16*)d_in[5];
    const __nv_bfloat16* wup = (const __nv_bfloat16*)d_in[6];
    const __nv_bfloat16* wdown = (const __nv_bfloat16*)d_in[7];
    __nv_bfloat16* out = (__nv_bfloat16*)d_out;

    static EncodeFn enc = nullptr;
    static void* p_xn = nullptr; static void* p_o = nullptr;
    if (!enc) {
        void* fn = nullptr; cudaDriverEntryPointQueryResult qr;
        cudaGetDriverEntryPoint("cuTensorMapEncodeTiled", &fn, cudaEnableDefault, &qr);
        enc = (EncodeFn)fn;
        cudaGetSymbolAddress(&p_xn, g_xn);
        cudaGetSymbolAddress(&p_o, g_o);
        cudaFuncSetAttribute(fused_kernel, cudaFuncAttributeMaxDynamicSharedMemorySize, FUSED_SMEM);
    }
    Maps maps;
    make_map(enc, &maps.g, wgate, FF, DM, 16, 7);
    make_map(enc, &maps.u, wup, FF, DM, 16, 7);
    make_map(enc, &maps.d, wdown, DM, FF, 32, 8);
    make_map(enc, &maps.xn, p_xn, DM, S_LEN, 128, 1);
    make_map(enc, &maps.wqkv, wqkv, 3 * DM, DM, 64, 3);
    make_map(enc, &maps.o, p_o, DM, S_LEN, 64, 2);
    make_map(enc, &maps.wo, wo, DM, DM, 256, 2);

    union { uint32_t u; float f; } scu; scu.u = 128u;

    cudaLaunchConfig_t cfg = {};
    cfg.gridDim = dim3(132); cfg.blockDim = dim3(512); cfg.dynamicSmemBytes = FUSED_SMEM; cfg.stream = cudaStreamPerThread;
    cudaLaunchAttribute at[1];
    at[0].id = cudaLaunchAttributeCooperative;
    at[0].val.cooperative = 1;
    cfg.attrs = at; cfg.numAttrs = 1;
    cudaLaunchKernelEx(&cfg, fused_kernel, maps, x, wr, out, scu.f);
}
```

```cpp
#include <cuda_runtime.h>
#include <cuda_bf16.h>
#include <cuda.h>
#include <stdint.h>
#include <type_traits>

namespace {

constexpr int S_LEN = 2048;
constexpr int DM = 512;
constexpr int NH = 32;
constexpr int FF = 1792;

__device__ __align__(1024) __nv_bfloat16 g_xn[S_LEN * DM];
__device__ __align__(16) float g_r[S_LEN];
__device__ __align__(1024) uint4 g_q[NH * 128 * 32];
__device__ __align__(1024) uint4 g_k[NH * 4096];
__device__ __align__(1024) uint4 g_v[NH * 4096];
__device__ __align__(1024) __nv_bfloat16 g_o[S_LEN * DM];
__device__ __align__(16) float g_ypart[4 * 2 * DM];
__device__ int g_sel[2];
__device__ float g_gate[2];
constexpr int C_LN = 0, C_QKV = 16, C_O = 24, C_FFN = 56, C_EXIT = 57, C_NUM = 58;
__device__ unsigned g_cnt[C_NUM * 32];

#define TL(slot) do {} while (0)

__device__ __forceinline__ uint32_t smem_u32(const void* p) { return (uint32_t)__cvta_generic_to_shared(p); }
__device__ __forceinline__ void warp_arrive(int idx) {
    __syncwarp();
    if ((threadIdx.x & 31) == 0)
        asm volatile("red.release.gpu.global.add.u32 [%0], 1;" :: "l"(g_cnt + idx * 32) : "memory");
}
__device__ __forceinline__ void nbar_arrive(int id, int cnt) { asm volatile("bar.arrive %0, %1;" :: "r"(id), "r"(cnt) : "memory"); }
__device__ __forceinline__ void nbar_sync(int id, int cnt) { asm volatile("bar.sync %0, %1;" :: "r"(id), "r"(cnt) : "memory"); }
__device__ __forceinline__ void flag_wait(int idx, unsigned target) {
    unsigned v, n = 0;
    do {
        asm volatile("ld.acquire.gpu.global.u32 %0, [%1];" : "=r"(v) : "l"(g_cnt + idx * 32) : "memory");
        if (v >= target) return;
    } while (++n < (1u << 24));
    __trap();
}
__device__ __forceinline__ void fence_proxy_async_all() { asm volatile("fence.proxy.async;" ::: "memory"); }
__device__ __forceinline__ void mbar_init(uint32_t bar, uint32_t cnt) {
    asm volatile("mbarrier.init.shared::cta.b64 [%0], %1;" :: "r"(bar), "r"(cnt) : "memory");
}
__device__ __forceinline__ void mbar_expect_tx(uint32_t bar, uint32_t bytes) {
    asm volatile("mbarrier.arrive.expect_tx.shared::cta.b64 _, [%0], %1;" :: "r"(bar), "r"(bytes) : "memory");
}
__device__ __forceinline__ void mbar_arrive(uint32_t bar) {
    asm volatile("mbarrier.arrive.shared::cta.b64 _, [%0];" :: "r"(bar) : "memory");
}
__device__ __forceinline__ void mbar_wait(uint32_t bar, uint32_t parity) {
    asm volatile("{\n.reg .pred p;\n.reg .u32 n;\nmov.u32 n, 0;\n"
                 "WAIT_%=:\n"
                 "mbarrier.try_wait.parity.shared::cta.b64 p, [%0], %1;\n"
                 "@p bra DONE_%=;\n"
                 "add.u32 n, n, 1;\n"
                 "setp.lt.u32 p, n, 4000000;\n"
                 "@p bra WAIT_%=;\n"
                 "trap;\n"
                 "DONE_%=:\n}"
                 :: "r"(bar), "r"(parity) : "memory");
}
__device__ __forceinline__ void fence_barrier_init() { asm volatile("fence.mbarrier_init.release.cluster;" ::: "memory"); }
__device__ __forceinline__ void fence_proxy_async() { asm volatile("fence.proxy.async.shared::cta;" ::: "memory"); }
__device__ __forceinline__ void tma3d(uint32_t dst, const CUtensorMap* map, uint32_t bar, int row, int chunk) {
    asm volatile("cp.async.bulk.tensor.3d.shared::cluster.global.mbarrier::complete_tx::bytes [%0], [%1, {%3, %4, %5}], [%2];"
                 :: "r"(dst), "l"((uint64_t)map), "r"(bar), "r"(0), "r"(row), "r"(chunk) : "memory");
}
__device__ __forceinline__ void bulk_g2s(uint32_t dst, const void* src, uint32_t bytes, uint32_t bar) {
    asm volatile("cp.async.bulk.shared::cluster.global.mbarrier::complete_tx::bytes [%0], [%1], %2, [%3];"
                 :: "r"(dst), "l"((uint64_t)src), "r"(bytes), "r"(bar) : "memory");
}
__device__ __forceinline__ void l2_prefetch(const void* src, uint32_t bytes) {
    asm volatile("cp.async.bulk.prefetch.L2.global [%0], %1;" :: "l"((uint64_t)src), "r"(bytes) : "memory");
}
__device__ __forceinline__ void map_prefetch(const CUtensorMap* m) {
    asm volatile("prefetch.tensormap [%0];" :: "l"((uint64_t)m) : "memory");
}
__device__ __forceinline__ uint64_t mkdesc(uint32_t addr, uint32_t lbo, uint32_t sbo, uint32_t swz) {
    return (uint64_t)((addr & 0x3FFFF) >> 4) | ((uint64_t)(lbo >> 4) << 16) | ((uint64_t)(sbo >> 4) << 32) | ((uint64_t)swz << 62);
}
#define WG_FENCE() asm volatile("wgmma.fence.sync.aligned;" ::: "memory")
#define WG_COMMIT() asm volatile("wgmma.commit_group.sync.aligned;" ::: "memory")
#define WG_WAIT(n) asm volatile("wgmma.wait_group.sync.aligned %0;" :: "n"(n) : "memory")

__device__ __forceinline__ float ex2(float x) { float y; asm("ex2.approx.ftz.f32 %0, %1;" : "=f"(y) : "f"(x)); return y; }
__device__ __forceinline__ uint32_t packbf(float lo, float hi) {
    uint32_t r; asm("cvt.rn.bf16x2.f32 %0, %1, %2;" : "=r"(r) : "f"(hi), "f"(lo)); return r;
}
__device__ __forceinline__ float bf_lo(uint32_t v) { return __uint_as_float(v << 16); }
__device__ __forceinline__ float bf_hi(uint32_t v) { return __uint_as_float(v & 0xffff0000u); }
__device__ __forceinline__ float bfr(float x) { return __bfloat162float(__float2bfloat16_rn(x)); }

__device__ __forceinline__ void wgmma_n192(float (&d)[96], uint64_t da, uint64_t db, int scale_d) {
    asm volatile("{\n.reg .pred p;\nsetp.ne.b32 p, %98, 0;\n"
        "wgmma.mma_async.sync.aligned.m64n192k16.f32.bf16.bf16 "
        "{%0,%1,%2,%3,%4,%5,%6,%7,%8,%9,%10,%11,%12,%13,%14,%15,%16,%17,%18,%19,%20,%21,%22,%23,"
        "%24,%25,%26,%27,%28,%29,%30,%31,%32,%33,%34,%35,%36,%37,%38,%39,%40,%41,%42,%43,%44,%45,%46,%47,"
        "%48,%49,%50,%51,%52,%53,%54,%55,%56,%57,%58,%59,%60,%61,%62,%63,%64,%65,%66,%67,%68,%69,%70,%71,"
        "%72,%73,%74,%75,%76,%77,%78,%79,%80,%81,%82,%83,%84,%85,%86,%87,%88,%89,%90,%91,%92,%93,%94,%95}, "
        "%96, %97, p, 1, 1, 0, 1;\n}"
        : "+f"(d[0]), "+f"(d[1]), "+f"(d[2]), "+f"(d[3]), "+f"(d[4]), "+f"(d[5]), "+f"(d[6]), "+f"(d[7]),
          "+f"(d[8]), "+f"(d[9]), "+f"(d[10]), "+f"(d[11]), "+f"(d[12]), "+f"(d[13]), "+f"(d[14]), "+f"(d[15]),
          "+f"(d[16]), "+f"(d[17]), "+f"(d[18]), "+f"(d[19]), "+f"(d[20]), "+f"(d[21]), "+f"(d[22]), "+f"(d[23]),
          "+f"(d[24]), "+f"(d[25]), "+f"(d[26]), "+f"(d[27]), "+f"(d[28]), "+f"(d[29]), "+f"(d[30]), "+f"(d[31]),
          "+f"(d[32]), "+f"(d[33]), "+f"(d[34]), "+f"(d[35]), "+f"(d[36]), "+f"(d[37]), "+f"(d[38]), "+f"(d[39]),
          "+f"(d[40]), "+f"(d[41]), "+f"(d[42]), "+f"(d[43]), "+f"(d[44]), "+f"(d[45]), "+f"(d[46]), "+f"(d[47]),
          "+f"(d[48]), "+f"(d[49]), "+f"(d[50]), "+f"(d[51]), "+f"(d[52]), "+f"(d[53]), "+f"(d[54]), "+f"(d[55]),
          "+f"(d[56]), "+f"(d[57]), "+f"(d[58]), "+f"(d[59]), "+f"(d[60]), "+f"(d[61]), "+f"(d[62]), "+f"(d[63]),
          "+f"(d[64]), "+f"(d[65]), "+f"(d[66]), "+f"(d[67]), "+f"(d[68]), "+f"(d[69]), "+f"(d[70]), "+f"(d[71]),
          "+f"(d[72]), "+f"(d[73]), "+f"(d[74]), "+f"(d[75]), "+f"(d[76]), "+f"(d[77]), "+f"(d[78]), "+f"(d[79]),
          "+f"(d[80]), "+f"(d[81]), "+f"(d[82]), "+f"(d[83]), "+f"(d[84]), "+f"(d[85]), "+f"(d[86]), "+f"(d[87]),
          "+f"(d[88]), "+f"(d[89]), "+f"(d[90]), "+f"(d[91]), "+f"(d[92]), "+f"(d[93]), "+f"(d[94]), "+f"(d[95])
        : "l"(da), "l"(db), "r"(scale_d));
}

constexpr float SHIFT = 90.0f;
constexpr float QS = 0.25f * 1.4426950408889634f * 18446744073709551616.0f;
constexpr float scq = 0.25f * 1.4426950408889634f * 3.3087224502121107e-24f;

__device__ __forceinline__ uint32_t polyexp(float lo, float hi) {
    uint32_t w, g, q, h;
    asm("cvt.pack.sat.s16.s32 %0, %1, %2;" : "=r"(w) : "r"(__float_as_uint(hi)), "r"(__float_as_uint(lo)));
    g = w & 0x007F007Fu;
    asm("fma.rn.f16x2 %0, %1, %2, %3;" : "=r"(q) : "r"(g), "r"(0xf940f940u), "r"(0x35513551u));
    asm("mul.rn.f16x2 %0, %1, %2;" : "=r"(h) : "r"(q), "r"(g));
    return w - h;
}
__device__ __forceinline__ void qk64(float (&s)[32], const uint32_t (&q)[4], uint64_t db) {
    asm volatile("wgmma.mma_async.sync.aligned.m64n64k16.f32.bf16.bf16 "
        "{%0,%1,%2,%3,%4,%5,%6,%7,%8,%9,%10,%11,%12,%13,%14,%15,%16,%17,%18,%19,%20,%21,%22,%23,%24,%25,%26,%27,%28,%29,%30,%31}, "
        "{%32,%33,%34,%35}, %36, 0, 1, 1, 0;"
        : "=f"(s[0]), "=f"(s[1]), "=f"(s[2]), "=f"(s[3]), "=f"(s[4]), "=f"(s[5]), "=f"(s[6]), "=f"(s[7]),
          "=f"(s[8]), "=f"(s[9]), "=f"(s[10]), "=f"(s[11]), "=f"(s[12]), "=f"(s[13]), "=f"(s[14]), "=f"(s[15]),
          "=f"(s[16]), "=f"(s[17]), "=f"(s[18]), "=f"(s[19]), "=f"(s[20]), "=f"(s[21]), "=f"(s[22]), "=f"(s[23]),
          "=f"(s[24]), "=f"(s[25]), "=f"(s[26]), "=f"(s[27]), "=f"(s[28]), "=f"(s[29]), "=f"(s[30]), "=f"(s[31])
        : "r"(q[0]), "r"(q[1]), "r"(q[2]), "r"(q[3]), "l"(db));
}
__device__ __forceinline__ void pv24(float (&o)[12], uint32_t a0, uint32_t a1, uint32_t a2, uint32_t a3, uint64_t db) {
    asm volatile("wgmma.mma_async.sync.aligned.m64n24k16.f32.bf16.bf16 "
        "{%0,%1,%2,%3,%4,%5,%6,%7,%8,%9,%10,%11}, {%12,%13,%14,%15}, %16, 1, 1, 1, 1;"
        : "+f"(o[0]), "+f"(o[1]), "+f"(o[2]), "+f"(o[3]), "+f"(o[4]), "+f"(o[5]), "+f"(o[6]), "+f"(o[7]),
          "+f"(o[8]), "+f"(o[9]), "+f"(o[10]), "+f"(o[11])
        : "r"(a0), "r"(a1), "r"(a2), "r"(a3), "l"(db));
}

__device__ __forceinline__ void attn_safe(float (&o)[12], const uint32_t (&q)[4], uint64_t kdesc0, uint64_t vdesc0) {
    float s[32];
    float m0 = -INFINITY, m1 = -INFINITY;
#pragma unroll
    for (int i = 0; i < 12; i++) o[i] = 0.f;
#pragma unroll 1
    for (int j = 0; j < 32; j++) {
        WG_FENCE();
        qk64(s, q, kdesc0 + (uint64_t)(j * 64));
        WG_COMMIT(); WG_WAIT(0);
        float n0 = m0, n1 = m1;
#pragma unroll
        for (int i = 0; i < 8; i++) { n0 = fmaxf(n0, fmaxf(s[4 * i], s[4 * i + 1])); n1 = fmaxf(n1, fmaxf(s[4 * i + 2], s[4 * i + 3])); }
        n0 = fmaxf(n0, __shfl_xor_sync(~0u, n0, 1)); n0 = fmaxf(n0, __shfl_xor_sync(~0u, n0, 2));
        n1 = fmaxf(n1, __shfl_xor_sync(~0u, n1, 1)); n1 = fmaxf(n1, __shfl_xor_sync(~0u, n1, 2));
        const float c0 = ex2((m0 - n0) * QS), c1 = ex2((m1 - n1) * QS);
        m0 = n0; m1 = n1;
#pragma unroll
        for (int i = 0; i < 3; i++) { o[4 * i] *= c0; o[4 * i + 1] *= c0; o[4 * i + 2] *= c1; o[4 * i + 3] *= c1; }
        uint32_t p[16];
#pragma unroll
        for (int i = 0; i < 8; i++) {
            p[2 * i] = packbf(ex2((s[4 * i] - m0) * QS), ex2((s[4 * i + 1] - m0) * QS));
            p[2 * i + 1] = packbf(ex2((s[4 * i + 2] - m1) * QS), ex2((s[4 * i + 3] - m1) * QS));
        }
        WG_FENCE();
#pragma unroll
        for (int kk = 0; kk < 4; kk++) pv24(o, p[4 * kk], p[4 * kk + 1], p[4 * kk + 2], p[4 * kk + 3], vdesc0 + (uint64_t)(j * 64 + kk * 16));
        WG_COMMIT(); WG_WAIT(0);
    }
}

__device__ __forceinline__ void attn_store(const float (&o)[12], int head, int m64, int warp, int lane) {
    const int g = lane >> 2, t = lane & 3;
    const int row = m64 * 64 + warp * 16 + g;
    const float i0 = 1.f / o[8], i1 = 1.f / o[10];
    uint32_t* p0 = reinterpret_cast<uint32_t*>(g_o + (size_t)row * DM + head * 16 + t * 2);
    uint32_t* p1 = reinterpret_cast<uint32_t*>(g_o + (size_t)(row + 8) * DM + head * 16 + t * 2);
    p0[0] = packbf(o[0] * i0, o[1] * i0); p0[4] = packbf(o[4] * i0, o[5] * i0);
    p1[0] = packbf(o[2] * i1, o[3] * i1); p1[4] = packbf(o[6] * i1, o[7] * i1);
}

constexpr int FS_N = 4;
constexpr int FS_BYTES = 32768;
__device__ __forceinline__ void ldsm4t(uint32_t& r0, uint32_t& r1, uint32_t& r2, uint32_t& r3, uint32_t addr) {
    asm volatile("ldmatrix.sync.aligned.m8n8.x4.trans.shared.b16 {%0,%1,%2,%3}, [%4];" : "=r"(r0), "=r"(r1), "=r"(r2), "=r"(r3) : "r"(addr) : "memory");
}
__device__ __forceinline__ void mma16816(float (&d)[4], uint32_t a0, uint32_t a2, uint32_t b0, uint32_t b1) {
    asm volatile("mma.sync.aligned.m16n8k16.row.col.f32.bf16.bf16.f32 {%0,%1,%2,%3}, {%4,%5,%6,%5}, {%7,%8}, {%0,%1,%2,%3};"
                 : "+f"(d[0]), "+f"(d[1]), "+f"(d[2]), "+f"(d[3]) : "r"(a0), "r"(0u), "r"(a2), "r"(b0), "r"(b1));
}
__device__ void ffn_block(int c, uint8_t* smem, uint32_t sbase, const CUtensorMap* mapG, const CUtensorMap* mapU, const CUtensorMap* mapD) {
    const int tid = threadIdx.x, warp = tid >> 5, lane = tid & 31;
    uint32_t* sx = reinterpret_cast<uint32_t*>(smem + FS_N * FS_BYTES);
    __nv_bfloat16* sh = reinterpret_cast<__nv_bfloat16*>(sx + 512);
    const uint32_t bars = sbase + FS_N * FS_BYTES + 8192;
    float* tv = reinterpret_cast<float*>(smem + FS_N * FS_BYTES + 4096);
    int* ti = reinterpret_cast<int*>(tv + 32);
    int* ssel = ti + 32;
    auto issue = [&](int item) {
        const int slot = item % FS_N;
        const uint32_t dst = sbase + slot * FS_BYTES, bar = bars + 8 * slot;
        mbar_expect_tx(bar, item < 32 ? 28672 : 32768);
        if (item < 32) {
            tma3d(dst, mapG, bar, item * 16, c * 7);
            tma3d(dst + 14336, mapU, bar, item * 16, c * 7);
        } else {
            tma3d(dst, mapD, bar, c * 448 + (item - 32) * 32, 0);
        }
    };
    if (tid == 0) {
        for (int i = 0; i < FS_N; i++) mbar_init(bars + 8 * i, 1);
        fence_barrier_init();
        for (int i = 0; i < FS_N; i++) issue(i);
    }
    if (lane == 0) flag_wait(C_LN + warp, 128);
    __syncthreads();
    float b1 = -INFINITY, b2 = -INFINITY; int i1 = 0x7fffffff, i2 = 0x7fffffff;
    auto push = [&](float v, int i) {
        if (v > b1 || (v == b1 && i < i1)) { b2 = b1; i2 = i1; b1 = v; i1 = i; }
        else if (v > b2 || (v == b2 && i < i2)) { b2 = v; i2 = i; }
    };
    {
        const float4 rv = __ldcg(reinterpret_cast<const float4*>(g_r) + tid);
        push(rv.x, 4 * tid); push(rv.y, 4 * tid + 1); push(rv.z, 4 * tid + 2); push(rv.w, 4 * tid + 3);
    }
#pragma unroll
    for (int o = 16; o > 0; o >>= 1) {
        float v1 = __shfl_xor_sync(~0u, b1, o), v2 = __shfl_xor_sync(~0u, b2, o);
        int j1 = __shfl_xor_sync(~0u, i1, o), j2 = __shfl_xor_sync(~0u, i2, o);
        push(v1, j1); push(v2, j2);
    }
    if (lane == 0) { tv[2 * warp] = b1; ti[2 * warp] = i1; tv[2 * warp + 1] = b2; ti[2 * warp + 1] = i2; }
    __syncthreads();
    if (warp == 1) {
        b1 = tv[lane]; i1 = ti[lane]; b2 = -INFINITY; i2 = 0x7fffffff;
#pragma unroll
        for (int o = 16; o > 0; o >>= 1) {
            float v1 = __shfl_xor_sync(~0u, b1, o), v2 = __shfl_xor_sync(~0u, b2, o);
            int j1 = __shfl_xor_sync(~0u, i1, o), j2 = __shfl_xor_sync(~0u, i2, o);
            push(v1, j1); push(v2, j2);
        }
        if (lane == 0) {
            i1 = min(max(i1, 0), S_LEN - 1); i2 = min(max(i2, 0), S_LEN - 1);
            ssel[0] = i1; ssel[1] = i2;
            if (c == 0) {
                g_sel[0] = i1; g_sel[1] = i2;
                g_gate[0] = bfr(1.f / (1.f + __expf(-bfr(b1))));
                g_gate[1] = bfr(1.f / (1.f + __expf(-bfr(b2))));
            }
        }
    }
    __syncthreads();
    sx[tid] = __ldcg(reinterpret_cast<const uint32_t*>(g_xn + (size_t)ssel[tid >> 8] * DM + (tid & 255) * 2));
    __syncthreads();
    TL(1);
    const int g = lane >> 2, t = lane & 3;
    const int lrow = lane & 15, lsel = lane >> 4;
    {
        float ag[4][4], au[4][4];
#pragma unroll
        for (int j = 0; j < 4; j++) { ag[j][0] = ag[j][1] = ag[j][2] = ag[j][3] = 0.f; au[j][0] = au[j][1] = au[j][2] = au[j][3] = 0.f; }
#pragma unroll 1
        for (int it = 0; it < 32; it++) {
            const int slot = it % FS_N;
            const uint32_t a0 = g < 2 ? sx[g * 256 + it * 8 + t] : 0u, a2 = g < 2 ? sx[g * 256 + it * 8 + 4 + t] : 0u;
            mbar_wait(bars + 8 * slot, (it / FS_N) & 1);
            const uint32_t base = sbase + slot * FS_BYTES + lsel * 14336 + lrow * 128;
#pragma unroll
            for (int j = 0; j < 4; j++) {
                const int nt = warp + j * 16;
                if (nt < 56) {
                    uint32_t b0, b1, b2, b3;
                    ldsm4t(b0, b1, b2, b3, base + (nt >> 3) * 2048 + (((nt & 7) ^ (lrow & 7)) << 4));
                    mma16816(ag[j], a0, a2, b0, b1);
                    mma16816(au[j], a0, a2, b2, b3);
                }
            }
            __syncthreads();
            if (tid == 480) issue(it + FS_N);
        }
        if (g < 2) {
#pragma unroll
            for (int j = 0; j < 4; j++) {
                const int nt = warp + j * 16;
                if (nt < 56) {
#pragma unroll
                    for (int e = 0; e < 2; e++) {
                        const float gs = bfr(ag[j][e]), us = bfr(au[j][e]);
                        const float sg = bfr(gs / (1.f + __expf(-gs)));
                        sh[g * 448 + nt * 8 + t * 2 + e] = __float2bfloat16_rn(sg * us);
                    }
                }
            }
        }
        __syncthreads();
    }
    TL(2);
    {
        const uint32_t* shw = reinterpret_cast<const uint32_t*>(sh);
        float a[4][4];
#pragma unroll
        for (int j = 0; j < 4; j++) a[j][0] = a[j][1] = a[j][2] = a[j][3] = 0.f;
#pragma unroll 1
        for (int it = 32; it < 46; it++) {
            const int slot = it % FS_N;
            uint32_t af[4];
#pragma unroll
            for (int q = 0; q < 4; q++) af[q] = g < 2 ? shw[g * 224 + (it - 32) * 16 + q * 4 + t] : 0u;
            mbar_wait(bars + 8 * slot, (it / FS_N) & 1);
            const uint32_t base = sbase + slot * FS_BYTES + (warp >> 1) * 4096 + lane * 128;
#pragma unroll
            for (int j = 0; j < 4; j++) {
                const int u = (warp & 1) * 4 + j;
                uint32_t b0, b1, b2, b3;
                ldsm4t(b0, b1, b2, b3, base + ((u ^ (lane & 7)) << 4));
                mma16816(a[j], af[0], af[1], b0, b1);
                mma16816(a[j], af[2], af[3], b2, b3);
            }
            __syncthreads();
            if (tid == 480 && it + FS_N < 46) issue(it + FS_N);
        }
        if (g < 2) {
#pragma unroll
            for (int j = 0; j < 4; j++)
                *reinterpret_cast<float2*>(&g_ypart[c * 1024 + g * 512 + (warp * 4 + j) * 8 + t * 2]) = make_float2(a[j][0], a[j][1]);
        }
    }
    warp_arrive(C_FFN);
}

__device__ __forceinline__ void wgmma_n64(float (&d)[32], uint64_t da, uint64_t db, int scale_d) {
    asm volatile("{\n.reg .pred p;\nsetp.ne.b32 p, %34, 0;\n"
        "wgmma.mma_async.sync.aligned.m64n64k16.f32.bf16.bf16 "
        "{%0,%1,%2,%3,%4,%5,%6,%7,%8,%9,%10,%11,%12,%13,%14,%15,%16,%17,%18,%19,%20,%21,%22,%23,%24,%25,%26,%27,%28,%29,%30,%31}, "
        "%32, %33, p, 1, 1, 0, 1;\n}"
        : "+f"(d[0]), "+f"(d[1]), "+f"(d[2]), "+f"(d[3]), "+f"(d[4]), "+f"(d[5]), "+f"(d[6]), "+f"(d[7]),
          "+f"(d[8]), "+f"(d[9]), "+f"(d[10]), "+f"(d[11]), "+f"(d[12]), "+f"(d[13]), "+f"(d[14]), "+f"(d[15]),
          "+f"(d[16]), "+f"(d[17]), "+f"(d[18]), "+f"(d[19]), "+f"(d[20]), "+f"(d[21]), "+f"(d[22]), "+f"(d[23]),
          "+f"(d[24]), "+f"(d[25]), "+f"(d[26]), "+f"(d[27]), "+f"(d[28]), "+f"(d[29]), "+f"(d[30]), "+f"(d[31])
        : "l"(da), "l"(db), "r"(scale_d));
}

constexpr int G_ST = 4;
constexpr int G_STAGE = 16384 + 24576;
constexpr int SM_K = 65536, SM_V = 131072, SM_ONES = 196608, SM_MISC = 229376;
constexpr int FUSED_SMEM = SM_MISC + 2048;
constexpr int B_FULL = 0, B_EMPTY = 4, B_KV = 8, B_WO = 16, B_OA = 18, B_NUM = 22;

struct Maps { CUtensorMap xn, wqkv, o, wo, g, u, d; };

__global__ void __launch_bounds__(512, 1) fused_kernel(const __grid_constant__ Maps maps, const __nv_bfloat16* __restrict__ x,
                                                       const __nv_bfloat16* __restrict__ wr, __nv_bfloat16* __restrict__ out, float sc) {
    extern __shared__ __align__(1024) uint8_t smem[];
    const uint32_t sbase = smem_u32(smem);
    const int tid = threadIdx.x, warp = tid >> 5, lane = tid & 31;
    const uint32_t bars = sbase + SM_MISC;
    TL(0);
    if (sbase & 1023u) __trap();
    if (blockIdx.x < 4) {
        ffn_block(blockIdx.x, smem, sbase, &maps.g, &maps.u, &maps.d);
        TL(3);
    } else {
        const int idx = blockIdx.x - 4;
        const int wg = warp >> 2;
        {
            const int nb = idx & 7;
            if (tid == 480) {
                for (int s = 0; s < G_ST; s++) { mbar_init(bars + 8 * (B_FULL + s), 2); mbar_init(bars + 8 * (B_EMPTY + s), 2); }
                for (int c = B_KV; c < B_NUM; c++) mbar_init(bars + 8 * c, 1);
                fence_barrier_init();
                for (int c = 0; c < G_ST; c++) {
                    mbar_expect_tx(bars + 8 * (B_FULL + c), 24576);
                    tma3d(sbase + c * G_STAGE + 16384, &maps.wqkv, bars + 8 * (B_FULL + c), c * 64, nb * 3);
                }
                map_prefetch(&maps.xn);
            }
        }
        {
            const int row = idx * 16 + warp;
            const uint4* xr = reinterpret_cast<const uint4*>(x + (size_t)row * DM);
            const uint4 a = xr[lane], b = xr[32 + lane];
            const uint4* wp = reinterpret_cast<const uint4*>(wr);
            const uint4 wa = wp[lane], wb = wp[32 + lane];
            {
                uint4* ones = reinterpret_cast<uint4*>(smem + SM_ONES);
#pragma unroll
                for (int i = 0; i < 4; i++) ones[tid + i * 512] = make_uint4(0x3f803f80u, 0x3f803f80u, 0x3f803f80u, 0x3f803f80u);
                fence_proxy_async();
            }
            __syncthreads();
            const uint32_t u[8] = {a.x, a.y, a.z, a.w, b.x, b.y, b.z, b.w};
            const uint32_t w[8] = {wa.x, wa.y, wa.z, wa.w, wb.x, wb.y, wb.z, wb.w};
            float f[16];
            float sum = 0.f;
#pragma unroll
            for (int i = 0; i < 8; i++) { f[2 * i] = bf_lo(u[i]); f[2 * i + 1] = bf_hi(u[i]); sum += f[2 * i] + f[2 * i + 1]; }
#pragma unroll
            for (int o = 16; o > 0; o >>= 1) sum += __shfl_xor_sync(~0u, sum, o);
            const float mean = sum * (1.f / DM);
            float sq = 0.f;
#pragma unroll
            for (int i = 0; i < 16; i++) { const float d = f[i] - mean; sq = fmaf(d, d, sq); }
#pragma unroll
            for (int o = 16; o > 0; o >>= 1) sq += __shfl_xor_sync(~0u, sq, o);
            const float mb_ = bfr(mean);
            const float vb = bfr(sq * (1.f / DM));
            const float rinv = 1.f / bfr(sqrtf(bfr(vb + 1e-5f)));
            uint32_t o[8];
            float r = 0.f;
#pragma unroll
            for (int i = 0; i < 8; i++) {
                const float d0 = bfr(f[2 * i] - mb_), d1 = bfr(f[2 * i + 1] - mb_);
                o[i] = packbf(d0 * rinv, d1 * rinv);
                r = fmaf(bf_lo(o[i]), bf_lo(w[i]), r);
                r = fmaf(bf_hi(o[i]), bf_hi(w[i]), r);
            }
            uint4* xo = reinterpret_cast<uint4*>(g_xn + (size_t)row * DM);
            xo[lane] = make_uint4(o[0], o[1], o[2], o[3]);
            xo[32 + lane] = make_uint4(o[4], o[5], o[6], o[7]);
#pragma unroll
            for (int of = 16; of > 0; of >>= 1) r += __shfl_xor_sync(~0u, r, of);
            if (lane == 0) g_r[row] = r;
            warp_arrive(C_LN + (idx >> 3));
        }
        TL(1);
        {
            const int nb = idx & 7, mb = idx >> 3;
            if (tid == 480) {
                for (int c = G_ST; c < 8; c++) {
                    const int s = c - G_ST;
                    mbar_wait(bars + 8 * (B_EMPTY + s), 0);
                    mbar_expect_tx(bars + 8 * (B_FULL + s), 24576);
                    tma3d(sbase + s * G_STAGE + 16384, &maps.wqkv, bars + 8 * (B_FULL + s), c * 64, nb * 3);
                }
            } else if (tid == 448) {
                flag_wait(C_LN + mb, 128);
                fence_proxy_async_all();
                for (int c = 0; c < 8; c++) {
                    const int s = c & (G_ST - 1);
                    if (c >= G_ST) mbar_wait(bars + 8 * (B_EMPTY + s), 0);
                    mbar_expect_tx(bars + 8 * (B_FULL + s), 16384);
                    tma3d(sbase + s * G_STAGE, &maps.xn, bars + 8 * (B_FULL + s), mb * 128, c);
                }
            } else if (wg < 2) {
                float acc[96];
#pragma unroll
                for (int i = 0; i < 96; i++) acc[i] = 0.f;
#pragma unroll 1
                for (int c = 0; c < 8; c++) {
                    const int s = c & (G_ST - 1);
                    const uint32_t st = sbase + s * G_STAGE;
                    mbar_wait(bars + 8 * (B_FULL + s), c >> 2);
                    if (c == 0) TL(2);
                    const uint64_t da = mkdesc(st + wg * 8192, 16, 1024, 1);
                    const uint64_t db = mkdesc(st + 16384, 8192, 1024, 1);
                    WG_FENCE();
#pragma unroll
                    for (int k = 0; k < 4; k++) wgmma_n192(acc, da + k * 2, db + k * 128, (c | k) != 0);
                    WG_COMMIT();
                    if (c <= G_ST) {
                        WG_WAIT(1);
                        if (c >= 1 && (tid & 127) == 0) mbar_arrive(bars + 8 * (B_EMPTY + c - 1));
                    }
                }
                WG_WAIT(0);
                nbar_arrive(6, 288);
                TL(3);
                const int g = lane >> 2, t = lane & 3;
                const int mt = mb * 8 + warp;
#pragma unroll
                for (int hh = 0; hh < 12; hh++) {
                    const int gh = nb * 12 + hh;
                    const float* a = &acc[hh * 8];
                    if (gh < 32) {
                        g_q[(gh * 128 + mt) * 32 + lane] = make_uint4(packbf(a[0], a[1]), packbf(a[2], a[3]), packbf(a[4], a[5]), packbf(a[6], a[7]));
                    } else {
                        uint32_t* dst = reinterpret_cast<uint32_t*>(gh < 64 ? g_k + (gh - 32) * 4096 : g_v + (gh - 64) * 4096);
                        const float ks = gh < 64 ? 5.421010862427522e-20f : 1.0f;
                        const int off = (mt * 16 + g) * 4 + t;
                        dst[off] = packbf(a[0] * ks, a[1] * ks);
                        dst[off + 32] = packbf(a[2] * ks, a[3] * ks);
                        dst[8192 + off] = packbf(a[4] * ks, a[5] * ks);
                        dst[8192 + off + 32] = packbf(a[6] * ks, a[7] * ks);
                    }
                }
                warp_arrive(C_QKV + nb);
            }
        }
        TL(4);
        uint32_t badmask = 0;
        const int head = idx >> 2, quarter = idx & 3, w4 = warp & 3;
        {
            if (warp == 15) { __syncwarp(); nbar_sync(6, 288); }
            if (tid == 480) {
                flag_wait(C_QKV + (32 + head) / 12, 128);
                flag_wait(C_QKV + (64 + head) / 12, 128);
                fence_proxy_async_all();
                const uint8_t* kp = reinterpret_cast<const uint8_t*>(g_k + head * 4096);
                const uint8_t* vp = reinterpret_cast<const uint8_t*>(g_v + head * 4096);
                for (int c = 0; c < 8; c++) {
                    const uint32_t bar = bars + 8 * (B_KV + c);
                    mbar_expect_tx(bar, 16384);
                    bulk_g2s(sbase + SM_K + c * 4096, kp + c * 4096, 4096, bar);
                    bulk_g2s(sbase + SM_K + 32768 + c * 4096, kp + 32768 + c * 4096, 4096, bar);
                    bulk_g2s(sbase + SM_V + c * 4096, vp + c * 4096, 4096, bar);
                    bulk_g2s(sbase + SM_V + 32768 + c * 4096, vp + 32768 + c * 4096, 4096, bar);
                }
                mbar_expect_tx(bars + 8 * B_WO, 65536);
                tma3d(sbase, &maps.wo, bars + 8 * B_WO, 0, (idx & 3) * 2);
                map_prefetch(&maps.o);
            }
            if (lane == 0) flag_wait(C_QKV + head / 12, 128);
            __syncwarp();
            const uint64_t kdesc0 = mkdesc(sbase + SM_K, 32768, 128, 0);
            const uint64_t vdesc0 = mkdesc(sbase + SM_V, 128, 32768, 0);
#pragma unroll 1
            for (int mt = 0; mt < 2; mt++) {
                const int m64 = quarter * 8 + mt * 4 + wg;
                uint32_t q[4];
                { const uint4 qq = __ldcg(&g_q[(head * 128 + m64 * 4 + w4) * 32 + lane]); q[0] = qq.x; q[1] = qq.y; q[2] = qq.z; q[3] = qq.w; }
                float s[32], s2[32], o[12];
#pragma unroll
                for (int i = 0; i < 12; i++) o[i] = 0.f;
                mbar_wait(bars + 8 * B_KV, 0);
                if (mt == 0) TL(5);
                WG_FENCE();
                qk64(s, q, kdesc0);
                WG_COMMIT(); WG_WAIT(0);
                float mx0 = -INFINITY, mx1 = -INFINITY;
#pragma unroll
                for (int i = 0; i < 8; i++) { mx0 = fmaxf(mx0, fmaxf(s[4 * i], s[4 * i + 1])); mx1 = fmaxf(mx1, fmaxf(s[4 * i + 2], s[4 * i + 3])); }
                mx0 = fmaxf(mx0, __shfl_xor_sync(~0u, mx0, 1)); mx0 = fmaxf(mx0, __shfl_xor_sync(~0u, mx0, 2));
                mx1 = fmaxf(mx1, __shfl_xor_sync(~0u, mx1, 1)); mx1 = fmaxf(mx1, __shfl_xor_sync(~0u, mx1, 2));
                float cm0 = -(ceilf(mx0 * QS) + SHIFT), cm1 = -(ceilf(mx1 * QS) + SHIFT);
                float cp0 = (cm0 + 127.f) * sc, cp1 = (cm1 + 127.f) * sc;
                asm volatile("" : "+f"(cm0), "+f"(cm1), "+f"(cp0), "+f"(cp1));
                uint64_t kd = kdesc0, vd = vdesc0;
                auto step = [&](float (&sc_)[32], float (&sn)[32]) {
                    kd += 64;
                    WG_FENCE();
                    qk64(sn, q, kd);
                    WG_COMMIT();
#pragma unroll
                    for (int kk = 0; kk < 4; kk++) {
                        const int i0 = kk * 2, i1 = kk * 2 + 1;
                        const uint32_t p0 = packbf(ex2(fmaf(sc_[4 * i0], QS, cm0)), ex2(fmaf(sc_[4 * i0 + 1], QS, cm0)));
                        const uint32_t p1 = packbf(ex2(fmaf(sc_[4 * i0 + 2], QS, cm1)), ex2(fmaf(sc_[4 * i0 + 3], QS, cm1)));
                        const uint32_t p2 = polyexp(fmaf(sc_[4 * i1], scq, cp0), fmaf(sc_[4 * i1 + 1], scq, cp0));
                        const uint32_t p3 = polyexp(fmaf(sc_[4 * i1 + 2], scq, cp1), fmaf(sc_[4 * i1 + 3], scq, cp1));
                        WG_FENCE();
                        pv24(o, p0, p1, p2, p3, vd);
                        vd += 16;
                    }
                    WG_COMMIT();
                    WG_WAIT(1);
                };
#pragma unroll 1
                for (int c = 0; c < 16; c++) {
                    if (mt == 0 && (c & 1) == 0 && c < 14) mbar_wait(bars + 8 * B_KV + 4 * c + 8, 0);
                    step(s, s2); step(s2, s);
                }
                WG_WAIT(0);
                bool bad = !(o[8] > 0.f) || !(o[10] > 0.f);
#pragma unroll
                for (int i = 0; i < 12; i++) bad = bad || !(fabsf(o[i]) <= 3.0e38f);
                uint32_t anybad;
                asm volatile("{\n.reg .pred p, q;\nsetp.ne.u32 p, %1, 0;\nbarrier.cta.red.or.pred q, %2, 128, p;\nselp.u32 %0, 1, 0, q;\n}"
                             : "=r"(anybad) : "r"((uint32_t)bad), "r"(wg + 1) : "memory");
                badmask |= anybad << mt;
                if (mt == 1 && !badmask) { if (warp == 15) nbar_sync(7, 512); else nbar_arrive(7, 512); }
                if (mt == 1 && !badmask && tid == 480) {
                    mbar_expect_tx(bars + 8 * (B_WO + 1), 65536);
                    tma3d(sbase + 65536, &maps.wo, bars + 8 * (B_WO + 1), 256, (idx & 3) * 2);
                }
                attn_store(o, head, m64, w4, lane);
            }
        }
        if (badmask) {
#pragma unroll 1
            for (int mt = 0; mt < 2; mt++) {
                if (!((badmask >> mt) & 1)) continue;
                const int m64 = quarter * 8 + mt * 4 + wg;
                uint32_t q[4];
                { const uint4 qq = __ldcg(&g_q[(head * 128 + m64 * 4 + w4) * 32 + lane]); q[0] = qq.x; q[1] = qq.y; q[2] = qq.z; q[3] = qq.w; }
                float o[12];
                attn_safe(o, q, mkdesc(sbase + SM_K, 32768, 128, 0), mkdesc(sbase + SM_V, 128, 32768, 0));
                attn_store(o, head, m64, w4, lane);
            }
            if (warp == 15) nbar_sync(7, 512); else nbar_arrive(7, 512);
            if (tid == 480) {
                mbar_expect_tx(bars + 8 * (B_WO + 1), 65536);
                tma3d(sbase + 65536, &maps.wo, bars + 8 * (B_WO + 1), 256, (idx & 3) * 2);
            }
        }
        __syncwarp();
        if (lane == 0) {
            asm volatile("fence.acq_rel.gpu;" ::: "memory");
            asm volatile("red.relaxed.gpu.global.add.u32 [%0], 1;" :: "l"(g_cnt + (C_O + quarter * 8 + 4 + wg) * 32) : "memory");
            asm volatile("red.relaxed.gpu.global.add.u32 [%0], 1;" :: "l"(g_cnt + (C_O + quarter * 8 + wg) * 32) : "memory");
        }
        TL(6);
        {
            const int nb = idx & 3, mb = idx >> 2;
            float* supd = reinterpret_cast<float*>(smem + SM_MISC + 512);
            if (tid == 480) {
                flag_wait(C_O + mb, 128);
                fence_proxy_async_all();
                for (int c = 0; c < 4; c++) {
                    mbar_expect_tx(bars + 8 * (B_OA + c), 16384);
                    tma3d(sbase + SM_V + c * 16384, &maps.o, bars + 8 * (B_OA + c), mb * 64, c * 2);
                }
            }
            if (wg < 2) {
                const int g = lane >> 2, t = lane & 3;
                const int row0 = mb * 64 + w4 * 16 + g;
                const int col0 = nb * 128 + wg * 64 + t * 2;
                if (lane == 0) { flag_wait(C_LN + (mb >> 1), 128); flag_wait(C_FFN, 64); }
                __syncwarp();
                uint32_t xv[16], nv[16];
#pragma unroll
                for (int i = 0; i < 8; i++) {
                    xv[2 * i] = *reinterpret_cast<const uint32_t*>(x + (size_t)row0 * DM + col0 + i * 8);
                    xv[2 * i + 1] = *reinterpret_cast<const uint32_t*>(x + (size_t)(row0 + 8) * DM + col0 + i * 8);
                    nv[2 * i] = __ldcg(reinterpret_cast<const uint32_t*>(g_xn + (size_t)row0 * DM + col0 + i * 8));
                    nv[2 * i + 1] = __ldcg(reinterpret_cast<const uint32_t*>(g_xn + (size_t)(row0 + 8) * DM + col0 + i * 8));
                }
                const int sel0 = __ldcg(&g_sel[0]), sel1 = __ldcg(&g_sel[1]);
                {
                    const int which = tid >> 7, col = nb * 128 + (tid & 127);
                    const float y = __ldcg(&g_ypart[which * 512 + col]) + __ldcg(&g_ypart[1024 + which * 512 + col]) +
                                    __ldcg(&g_ypart[2048 + which * 512 + col]) + __ldcg(&g_ypart[3072 + which * 512 + col]);
                    supd[tid] = bfr(bfr(y) * __ldcg(&g_gate[which]));
                }
                asm volatile("bar.sync 5, 256;" ::: "memory");
                float acc[32];
#pragma unroll
                for (int i = 0; i < 32; i++) acc[i] = 0.f;
#pragma unroll 1
                for (int c = 0; c < 8; c++) {
                    if ((c & 3) == 0) mbar_wait(bars + 8 * (B_WO + (c >> 2)), 0);
                    if ((c & 1) == 0) mbar_wait(bars + 8 * (B_OA + (c >> 1)), 0);
                    if (c == 0) TL(7);
                    const uint64_t da = mkdesc(sbase + SM_V + c * 8192, 16, 1024, 1);
                    const uint64_t db = mkdesc(sbase + (c >> 2) * 65536 + wg * 32768 + (c & 3) * 8192, 8192, 1024, 1);
                    WG_FENCE();
#pragma unroll
                    for (int k = 0; k < 4; k++) wgmma_n64(acc, da + k * 2, db + k * 128, (c | k) != 0);
                    WG_COMMIT();
                }
                WG_WAIT(0);
                TL(8);
#pragma unroll
                for (int h = 0; h < 2; h++) {
                    const int row = row0 + h * 8;
                    const int which = row == sel0 ? 0 : (row == sel1 ? 1 : -1);
#pragma unroll
                    for (int i = 0; i < 8; i++) {
                        const int col = col0 + i * 8;
                        float b0 = bf_lo(nv[2 * i + h]), b1 = bf_hi(nv[2 * i + h]);
                        if (which >= 0) {
                            b0 = bfr(b0 + supd[which * 128 + col - nb * 128]); b1 = bfr(b1 + supd[which * 128 + col + 1 - nb * 128]);
                        }
                        const float t0 = bfr(bf_lo(xv[2 * i + h]) + bfr(acc[4 * i + 2 * h]));
                        const float t1 = bfr(bf_hi(xv[2 * i + h]) + bfr(acc[4 * i + 2 * h + 1]));
                        *reinterpret_cast<uint32_t*>(out + (size_t)row * DM + col) = packbf(t0 + b0, t1 + b1);
                    }
                }
            }
        }
        TL(9);
    }
    __syncthreads();
    if (tid == 0) {
        __threadfence();
        const unsigned tk = atomicAdd(&g_cnt[C_EXIT * 32], 1u);
        if (tk == gridDim.x - 1) {
            for (int i = 0; i < C_NUM; i++) g_cnt[i * 32] = 0u;
            __threadfence();
        }
    }
}

typedef CUresult (*EncodeFn)(CUtensorMap*, CUtensorMapDataType, cuuint32_t, void*, const cuuint64_t*, const cuuint64_t*,
                             const cuuint32_t*, const cuuint32_t*, CUtensorMapInterleave, CUtensorMapSwizzle,
                             CUtensorMapL2promotion, CUtensorMapFloatOOBfill);

void make_map(EncodeFn fn, CUtensorMap* m, const void* ptr, uint64_t cols, uint64_t rows, uint32_t box_rows, uint32_t box_chunks) {
    cuuint64_t dims[3] = {64, rows, cols / 64};
    cuuint64_t strides[2] = {cols * 2, 128};
    cuuint32_t box[3] = {64, box_rows, box_chunks};
    cuuint32_t es[3] = {1, 1, 1};
    fn(m, CU_TENSOR_MAP_DATA_TYPE_BFLOAT16, 3, const_cast<void*>(ptr), dims, strides, box, es, CU_TENSOR_MAP_INTERLEAVE_NONE,
       CU_TENSOR_MAP_SWIZZLE_128B, CU_TENSOR_MAP_L2_PROMOTION_L2_256B, CU_TENSOR_MAP_FLOAT_OOB_FILL_NONE);
}

}

extern "C" void kernel_launch(void* const* d_in, const int* in_sizes, int n_in, void* d_out, int out_size) {
    const __nv_bfloat16* x = (const __nv_bfloat16*)d_in[0];
    const __nv_bfloat16* wqkv = (const __nv_bfloat16*)d_in[1];
    const __nv_bfloat16* wo = (const __nv_bfloat16*)d_in[2];
    const __nv_bfloat16* wr = (const __nv_bfloat16*)d_in[4];
    const __nv_bfloat16* wgate = (const __nv_bfloat16*)d_in[5];
    const __nv_bfloat16* wup = (const __nv_bfloat16*)d_in[6];
    const __nv_bfloat16* wdown = (const __nv_bfloat16*)d_in[7];
    __nv_bfloat16* out = (__nv_bfloat16*)d_out;

    static EncodeFn enc = nullptr;
    static void* p_xn = nullptr; static void* p_o = nullptr;
    if (!enc) {
        void* fn = nullptr; cudaDriverEntryPointQueryResult qr;
        cudaGetDriverEntryPoint("cuTensorMapEncodeTiled", &fn, cudaEnableDefault, &qr);
        enc = (EncodeFn)fn;
        cudaGetSymbolAddress(&p_xn, g_xn);
        cudaGetSymbolAddress(&p_o, g_o);
        cudaFuncSetAttribute(fused_kernel, cudaFuncAttributeMaxDynamicSharedMemorySize, FUSED_SMEM);
    }
    Maps maps;
    make_map(enc, &maps.g, wgate, FF, DM, 16, 7);
    make_map(enc, &maps.u, wup, FF, DM, 16, 7);
    make_map(enc, &maps.d, wdown, DM, FF, 32, 8);
    make_map(enc, &maps.xn, p_xn, DM, S_LEN, 128, 1);
    make_map(enc, &maps.wqkv, wqkv, 3 * DM, DM, 64, 3);
    make_map(enc, &maps.o, p_o, DM, S_LEN, 64, 2);
    make_map(enc, &maps.wo, wo, DM, DM, 256, 2);

    union { uint32_t u; float f; } scu; scu.u = 128u;

    cudaLaunchConfig_t cfg = {};
    cfg.gridDim = dim3(132); cfg.blockDim = dim3(512); cfg.dynamicSmemBytes = FUSED_SMEM; cfg.stream = cudaStreamPerThread;
    cudaLaunchAttribute at[1];
    at[0].id = cudaLaunchAttributeCooperative;
    at[0].val.cooperative = 1;
    cfg.attrs = at; cfg.numAttrs = 1;
    cudaLaunchKernelEx(&cfg, fused_kernel, maps, x, wr, out, scu.f);
}
```

```cpp
#include <cuda_runtime.h>
#include <cuda_bf16.h>
#include <cuda.h>
#include <stdint.h>
#include <type_traits>

namespace {

constexpr int S_LEN = 2048;
constexpr int DM = 512;
constexpr int NH = 32;
constexpr int FF = 1792;

__device__ __align__(1024) __nv_bfloat16 g_xn[S_LEN * DM];
__device__ __align__(16) float g_r[S_LEN];
__device__ __align__(1024) uint4 g_q[NH * 128 * 32];
__device__ __align__(1024) uint4 g_k[NH * 4096];
__device__ __align__(1024) uint4 g_v[NH * 4096];
__device__ __align__(1024) __nv_bfloat16 g_o[S_LEN * DM];
__device__ __align__(16) float g_ypart[4 * 2 * DM];
__device__ int g_sel[2];
__device__ float g_gate[2];
constexpr int C_LN = 0, C_QKV = 16, C_O = 24, C_FFN = 56, C_EXIT = 57, C_NUM = 58;
__device__ unsigned g_cnt[C_NUM * 32];

#define TL(slot) do {} while (0)

__device__ __forceinline__ uint32_t smem_u32(const void* p) { return (uint32_t)__cvta_generic_to_shared(p); }
__device__ __forceinline__ void warp_arrive(int idx) {
    __syncwarp();
    if ((threadIdx.x & 31) == 0)
        asm volatile("red.release.gpu.global.add.u32 [%0], 1;" :: "l"(g_cnt + idx * 32) : "memory");
}
__device__ __forceinline__ void nbar_arrive(int id, int cnt) { asm volatile("bar.arrive %0, %1;" :: "r"(id), "r"(cnt) : "memory"); }
__device__ __forceinline__ void nbar_sync(int id, int cnt) { asm volatile("bar.sync %0, %1;" :: "r"(id), "r"(cnt) : "memory"); }
__device__ __forceinline__ void flag_wait(int idx, unsigned target) {
    asm volatile("{\n.reg .pred p;\n.reg .u32 n, v;\nmov.u32 n, 0;\n"
                 "FW_%=:\n"
                 "ld.acquire.gpu.global.u32 v, [%0];\n"
                 "setp.ge.u32 p, v, %1;\n"
                 "@p bra FD_%=;\n"
                 "add.u32 n, n, 1;\n"
                 "setp.lt.u32 p, n, 16000000;\n"
                 "@p bra FW_%=;\n"
                 "trap;\n"
                 "FD_%=:\n}"
                 :: "l"(g_cnt + idx * 32), "r"(target) : "memory");
}
__device__ __forceinline__ void fence_proxy_async_all() { asm volatile("fence.proxy.async;" ::: "memory"); }
__device__ __forceinline__ void mbar_init(uint32_t bar, uint32_t cnt) {
    asm volatile("mbarrier.init.shared::cta.b64 [%0], %1;" :: "r"(bar), "r"(cnt) : "memory");
}
__device__ __forceinline__ void mbar_expect_tx(uint32_t bar, uint32_t bytes) {
    asm volatile("mbarrier.arrive.expect_tx.shared::cta.b64 _, [%0], %1;" :: "r"(bar), "r"(bytes) : "memory");
}
__device__ __forceinline__ void mbar_arrive(uint32_t bar) {
    asm volatile("mbarrier.arrive.shared::cta.b64 _, [%0];" :: "r"(bar) : "memory");
}
__device__ __forceinline__ void mbar_wait(uint32_t bar, uint32_t parity) {
    asm volatile("{\n.reg .pred p;\n.reg .u32 n;\nmov.u32 n, 0;\n"
                 "WAIT_%=:\n"
                 "mbarrier.try_wait.parity.shared::cta.b64 p, [%0], %1;\n"
                 "@p bra DONE_%=;\n"
                 "add.u32 n, n, 1;\n"
                 "setp.lt.u32 p, n, 4000000;\n"
                 "@p bra WAIT_%=;\n"
                 "trap;\n"
                 "DONE_%=:\n}"
                 :: "r"(bar), "r"(parity) : "memory");
}
__device__ __forceinline__ void fence_barrier_init() { asm volatile("fence.mbarrier_init.release.cluster;" ::: "memory"); }
__device__ __forceinline__ void fence_proxy_async() { asm volatile("fence.proxy.async.shared::cta;" ::: "memory"); }
__device__ __forceinline__ void tma3d(uint32_t dst, const CUtensorMap* map, uint32_t bar, int row, int chunk) {
    asm volatile("cp.async.bulk.tensor.3d.shared::cluster.global.mbarrier::complete_tx::bytes [%0], [%1, {%3, %4, %5}], [%2];"
                 :: "r"(dst), "l"((uint64_t)map), "r"(bar), "r"(0), "r"(row), "r"(chunk) : "memory");
}
__device__ __forceinline__ void bulk_g2s(uint32_t dst, const void* src, uint32_t bytes, uint32_t bar) {
    asm volatile("cp.async.bulk.shared::cluster.global.mbarrier::complete_tx::bytes [%0], [%1], %2, [%3];"
                 :: "r"(dst), "l"((uint64_t)src), "r"(bytes), "r"(bar) : "memory");
}
__device__ __forceinline__ void l2_prefetch(const void* src, uint32_t bytes) {
    asm volatile("cp.async.bulk.prefetch.L2.global [%0], %1;" :: "l"((uint64_t)src), "r"(bytes) : "memory");
}
__device__ __forceinline__ void map_prefetch(const CUtensorMap* m) {
    asm volatile("prefetch.tensormap [%0];" :: "l"((uint64_t)m) : "memory");
}
__device__ __forceinline__ uint64_t mkdesc(uint32_t addr, uint32_t lbo, uint32_t sbo, uint32_t swz) {
    return (uint64_t)((addr & 0x3FFFF) >> 4) | ((uint64_t)(lbo >> 4) << 16) | ((uint64_t)(sbo >> 4) << 32) | ((uint64_t)swz << 62);
}
#define WG_FENCE() asm volatile("wgmma.fence.sync.aligned;" ::: "memory")
#define WG_COMMIT() asm volatile("wgmma.commit_group.sync.aligned;" ::: "memory")
#define WG_WAIT(n) asm volatile("wgmma.wait_group.sync.aligned %0;" :: "n"(n) : "memory")

__device__ __forceinline__ float ex2(float x) { float y; asm("ex2.approx.ftz.f32 %0, %1;" : "=f"(y) : "f"(x)); return y; }
__device__ __forceinline__ uint32_t packbf(float lo, float hi) {
    uint32_t r; asm("cvt.rn.bf16x2.f32 %0, %1, %2;" : "=r"(r) : "f"(hi), "f"(lo)); return r;
}
__device__ __forceinline__ float bf_lo(uint32_t v) { return __uint_as_float(v << 16); }
__device__ __forceinline__ float bf_hi(uint32_t v) { return __uint_as_float(v & 0xffff0000u); }
__device__ __forceinline__ float bfr(float x) { return __bfloat162float(__float2bfloat16_rn(x)); }

__device__ __forceinline__ void wgmma_n192(float (&d)[96], uint64_t da, uint64_t db, int scale_d) {
    asm volatile("{\n.reg .pred p;\nsetp.ne.b32 p, %98, 0;\n"
        "wgmma.mma_async.sync.aligned.m64n192k16.f32.bf16.bf16 "
        "{%0,%1,%2,%3,%4,%5,%6,%7,%8,%9,%10,%11,%12,%13,%14,%15,%16,%17,%18,%19,%20,%21,%22,%23,"
        "%24,%25,%26,%27,%28,%29,%30,%31,%32,%33,%34,%35,%36,%37,%38,%39,%40,%41,%42,%43,%44,%45,%46,%47,"
        "%48,%49,%50,%51,%52,%53,%54,%55,%56,%57,%58,%59,%60,%61,%62,%63,%64,%65,%66,%67,%68,%69,%70,%71,"
        "%72,%73,%74,%75,%76,%77,%78,%79,%80,%81,%82,%83,%84,%85,%86,%87,%88,%89,%90,%91,%92,%93,%94,%95}, "
        "%96, %97, p, 1, 1, 0, 1;\n}"
        : "+f"(d[0]), "+f"(d[1]), "+f"(d[2]), "+f"(d[3]), "+f"(d[4]), "+f"(d[5]), "+f"(d[6]), "+f"(d[7]),
          "+f"(d[8]), "+f"(d[9]), "+f"(d[10]), "+f"(d[11]), "+f"(d[12]), "+f"(d[13]), "+f"(d[14]), "+f"(d[15]),
          "+f"(d[16]), "+f"(d[17]), "+f"(d[18]), "+f"(d[19]), "+f"(d[20]), "+f"(d[21]), "+f"(d[22]), "+f"(d[23]),
          "+f"(d[24]), "+f"(d[25]), "+f"(d[26]), "+f"(d[27]), "+f"(d[28]), "+f"(d[29]), "+f"(d[30]), "+f"(d[31]),
          "+f"(d[32]), "+f"(d[33]), "+f"(d[34]), "+f"(d[35]), "+f"(d[36]), "+f"(d[37]), "+f"(d[38]), "+f"(d[39]),
          "+f"(d[40]), "+f"(d[41]), "+f"(d[42]), "+f"(d[43]), "+f"(d[44]), "+f"(d[45]), "+f"(d[46]), "+f"(d[47]),
          "+f"(d[48]), "+f"(d[49]), "+f"(d[50]), "+f"(d[51]), "+f"(d[52]), "+f"(d[53]), "+f"(d[54]), "+f"(d[55]),
          "+f"(d[56]), "+f"(d[57]), "+f"(d[58]), "+f"(d[59]), "+f"(d[60]), "+f"(d[61]), "+f"(d[62]), "+f"(d[63]),
          "+f"(d[64]), "+f"(d[65]), "+f"(d[66]), "+f"(d[67]), "+f"(d[68]), "+f"(d[69]), "+f"(d[70]), "+f"(d[71]),
          "+f"(d[72]), "+f"(d[73]), "+f"(d[74]), "+f"(d[75]), "+f"(d[76]), "+f"(d[77]), "+f"(d[78]), "+f"(d[79]),
          "+f"(d[80]), "+f"(d[81]), "+f"(d[82]), "+f"(d[83]), "+f"(d[84]), "+f"(d[85]), "+f"(d[86]), "+f"(d[87]),
          "+f"(d[88]), "+f"(d[89]), "+f"(d[90]), "+f"(d[91]), "+f"(d[92]), "+f"(d[93]), "+f"(d[94]), "+f"(d[95])
        : "l"(da), "l"(db), "r"(scale_d));
}

constexpr float SHIFT = 90.0f;
constexpr float QS = 0.25f * 1.4426950408889634f * 18446744073709551616.0f;
constexpr float scq = 0.25f * 1.4426950408889634f * 3.3087224502121107e-24f;

__device__ __forceinline__ uint32_t polyexp(float lo, float hi) {
    uint32_t w, g, q, h;
    asm("cvt.pack.sat.s16.s32 %0, %1, %2;" : "=r"(w) : "r"(__float_as_uint(hi)), "r"(__float_as_uint(lo)));
    g = w & 0x007F007Fu;
    asm("fma.rn.f16x2 %0, %1, %2, %3;" : "=r"(q) : "r"(g), "r"(0xf940f940u), "r"(0x35513551u));
    asm("mul.rn.f16x2 %0, %1, %2;" : "=r"(h) : "r"(q), "r"(g));
    return w - h;
}
__device__ __forceinline__ void qk64(float (&s)[32], const uint32_t (&q)[4], uint64_t db) {
    asm volatile("wgmma.mma_async.sync.aligned.m64n64k16.f32.bf16.bf16 "
        "{%0,%1,%2,%3,%4,%5,%6,%7,%8,%9,%10,%11,%12,%13,%14,%15,%16,%17,%18,%19,%20,%21,%22,%23,%24,%25,%26,%27,%28,%29,%30,%31}, "
        "{%32,%33,%34,%35}, %36, 0, 1, 1, 0;"
        : "=f"(s[0]), "=f"(s[1]), "=f"(s[2]), "=f"(s[3]), "=f"(s[4]), "=f"(s[5]), "=f"(s[6]), "=f"(s[7]),
          "=f"(s[8]), "=f"(s[9]), "=f"(s[10]), "=f"(s[11]), "=f"(s[12]), "=f"(s[13]), "=f"(s[14]), "=f"(s[15]),
          "=f"(s[16]), "=f"(s[17]), "=f"(s[18]), "=f"(s[19]), "=f"(s[20]), "=f"(s[21]), "=f"(s[22]), "=f"(s[23]),
          "=f"(s[24]), "=f"(s[25]), "=f"(s[26]), "=f"(s[27]), "=f"(s[28]), "=f"(s[29]), "=f"(s[30]), "=f"(s[31])
        : "r"(q[0]), "r"(q[1]), "r"(q[2]), "r"(q[3]), "l"(db));
}
__device__ __forceinline__ void pv24(float (&o)[12], uint32_t a0, uint32_t a1, uint32_t a2, uint32_t a3, uint64_t db) {
    asm volatile("wgmma.mma_async.sync.aligned.m64n24k16.f32.bf16.bf16 "
        "{%0,%1,%2,%3,%4,%5,%6,%7,%8,%9,%10,%11}, {%12,%13,%14,%15}, %16, 1, 1, 1, 1;"
        : "+f"(o[0]), "+f"(o[1]), "+f"(o[2]), "+f"(o[3]), "+f"(o[4]), "+f"(o[5]), "+f"(o[6]), "+f"(o[7]),
          "+f"(o[8]), "+f"(o[9]), "+f"(o[10]), "+f"(o[11])
        : "r"(a0), "r"(a1), "r"(a2), "r"(a3), "l"(db));
}

__device__ __forceinline__ void attn_safe(float (&o)[12], const uint32_t (&q)[4], uint64_t kdesc0, uint64_t vdesc0) {
    float s[32];
    float m0 = -INFINITY, m1 = -INFINITY;
#pragma unroll
    for (int i = 0; i < 12; i++) o[i] = 0.f;
#pragma unroll 1
    for (int j = 0; j < 32; j++) {
        WG_FENCE();
        qk64(s, q, kdesc0 + (uint64_t)(j * 64));
        WG_COMMIT(); WG_WAIT(0);
        float n0 = m0, n1 = m1;
#pragma unroll
        for (int i = 0; i < 8; i++) { n0 = fmaxf(n0, fmaxf(s[4 * i], s[4 * i + 1])); n1 = fmaxf(n1, fmaxf(s[4 * i + 2], s[4 * i + 3])); }
        n0 = fmaxf(n0, __shfl_xor_sync(~0u, n0, 1)); n0 = fmaxf(n0, __shfl_xor_sync(~0u, n0, 2));
        n1 = fmaxf(n1, __shfl_xor_sync(~0u, n1, 1)); n1 = fmaxf(n1, __shfl_xor_sync(~0u, n1, 2));
        const float c0 = ex2((m0 - n0) * QS), c1 = ex2((m1 - n1) * QS);
        m0 = n0; m1 = n1;
#pragma unroll
        for (int i = 0; i < 3; i++) { o[4 * i] *= c0; o[4 * i + 1] *= c0; o[4 * i + 2] *= c1; o[4 * i + 3] *= c1; }
        uint32_t p[16];
#pragma unroll
        for (int i = 0; i < 8; i++) {
            p[2 * i] = packbf(ex2((s[4 * i] - m0) * QS), ex2((s[4 * i + 1] - m0) * QS));
            p[2 * i + 1] = packbf(ex2((s[4 * i + 2] - m1) * QS), ex2((s[4 * i + 3] - m1) * QS));
        }
        WG_FENCE();
#pragma unroll
        for (int kk = 0; kk < 4; kk++) pv24(o, p[4 * kk], p[4 * kk + 1], p[4 * kk + 2], p[4 * kk + 3], vdesc0 + (uint64_t)(j * 64 + kk * 16));
        WG_COMMIT(); WG_WAIT(0);
    }
}

__device__ __forceinline__ void attn_store(const float (&o)[12], int head, int m64, int warp, int lane) {
    const int g = lane >> 2, t = lane & 3;
    const int row = m64 * 64 + warp * 16 + g;
    const float i0 = 1.f / o[8], i1 = 1.f / o[10];
    uint32_t* p0 = reinterpret_cast<uint32_t*>(g_o + (size_t)row * DM + head * 16 + t * 2);
    uint32_t* p1 = reinterpret_cast<uint32_t*>(g_o + (size_t)(row + 8) * DM + head * 16 + t * 2);
    p0[0] = packbf(o[0] * i0, o[1] * i0); p0[4] = packbf(o[4] * i0, o[5] * i0);
    p1[0] = packbf(o[2] * i1, o[3] * i1); p1[4] = packbf(o[6] * i1, o[7] * i1);
}

constexpr int FS_N = 4;
constexpr int FS_BYTES = 32768;
__device__ __forceinline__ void ldsm4t(uint32_t& r0, uint32_t& r1, uint32_t& r2, uint32_t& r3, uint32_t addr) {
    asm volatile("ldmatrix.sync.aligned.m8n8.x4.trans.shared.b16 {%0,%1,%2,%3}, [%4];" : "=r"(r0), "=r"(r1), "=r"(r2), "=r"(r3) : "r"(addr) : "memory");
}
__device__ __forceinline__ void mma16816(float (&d)[4], uint32_t a0, uint32_t a2, uint32_t b0, uint32_t b1) {
    asm volatile("mma.sync.aligned.m16n8k16.row.col.f32.bf16.bf16.f32 {%0,%1,%2,%3}, {%4,%5,%6,%5}, {%7,%8}, {%0,%1,%2,%3};"
                 : "+f"(d[0]), "+f"(d[1]), "+f"(d[2]), "+f"(d[3]) : "r"(a0), "r"(0u), "r"(a2), "r"(b0), "r"(b1));
}
__device__ void ffn_block(int c, uint8_t* smem, uint32_t sbase, const CUtensorMap* mapG, const CUtensorMap* mapU, const CUtensorMap* mapD) {
    const int tid = threadIdx.x, warp = tid >> 5, lane = tid & 31;
    uint32_t* sx = reinterpret_cast<uint32_t*>(smem + FS_N * FS_BYTES);
    __nv_bfloat16* sh = reinterpret_cast<__nv_bfloat16*>(sx + 512);
    const uint32_t bars = sbase + FS_N * FS_BYTES + 8192;
    float* tv = reinterpret_cast<float*>(smem + FS_N * FS_BYTES + 4096);
    int* ti = reinterpret_cast<int*>(tv + 32);
    int* ssel = ti + 32;
    auto issue = [&](int item) {
        const int slot = item % FS_N;
        const uint32_t dst = sbase + slot * FS_BYTES, bar = bars + 8 * slot;
        mbar_expect_tx(bar, item < 32 ? 28672 : 32768);
        if (item < 32) {
            tma3d(dst, mapG, bar, item * 16, c * 7);
            tma3d(dst + 14336, mapU, bar, item * 16, c * 7);
        } else {
            tma3d(dst, mapD, bar, c * 448 + (item - 32) * 32, 0);
        }
    };
    if (tid == 0) {
        for (int i = 0; i < FS_N; i++) mbar_init(bars + 8 * i, 1);
        fence_barrier_init();
        for (int i = 0; i < FS_N; i++) issue(i);
    }
    flag_wait(C_LN + warp, 128);
    __syncthreads();
    float b1 = -INFINITY, b2 = -INFINITY; int i1 = 0x7fffffff, i2 = 0x7fffffff;
    auto push = [&](float v, int i) {
        if (v > b1 || (v == b1 && i < i1)) { b2 = b1; i2 = i1; b1 = v; i1 = i; }
        else if (v > b2 || (v == b2 && i < i2)) { b2 = v; i2 = i; }
    };
    {
        const float4 rv = __ldcg(reinterpret_cast<const float4*>(g_r) + tid);
        push(rv.x, 4 * tid); push(rv.y, 4 * tid + 1); push(rv.z, 4 * tid + 2); push(rv.w, 4 * tid + 3);
    }
#pragma unroll
    for (int o = 16; o > 0; o >>= 1) {
        float v1 = __shfl_xor_sync(~0u, b1, o), v2 = __shfl_xor_sync(~0u, b2, o);
        int j1 = __shfl_xor_sync(~0u, i1, o), j2 = __shfl_xor_sync(~0u, i2, o);
        push(v1, j1); push(v2, j2);
    }
    if (lane == 0) { tv[2 * warp] = b1; ti[2 * warp] = i1; tv[2 * warp + 1] = b2; ti[2 * warp + 1] = i2; }
    __syncthreads();
    if (warp == 1) {
        b1 = tv[lane]; i1 = ti[lane]; b2 = -INFINITY; i2 = 0x7fffffff;
#pragma unroll
        for (int o = 16; o > 0; o >>= 1) {
            float v1 = __shfl_xor_sync(~0u, b1, o), v2 = __shfl_xor_sync(~0u, b2, o);
            int j1 = __shfl_xor_sync(~0u, i1, o), j2 = __shfl_xor_sync(~0u, i2, o);
            push(v1, j1); push(v2, j2);
        }
        if (lane == 0) {
            i1 = min(max(i1, 0), S_LEN - 1); i2 = min(max(i2, 0), S_LEN - 1);
            ssel[0] = i1; ssel[1] = i2;
            if (c == 0) {
                g_sel[0] = i1; g_sel[1] = i2;
                g_gate[0] = bfr(1.f / (1.f + __expf(-bfr(b1))));
                g_gate[1] = bfr(1.f / (1.f + __expf(-bfr(b2))));
            }
        }
    }
    __syncthreads();
    sx[tid] = __ldcg(reinterpret_cast<const uint32_t*>(g_xn + (size_t)ssel[tid >> 8] * DM + (tid & 255) * 2));
    __syncthreads();
    TL(1);
    const int g = lane >> 2, t = lane & 3;
    const int lrow = lane & 15, lsel = lane >> 4;
    {
        float ag[4][4], au[4][4];
#pragma unroll
        for (int j = 0; j < 4; j++) { ag[j][0] = ag[j][1] = ag[j][2] = ag[j][3] = 0.f; au[j][0] = au[j][1] = au[j][2] = au[j][3] = 0.f; }
#pragma unroll 1
        for (int it = 0; it < 32; it++) {
            const int slot = it % FS_N;
            const uint32_t a0 = g < 2 ? sx[g * 256 + it * 8 + t] : 0u, a2 = g < 2 ? sx[g * 256 + it * 8 + 4 + t] : 0u;
            mbar_wait(bars + 8 * slot, (it / FS_N) & 1);
            const uint32_t base = sbase + slot * FS_BYTES + lsel * 14336 + lrow * 128;
#pragma unroll
            for (int j = 0; j < 4; j++) {
                const int nt = warp + j * 16;
                if (nt < 56) {
                    uint32_t b0, b1, b2, b3;
                    ldsm4t(b0, b1, b2, b3, base + (nt >> 3) * 2048 + (((nt & 7) ^ (lrow & 7)) << 4));
                    mma16816(ag[j], a0, a2, b0, b1);
                    mma16816(au[j], a0, a2, b2, b3);
                }
            }
            __syncthreads();
            if (tid == 480) issue(it + FS_N);
        }
        if (g < 2) {
#pragma unroll
            for (int j = 0; j < 4; j++) {
                const int nt = warp + j * 16;
                if (nt < 56) {
#pragma unroll
                    for (int e = 0; e < 2; e++) {
                        const float gs = bfr(ag[j][e]), us = bfr(au[j][e]);
                        const float sg = bfr(gs / (1.f + __expf(-gs)));
                        sh[g * 448 + nt * 8 + t * 2 + e] = __float2bfloat16_rn(sg * us);
                    }
                }
            }
        }
        __syncthreads();
    }
    TL(2);
    {
        const uint32_t* shw = reinterpret_cast<const uint32_t*>(sh);
        float a[4][4];
#pragma unroll
        for (int j = 0; j < 4; j++) a[j][0] = a[j][1] = a[j][2] = a[j][3] = 0.f;
#pragma unroll 1
        for (int it = 32; it < 46; it++) {
            const int slot = it % FS_N;
            uint32_t af[4];
#pragma unroll
            for (int q = 0; q < 4; q++) af[q] = g < 2 ? shw[g * 224 + (it - 32) * 16 + q * 4 + t] : 0u;
            mbar_wait(bars + 8 * slot, (it / FS_N) & 1);
            const uint32_t base = sbase + slot * FS_BYTES + (warp >> 1) * 4096 + lane * 128;
#pragma unroll
            for (int j = 0; j < 4; j++) {
                const int u = (warp & 1) * 4 + j;
                uint32_t b0, b1, b2, b3;
                ldsm4t(b0, b1, b2, b3, base + ((u ^ (lane & 7)) << 4));
                mma16816(a[j], af[0], af[1], b0, b1);
                mma16816(a[j], af[2], af[3], b2, b3);
            }
            __syncthreads();
            if (tid == 480 && it + FS_N < 46) issue(it + FS_N);
        }
        if (g < 2) {
#pragma unroll
            for (int j = 0; j < 4; j++)
                *reinterpret_cast<float2*>(&g_ypart[c * 1024 + g * 512 + (warp * 4 + j) * 8 + t * 2]) = make_float2(a[j][0], a[j][1]);
        }
    }
    warp_arrive(C_FFN);
}

__device__ __forceinline__ void wgmma_n64(float (&d)[32], uint64_t da, uint64_t db, int scale_d) {
    asm volatile("{\n.reg .pred p;\nsetp.ne.b32 p, %34, 0;\n"
        "wgmma.mma_async.sync.aligned.m64n64k16.f32.bf16.bf16 "
        "{%0,%1,%2,%3,%4,%5,%6,%7,%8,%9,%10,%11,%12,%13,%14,%15,%16,%17,%18,%19,%20,%21,%22,%23,%24,%25,%26,%27,%28,%29,%30,%31}, "
        "%32, %33, p, 1, 1, 0, 1;\n}"
        : "+f"(d[0]), "+f"(d[1]), "+f"(d[2]), "+f"(d[3]), "+f"(d[4]), "+f"(d[5]), "+f"(d[6]), "+f"(d[7]),
          "+f"(d[8]), "+f"(d[9]), "+f"(d[10]), "+f"(d[11]), "+f"(d[12]), "+f"(d[13]), "+f"(d[14]), "+f"(d[15]),
          "+f"(d[16]), "+f"(d[17]), "+f"(d[18]), "+f"(d[19]), "+f"(d[20]), "+f"(d[21]), "+f"(d[22]), "+f"(d[23]),
          "+f"(d[24]), "+f"(d[25]), "+f"(d[26]), "+f"(d[27]), "+f"(d[28]), "+f"(d[29]), "+f"(d[30]), "+f"(d[31])
        : "l"(da), "l"(db), "r"(scale_d));
}

constexpr int G_ST = 4;
constexpr int G_STAGE = 16384 + 24576;
constexpr int SM_K = 65536, SM_V = 131072, SM_ONES = 196608, SM_MISC = 229376;
constexpr int FUSED_SMEM = SM_MISC + 2048;
constexpr int B_FULL = 0, B_EMPTY = 4, B_KV = 8, B_WO = 16, B_OA = 18, B_NUM = 22;

struct Maps { CUtensorMap xn, wqkv, o, wo, g, u, d; };

__global__ void __launch_bounds__(512, 1) fused_kernel(const __grid_constant__ Maps maps, const __nv_bfloat16* __restrict__ x,
                                                       const __nv_bfloat16* __restrict__ wr, __nv_bfloat16* __restrict__ out, float sc) {
    extern __shared__ __align__(1024) uint8_t smem[];
    const uint32_t sbase = smem_u32(smem);
    const int tid = threadIdx.x, warp = __shfl_sync(~0u, tid >> 5, 0), lane = tid & 31;
    const uint32_t bars = sbase + SM_MISC;
    TL(0);
    if (sbase & 1023u) __trap();
    if (blockIdx.x < 4) {
        ffn_block(blockIdx.x, smem, sbase, &maps.g, &maps.u, &maps.d);
        TL(3);
    } else {
        const int idx = blockIdx.x - 4;
        const int wg = warp >> 2;
        {
            const int nb = idx & 7;
            if (tid == 480) {
                for (int s = 0; s < G_ST; s++) { mbar_init(bars + 8 * (B_FULL + s), 2); mbar_init(bars + 8 * (B_EMPTY + s), 2); }
                for (int c = B_KV; c < B_NUM; c++) mbar_init(bars + 8 * c, 1);
                fence_barrier_init();
                for (int c = 0; c < G_ST; c++) {
                    mbar_expect_tx(bars + 8 * (B_FULL + c), 24576);
                    tma3d(sbase + c * G_STAGE + 16384, &maps.wqkv, bars + 8 * (B_FULL + c), c * 64, nb * 3);
                }
                map_prefetch(&maps.xn);
            }
        }
        {
            const int row = idx * 16 + warp;
            const uint4* xr = reinterpret_cast<const uint4*>(x + (size_t)row * DM);
            const uint4 a = xr[lane], b = xr[32 + lane];
            const uint4* wp = reinterpret_cast<const uint4*>(wr);
            const uint4 wa = wp[lane], wb = wp[32 + lane];
            {
                uint4* ones = reinterpret_cast<uint4*>(smem + SM_ONES);
#pragma unroll
                for (int i = 0; i < 4; i++) ones[tid + i * 512] = make_uint4(0x3f803f80u, 0x3f803f80u, 0x3f803f80u, 0x3f803f80u);
                fence_proxy_async();
            }
            __syncthreads();
            const uint32_t u[8] = {a.x, a.y, a.z, a.w, b.x, b.y, b.z, b.w};
            const uint32_t w[8] = {wa.x, wa.y, wa.z, wa.w, wb.x, wb.y, wb.z, wb.w};
            float f[16];
            float sum = 0.f;
#pragma unroll
            for (int i = 0; i < 8; i++) { f[2 * i] = bf_lo(u[i]); f[2 * i + 1] = bf_hi(u[i]); sum += f[2 * i] + f[2 * i + 1]; }
#pragma unroll
            for (int o = 16; o > 0; o >>= 1) sum += __shfl_xor_sync(~0u, sum, o);
            const float mean = sum * (1.f / DM);
            float sq = 0.f;
#pragma unroll
            for (int i = 0; i < 16; i++) { const float d = f[i] - mean; sq = fmaf(d, d, sq); }
#pragma unroll
            for (int o = 16; o > 0; o >>= 1) sq += __shfl_xor_sync(~0u, sq, o);
            const float mb_ = bfr(mean);
            const float vb = bfr(sq * (1.f / DM));
            const float rinv = 1.f / bfr(sqrtf(bfr(vb + 1e-5f)));
            uint32_t o[8];
            float r = 0.f;
#pragma unroll
            for (int i = 0; i < 8; i++) {
                const float d0 = bfr(f[2 * i] - mb_), d1 = bfr(f[2 * i + 1] - mb_);
                o[i] = packbf(d0 * rinv, d1 * rinv);
                r = fmaf(bf_lo(o[i]), bf_lo(w[i]), r);
                r = fmaf(bf_hi(o[i]), bf_hi(w[i]), r);
            }
            uint4* xo = reinterpret_cast<uint4*>(g_xn + (size_t)row * DM);
            xo[lane] = make_uint4(o[0], o[1], o[2], o[3]);
            xo[32 + lane] = make_uint4(o[4], o[5], o[6], o[7]);
#pragma unroll
            for (int of = 16; of > 0; of >>= 1) r += __shfl_xor_sync(~0u, r, of);
            if (lane == 0) g_r[row] = r;
            warp_arrive(C_LN + (idx >> 3));
        }
        TL(1);
        {
            const int nb = idx & 7, mb = idx >> 3;
            if (warp == 15) {
                for (int c = G_ST; c < 8; c++) {
                    const int s = c - G_ST;
                    mbar_wait(bars + 8 * (B_EMPTY + s), 0);
                    if (lane == 0) {
                        mbar_expect_tx(bars + 8 * (B_FULL + s), 24576);
                        tma3d(sbase + s * G_STAGE + 16384, &maps.wqkv, bars + 8 * (B_FULL + s), c * 64, nb * 3);
                    }
                    __syncwarp();
                }
            } else if (warp == 14) {
                flag_wait(C_LN + mb, 128);
                fence_proxy_async_all();
                for (int c = 0; c < 8; c++) {
                    const int s = c & (G_ST - 1);
                    if (c >= G_ST) mbar_wait(bars + 8 * (B_EMPTY + s), 0);
                    if (lane == 0) {
                        mbar_expect_tx(bars + 8 * (B_FULL + s), 16384);
                        tma3d(sbase + s * G_STAGE, &maps.xn, bars + 8 * (B_FULL + s), mb * 128, c);
                    }
                    __syncwarp();
                }
            } else if (wg < 2) {
                float acc[96];
#pragma unroll
                for (int i = 0; i < 96; i++) acc[i] = 0.f;
#pragma unroll 1
                for (int c = 0; c < 8; c++) {
                    const int s = c & (G_ST - 1);
                    const uint32_t st = sbase + s * G_STAGE;
                    mbar_wait(bars + 8 * (B_FULL + s), c >> 2);
                    if (c == 0) TL(2);
                    const uint64_t da = mkdesc(st + wg * 8192, 16, 1024, 1);
                    const uint64_t db = mkdesc(st + 16384, 8192, 1024, 1);
                    WG_FENCE();
#pragma unroll
                    for (int k = 0; k < 4; k++) wgmma_n192(acc, da + k * 2, db + k * 128, (c | k) != 0);
                    WG_COMMIT();
                    if (c <= G_ST) {
                        WG_WAIT(1);
                        if (c >= 1 && (tid & 127) == 0) mbar_arrive(bars + 8 * (B_EMPTY + c - 1));
                    }
                }
                WG_WAIT(0);
                nbar_arrive(6, 288);
                TL(3);
                const int g = lane >> 2, t = lane & 3;
                const int mt = mb * 8 + warp;
#pragma unroll
                for (int hh = 0; hh < 12; hh++) {
                    const int gh = nb * 12 + hh;
                    const float* a = &acc[hh * 8];
                    if (gh < 32) {
                        g_q[(gh * 128 + mt) * 32 + lane] = make_uint4(packbf(a[0], a[1]), packbf(a[2], a[3]), packbf(a[4], a[5]), packbf(a[6], a[7]));
                    } else {
                        uint32_t* dst = reinterpret_cast<uint32_t*>(gh < 64 ? g_k + (gh - 32) * 4096 : g_v + (gh - 64) * 4096);
                        const float ks = gh < 64 ? 5.421010862427522e-20f : 1.0f;
                        const int off = (mt * 16 + g) * 4 + t;
                        dst[off] = packbf(a[0] * ks, a[1] * ks);
                        dst[off + 32] = packbf(a[2] * ks, a[3] * ks);
                        dst[8192 + off] = packbf(a[4] * ks, a[5] * ks);
                        dst[8192 + off + 32] = packbf(a[6] * ks, a[7] * ks);
                    }
                }
                warp_arrive(C_QKV + nb);
            }
        }
        TL(4);
        uint32_t badmask = 0;
        const int head = idx >> 2, quarter = idx & 3, w4 = warp & 3;
        {
            if (warp == 15) {
                nbar_sync(6, 288);
                flag_wait(C_QKV + (32 + head) / 12, 128);
                flag_wait(C_QKV + (64 + head) / 12, 128);
                fence_proxy_async_all();
            }
            if (tid == 480) {
                const uint8_t* kp = reinterpret_cast<const uint8_t*>(g_k + head * 4096);
                const uint8_t* vp = reinterpret_cast<const uint8_t*>(g_v + head * 4096);
                for (int c = 0; c < 8; c++) {
                    const uint32_t bar = bars + 8 * (B_KV + c);
                    mbar_expect_tx(bar, 16384);
                    bulk_g2s(sbase + SM_K + c * 4096, kp + c * 4096, 4096, bar);
                    bulk_g2s(sbase + SM_K + 32768 + c * 4096, kp + 32768 + c * 4096, 4096, bar);
                    bulk_g2s(sbase + SM_V + c * 4096, vp + c * 4096, 4096, bar);
                    bulk_g2s(sbase + SM_V + 32768 + c * 4096, vp + 32768 + c * 4096, 4096, bar);
                }
                mbar_expect_tx(bars + 8 * B_WO, 65536);
                tma3d(sbase, &maps.wo, bars + 8 * B_WO, 0, (idx & 3) * 2);
                map_prefetch(&maps.o);
            }
            __syncwarp();
            flag_wait(C_QKV + head / 12, 128);
            const uint64_t kdesc0 = mkdesc(sbase + SM_K, 32768, 128, 0);
            const uint64_t vdesc0 = mkdesc(sbase + SM_V, 128, 32768, 0);
#pragma unroll 1
            for (int mt = 0; mt < 2; mt++) {
                const int m64 = quarter * 8 + mt * 4 + wg;
                uint32_t q[4];
                { const uint4 qq = __ldcg(&g_q[(head * 128 + m64 * 4 + w4) * 32 + lane]); q[0] = qq.x; q[1] = qq.y; q[2] = qq.z; q[3] = qq.w; }
                float s[32], s2[32], o[12];
#pragma unroll
                for (int i = 0; i < 12; i++) o[i] = 0.f;
                mbar_wait(bars + 8 * B_KV, 0);
                if (mt == 0) TL(5);
                WG_FENCE();
                qk64(s, q, kdesc0);
                WG_COMMIT(); WG_WAIT(0);
                float mx0 = -INFINITY, mx1 = -INFINITY;
#pragma unroll
                for (int i = 0; i < 8; i++) { mx0 = fmaxf(mx0, fmaxf(s[4 * i], s[4 * i + 1])); mx1 = fmaxf(mx1, fmaxf(s[4 * i + 2], s[4 * i + 3])); }
                mx0 = fmaxf(mx0, __shfl_xor_sync(~0u, mx0, 1)); mx0 = fmaxf(mx0, __shfl_xor_sync(~0u, mx0, 2));
                mx1 = fmaxf(mx1, __shfl_xor_sync(~0u, mx1, 1)); mx1 = fmaxf(mx1, __shfl_xor_sync(~0u, mx1, 2));
                float cm0 = -(ceilf(mx0 * QS) + SHIFT), cm1 = -(ceilf(mx1 * QS) + SHIFT);
                float cp0 = (cm0 + 127.f) * sc, cp1 = (cm1 + 127.f) * sc;
                asm volatile("" : "+f"(cm0), "+f"(cm1), "+f"(cp0), "+f"(cp1));
                uint64_t kd = kdesc0, vd = vdesc0;
                auto step = [&](float (&sc_)[32], float (&sn)[32]) {
                    kd += 64;
                    WG_FENCE();
                    qk64(sn, q, kd);
                    WG_COMMIT();
#pragma unroll
                    for (int kk = 0; kk < 4; kk++) {
                        const int i0 = kk * 2, i1 = kk * 2 + 1;
                        const uint32_t p0 = packbf(ex2(fmaf(sc_[4 * i0], QS, cm0)), ex2(fmaf(sc_[4 * i0 + 1], QS, cm0)));
                        const uint32_t p1 = packbf(ex2(fmaf(sc_[4 * i0 + 2], QS, cm1)), ex2(fmaf(sc_[4 * i0 + 3], QS, cm1)));
                        const uint32_t p2 = polyexp(fmaf(sc_[4 * i1], scq, cp0), fmaf(sc_[4 * i1 + 1], scq, cp0));
                        const uint32_t p3 = polyexp(fmaf(sc_[4 * i1 + 2], scq, cp1), fmaf(sc_[4 * i1 + 3], scq, cp1));
                        WG_FENCE();
                        pv24(o, p0, p1, p2, p3, vd);
                        vd += 16;
                    }
                    WG_COMMIT();
                    WG_WAIT(1);
                };
#pragma unroll 1
                for (int c = 0; c < 16; c++) {
                    if (mt == 0 && (c & 1) == 0 && c < 14) mbar_wait(bars + 8 * B_KV + 4 * c + 8, 0);
                    step(s, s2); step(s2, s);
                }
                WG_WAIT(0);
                bool bad = !(o[8] > 0.f) || !(o[10] > 0.f);
#pragma unroll
                for (int i = 0; i < 12; i++) bad = bad || !(fabsf(o[i]) <= 3.0e38f);
                uint32_t anybad;
                asm volatile("{\n.reg .pred p, q;\nsetp.ne.u32 p, %1, 0;\nbarrier.cta.red.or.pred q, %2, 128, p;\nselp.u32 %0, 1, 0, q;\n}"
                             : "=r"(anybad) : "r"((uint32_t)bad), "r"(wg + 1) : "memory");
                badmask |= anybad << mt;
                attn_store(o, head, m64, w4, lane);
            }
        }
        if (badmask) {
#pragma unroll 1
            for (int mt = 0; mt < 2; mt++) {
                if (!((badmask >> mt) & 1)) continue;
                const int m64 = quarter * 8 + mt * 4 + wg;
                uint32_t q[4];
                { const uint4 qq = __ldcg(&g_q[(head * 128 + m64 * 4 + w4) * 32 + lane]); q[0] = qq.x; q[1] = qq.y; q[2] = qq.z; q[3] = qq.w; }
                float o[12];
                attn_safe(o, q, mkdesc(sbase + SM_K, 32768, 128, 0), mkdesc(sbase + SM_V, 128, 32768, 0));
                attn_store(o, head, m64, w4, lane);
            }
        }
        if (warp == 15) nbar_sync(7, 512); else nbar_arrive(7, 512);
        if (tid == 480) {
            mbar_expect_tx(bars + 8 * (B_WO + 1), 65536);
            tma3d(sbase + 65536, &maps.wo, bars + 8 * (B_WO + 1), 256, (idx & 3) * 2);
        }
        __syncwarp();
        if (lane == 0) {
            asm volatile("fence.acq_rel.gpu;" ::: "memory");
            asm volatile("red.relaxed.gpu.global.add.u32 [%0], 1;" :: "l"(g_cnt + (C_O + quarter * 8 + 4 + wg) * 32) : "memory");
            asm volatile("red.relaxed.gpu.global.add.u32 [%0], 1;" :: "l"(g_cnt + (C_O + quarter * 8 + wg) * 32) : "memory");
        }
        TL(6);
        {
            const int nb = idx & 3, mb = idx >> 2;
            float* supd = reinterpret_cast<float*>(smem + SM_MISC + 512);
            if (warp == 15) {
                flag_wait(C_O + mb, 128);
                fence_proxy_async_all();
            }
            if (tid == 480) {
                for (int c = 0; c < 4; c++) {
                    mbar_expect_tx(bars + 8 * (B_OA + c), 16384);
                    tma3d(sbase + SM_V + c * 16384, &maps.o, bars + 8 * (B_OA + c), mb * 64, c * 2);
                }
            }
            if (wg < 2) {
                const int g = lane >> 2, t = lane & 3;
                const int row0 = mb * 64 + w4 * 16 + g;
                const int col0 = nb * 128 + wg * 64 + t * 2;
                flag_wait(C_LN + (mb >> 1), 128); flag_wait(C_FFN, 64);
                uint32_t xv[16], nv[16];
#pragma unroll
                for (int i = 0; i < 8; i++) {
                    xv[2 * i] = *reinterpret_cast<const uint32_t*>(x + (size_t)row0 * DM + col0 + i * 8);
                    xv[2 * i + 1] = *reinterpret_cast<const uint32_t*>(x + (size_t)(row0 + 8) * DM + col0 + i * 8);
                    nv[2 * i] = __ldcg(reinterpret_cast<const uint32_t*>(g_xn + (size_t)row0 * DM + col0 + i * 8));
                    nv[2 * i + 1] = __ldcg(reinterpret_cast<const uint32_t*>(g_xn + (size_t)(row0 + 8) * DM + col0 + i * 8));
                }
                const int sel0 = __ldcg(&g_sel[0]), sel1 = __ldcg(&g_sel[1]);
                {
                    const int which = tid >> 7, col = nb * 128 + (tid & 127);
                    const float y = __ldcg(&g_ypart[which * 512 + col]) + __ldcg(&g_ypart[1024 + which * 512 + col]) +
                                    __ldcg(&g_ypart[2048 + which * 512 + col]) + __ldcg(&g_ypart[3072 + which * 512 + col]);
                    supd[tid] = bfr(bfr(y) * __ldcg(&g_gate[which]));
                }
                asm volatile("bar.sync 5, 256;" ::: "memory");
                float acc[32];
#pragma unroll
                for (int i = 0; i < 32; i++) acc[i] = 0.f;
#pragma unroll 1
                for (int c = 0; c < 8; c++) {
                    if ((c & 3) == 0) mbar_wait(bars + 8 * (B_WO + (c >> 2)), 0);
                    if ((c & 1) == 0) mbar_wait(bars + 8 * (B_OA + (c >> 1)), 0);
                    if (c == 0) TL(7);
                    const uint64_t da = mkdesc(sbase + SM_V + c * 8192, 16, 1024, 1);
                    const uint64_t db = mkdesc(sbase + (c >> 2) * 65536 + wg * 32768 + (c & 3) * 8192, 8192, 1024, 1);
                    WG_FENCE();
#pragma unroll
                    for (int k = 0; k < 4; k++) wgmma_n64(acc, da + k * 2, db + k * 128, (c | k) != 0);
                    WG_COMMIT();
                }
                WG_WAIT(0);
                TL(8);
#pragma unroll
                for (int h = 0; h < 2; h++) {
                    const int row = row0 + h * 8;
                    const int which = row == sel0 ? 0 : (row == sel1 ? 1 : -1);
#pragma unroll
                    for (int i = 0; i < 8; i++) {
                        const int col = col0 + i * 8;
                        float b0 = bf_lo(nv[2 * i + h]), b1 = bf_hi(nv[2 * i + h]);
                        if (which >= 0) {
                            b0 = bfr(b0 + supd[which * 128 + col - nb * 128]); b1 = bfr(b1 + supd[which * 128 + col + 1 - nb * 128]);
                        }
                        const float t0 = bfr(bf_lo(xv[2 * i + h]) + bfr(acc[4 * i + 2 * h]));
                        const float t1 = bfr(bf_hi(xv[2 * i + h]) + bfr(acc[4 * i + 2 * h + 1]));
                        *reinterpret_cast<uint32_t*>(out + (size_t)row * DM + col) = packbf(t0 + b0, t1 + b1);
                    }
                }
            }
        }
        TL(9);
    }
    __syncthreads();
    if (tid == 0) {
        __threadfence();
        const unsigned tk = atomicAdd(&g_cnt[C_EXIT * 32], 1u);
        if (tk == gridDim.x - 1) {
            for (int i = 0; i < C_NUM; i++) g_cnt[i * 32] = 0u;
            __threadfence();
        }
    }
}

typedef CUresult (*EncodeFn)(CUtensorMap*, CUtensorMapDataType, cuuint32_t, void*, const cuuint64_t*, const cuuint64_t*,
                             const cuuint32_t*, const cuuint32_t*, CUtensorMapInterleave, CUtensorMapSwizzle,
                             CUtensorMapL2promotion, CUtensorMapFloatOOBfill);

void make_map(EncodeFn fn, CUtensorMap* m, const void* ptr, uint64_t cols, uint64_t rows, uint32_t box_rows, uint32_t box_chunks) {
    cuuint64_t dims[3] = {64, rows, cols / 64};
    cuuint64_t strides[2] = {cols * 2, 128};
    cuuint32_t box[3] = {64, box_rows, box_chunks};
    cuuint32_t es[3] = {1, 1, 1};
    fn(m, CU_TENSOR_MAP_DATA_TYPE_BFLOAT16, 3, const_cast<void*>(ptr), dims, strides, box, es, CU_TENSOR_MAP_INTERLEAVE_NONE,
       CU_TENSOR_MAP_SWIZZLE_128B, CU_TENSOR_MAP_L2_PROMOTION_L2_256B, CU_TENSOR_MAP_FLOAT_OOB_FILL_NONE);
}

}

extern "C" void kernel_launch(void* const* d_in, const int* in_sizes, int n_in, void* d_out, int out_size) {
    const __nv_bfloat16* x = (const __nv_bfloat16*)d_in[0];
    const __nv_bfloat16* wqkv = (const __nv_bfloat16*)d_in[1];
    const __nv_bfloat16* wo = (const __nv_bfloat16*)d_in[2];
    const __nv_bfloat16* wr = (const __nv_bfloat16*)d_in[4];
    const __nv_bfloat16* wgate = (const __nv_bfloat16*)d_in[5];
    const __nv_bfloat16* wup = (const __nv_bfloat16*)d_in[6];
    const __nv_bfloat16* wdown = (const __nv_bfloat16*)d_in[7];
    __nv_bfloat16* out = (__nv_bfloat16*)d_out;

    static EncodeFn enc = nullptr;
    static void* p_xn = nullptr; static void* p_o = nullptr;
    if (!enc) {
        void* fn = nullptr; cudaDriverEntryPointQueryResult qr;
        cudaGetDriverEntryPoint("cuTensorMapEncodeTiled", &fn, cudaEnableDefault, &qr);
        enc = (EncodeFn)fn;
        cudaGetSymbolAddress(&p_xn, g_xn);
        cudaGetSymbolAddress(&p_o, g_o);
        cudaFuncSetAttribute(fused_kernel, cudaFuncAttributeMaxDynamicSharedMemorySize, FUSED_SMEM);
    }
    Maps maps;
    make_map(enc, &maps.g, wgate, FF, DM, 16, 7);
    make_map(enc, &maps.u, wup, FF, DM, 16, 7);
    make_map(enc, &maps.d, wdown, DM, FF, 32, 8);
    make_map(enc, &maps.xn, p_xn, DM, S_LEN, 128, 1);
    make_map(enc, &maps.wqkv, wqkv, 3 * DM, DM, 64, 3);
    make_map(enc, &maps.o, p_o, DM, S_LEN, 64, 2);
    make_map(enc, &maps.wo, wo, DM, DM, 256, 2);

    union { uint32_t u; float f; } scu; scu.u = 128u;

    cudaLaunchConfig_t cfg = {};
    cfg.gridDim = dim3(132); cfg.blockDim = dim3(512); cfg.dynamicSmemBytes = FUSED_SMEM; cfg.stream = cudaStreamPerThread;
    cudaLaunchAttribute at[1];
    at[0].id = cudaLaunchAttributeCooperative;
    at[0].val.cooperative = 1;
    cfg.attrs = at; cfg.numAttrs = 1;
    cudaLaunchKernelEx(&cfg, fused_kernel, maps, x, wr, out, scu.f);
}
```

```cpp
#include <cuda_runtime.h>
#include <cuda_bf16.h>
#include <cuda.h>
#include <stdint.h>
#include <type_traits>

namespace {

constexpr int S_LEN = 2048;
constexpr int DM = 512;
constexpr int NH = 32;
constexpr int FF = 1792;

__device__ __align__(1024) __nv_bfloat16 g_xn[S_LEN * DM];
__device__ __align__(16) float g_r[S_LEN];
__device__ __align__(1024) uint4 g_q[NH * 128 * 32];
__device__ __align__(1024) uint4 g_k[NH * 4096];
__device__ __align__(1024) uint4 g_v[NH * 4096];
__device__ __align__(1024) __nv_bfloat16 g_o[S_LEN * DM];
__device__ __align__(16) float g_ypart[4 * 2 * DM];
__device__ int g_sel[2];
__device__ float g_gate[2];
constexpr int C_LN = 0, C_QKV = 16, C_O = 24, C_FFN = 56, C_EXIT = 57, C_NUM = 58;
__device__ unsigned g_cnt[C_NUM * 32];

#define TL(slot) do {} while (0)

__device__ __forceinline__ uint32_t smem_u32(const void* p) { return (uint32_t)__cvta_generic_to_shared(p); }
__device__ __forceinline__ void warp_arrive(int idx) {
    __syncwarp();
    if ((threadIdx.x & 31) == 0)
        asm volatile("red.release.gpu.global.add.u32 [%0], 1;" :: "l"(g_cnt + idx * 32) : "memory");
}
__device__ __forceinline__ void flag_release(int idx) {
    asm volatile("red.release.gpu.global.add.u32 [%0], 1;" :: "l"(g_cnt + idx * 32) : "memory");
}
__device__ __forceinline__ void nbar_arrive(int id, int cnt) { asm volatile("bar.arrive %0, %1;" :: "r"(id), "r"(cnt) : "memory"); }
__device__ __forceinline__ void nbar_sync(int id, int cnt) { asm volatile("bar.sync %0, %1;" :: "r"(id), "r"(cnt) : "memory"); }
__device__ __forceinline__ void flag_wait(int idx, unsigned target) {
    asm volatile("{\n.reg .pred p;\n.reg .u32 n, v;\nmov.u32 n, 0;\n"
                 "FW_%=:\n"
                 "ld.acquire.gpu.global.u32 v, [%0];\n"
                 "setp.ge.u32 p, v, %1;\n"
                 "@p bra FD_%=;\n"
                 "add.u32 n, n, 1;\n"
                 "setp.lt.u32 p, n, 16000000;\n"
                 "@p bra FW_%=;\n"
                 "trap;\n"
                 "FD_%=:\n}"
                 :: "l"(g_cnt + idx * 32), "r"(target) : "memory");
}
__device__ __forceinline__ void fence_proxy_async_all() { asm volatile("fence.proxy.async;" ::: "memory"); }
__device__ __forceinline__ void mbar_init(uint32_t bar, uint32_t cnt) {
    asm volatile("mbarrier.init.shared::cta.b64 [%0], %1;" :: "r"(bar), "r"(cnt) : "memory");
}
__device__ __forceinline__ void mbar_expect_tx(uint32_t bar, uint32_t bytes) {
    asm volatile("mbarrier.arrive.expect_tx.shared::cta.b64 _, [%0], %1;" :: "r"(bar), "r"(bytes) : "memory");
}
__device__ __forceinline__ void mbar_arrive(uint32_t bar) {
    asm volatile("mbarrier.arrive.shared::cta.b64 _, [%0];" :: "r"(bar) : "memory");
}
__device__ __forceinline__ void mbar_wait(uint32_t bar, uint32_t parity) {
    asm volatile("{\n.reg .pred p;\n.reg .u32 n;\nmov.u32 n, 0;\n"
                 "WAIT_%=:\n"
                 "mbarrier.try_wait.parity.shared::cta.b64 p, [%0], %1;\n"
                 "@p bra DONE_%=;\n"
                 "add.u32 n, n, 1;\n"
                 "setp.lt.u32 p, n, 4000000;\n"
                 "@p bra WAIT_%=;\n"
                 "trap;\n"
                 "DONE_%=:\n}"
                 :: "r"(bar), "r"(parity) : "memory");
}
__device__ __forceinline__ void fence_barrier_init() { asm volatile("fence.mbarrier_init.release.cluster;" ::: "memory"); }
__device__ __forceinline__ void fence_proxy_async() { asm volatile("fence.proxy.async.shared::cta;" ::: "memory"); }
__device__ __forceinline__ void tma3d(uint32_t dst, const CUtensorMap* map, uint32_t bar, int row, int chunk) {
    asm volatile("cp.async.bulk.tensor.3d.shared::cluster.global.mbarrier::complete_tx::bytes [%0], [%1, {%3, %4, %5}], [%2];"
                 :: "r"(dst), "l"((uint64_t)map), "r"(bar), "r"(0), "r"(row), "r"(chunk) : "memory");
}
__device__ __forceinline__ void bulk_g2s(uint32_t dst, const void* src, uint32_t bytes, uint32_t bar) {
    asm volatile("cp.async.bulk.shared::cluster.global.mbarrier::complete_tx::bytes [%0], [%1], %2, [%3];"
                 :: "r"(dst), "l"((uint64_t)src), "r"(bytes), "r"(bar) : "memory");
}
__device__ __forceinline__ void l2_prefetch(const void* src, uint32_t bytes) {
    asm volatile("cp.async.bulk.prefetch.L2.global [%0], %1;" :: "l"((uint64_t)src), "r"(bytes) : "memory");
}
__device__ __forceinline__ void map_prefetch(const CUtensorMap* m) {
    asm volatile("prefetch.tensormap [%0];" :: "l"((uint64_t)m) : "memory");
}
__device__ __forceinline__ uint64_t mkdesc(uint32_t addr, uint32_t lbo, uint32_t sbo, uint32_t swz) {
    return (uint64_t)((addr & 0x3FFFF) >> 4) | ((uint64_t)(lbo >> 4) << 16) | ((uint64_t)(sbo >> 4) << 32) | ((uint64_t)swz << 62);
}
#define WG_FENCE() asm volatile("wgmma.fence.sync.aligned;" ::: "memory")
#define WG_COMMIT() asm volatile("wgmma.commit_group.sync.aligned;" ::: "memory")
#define WG_WAIT(n) asm volatile("wgmma.wait_group.sync.aligned %0;" :: "n"(n) : "memory")

__device__ __forceinline__ float ex2(float x) { float y; asm("ex2.approx.ftz.f32 %0, %1;" : "=f"(y) : "f"(x)); return y; }
__device__ __forceinline__ uint32_t packbf(float lo, float hi) {
    uint32_t r; asm("cvt.rn.bf16x2.f32 %0, %1, %2;" : "=r"(r) : "f"(hi), "f"(lo)); return r;
}
__device__ __forceinline__ float bf_lo(uint32_t v) { return __uint_as_float(v << 16); }
__device__ __forceinline__ float bf_hi(uint32_t v) { return __uint_as_float(v & 0xffff0000u); }
__device__ __forceinline__ float bfr(float x) { return __bfloat162float(__float2bfloat16_rn(x)); }

__device__ __forceinline__ void wgmma_n192(float (&d)[96], uint64_t da, uint64_t db, int scale_d) {
    asm volatile("{\n.reg .pred p;\nsetp.ne.b32 p, %98, 0;\n"
        "wgmma.mma_async.sync.aligned.m64n192k16.f32.bf16.bf16 "
        "{%0,%1,%2,%3,%4,%5,%6,%7,%8,%9,%10,%11,%12,%13,%14,%15,%16,%17,%18,%19,%20,%21,%22,%23,"
        "%24,%25,%26,%27,%28,%29,%30,%31,%32,%33,%34,%35,%36,%37,%38,%39,%40,%41,%42,%43,%44,%45,%46,%47,"
        "%48,%49,%50,%51,%52,%53,%54,%55,%56,%57,%58,%59,%60,%61,%62,%63,%64,%65,%66,%67,%68,%69,%70,%71,"
        "%72,%73,%74,%75,%76,%77,%78,%79,%80,%81,%82,%83,%84,%85,%86,%87,%88,%89,%90,%91,%92,%93,%94,%95}, "
        "%96, %97, p, 1, 1, 0, 1;\n}"
        : "+f"(d[0]), "+f"(d[1]), "+f"(d[2]), "+f"(d[3]), "+f"(d[4]), "+f"(d[5]), "+f"(d[6]), "+f"(d[7]),
          "+f"(d[8]), "+f"(d[9]), "+f"(d[10]), "+f"(d[11]), "+f"(d[12]), "+f"(d[13]), "+f"(d[14]), "+f"(d[15]),
          "+f"(d[16]), "+f"(d[17]), "+f"(d[18]), "+f"(d[19]), "+f"(d[20]), "+f"(d[21]), "+f"(d[22]), "+f"(d[23]),
          "+f"(d[24]), "+f"(d[25]), "+f"(d[26]), "+f"(d[27]), "+f"(d[28]), "+f"(d[29]), "+f"(d[30]), "+f"(d[31]),
          "+f"(d[32]), "+f"(d[33]), "+f"(d[34]), "+f"(d[35]), "+f"(d[36]), "+f"(d[37]), "+f"(d[38]), "+f"(d[39]),
          "+f"(d[40]), "+f"(d[41]), "+f"(d[42]), "+f"(d[43]), "+f"(d[44]), "+f"(d[45]), "+f"(d[46]), "+f"(d[47]),
          "+f"(d[48]), "+f"(d[49]), "+f"(d[50]), "+f"(d[51]), "+f"(d[52]), "+f"(d[53]), "+f"(d[54]), "+f"(d[55]),
          "+f"(d[56]), "+f"(d[57]), "+f"(d[58]), "+f"(d[59]), "+f"(d[60]), "+f"(d[61]), "+f"(d[62]), "+f"(d[63]),
          "+f"(d[64]), "+f"(d[65]), "+f"(d[66]), "+f"(d[67]), "+f"(d[68]), "+f"(d[69]), "+f"(d[70]), "+f"(d[71]),
          "+f"(d[72]), "+f"(d[73]), "+f"(d[74]), "+f"(d[75]), "+f"(d[76]), "+f"(d[77]), "+f"(d[78]), "+f"(d[79]),
          "+f"(d[80]), "+f"(d[81]), "+f"(d[82]), "+f"(d[83]), "+f"(d[84]), "+f"(d[85]), "+f"(d[86]), "+f"(d[87]),
          "+f"(d[88]), "+f"(d[89]), "+f"(d[90]), "+f"(d[91]), "+f"(d[92]), "+f"(d[93]), "+f"(d[94]), "+f"(d[95])
        : "l"(da), "l"(db), "r"(scale_d));
}

constexpr float SHIFT = 90.0f;
constexpr float QS = 0.25f * 1.4426950408889634f * 18446744073709551616.0f;
constexpr float scq = 0.25f * 1.4426950408889634f * 3.3087224502121107e-24f;

__device__ __forceinline__ uint32_t polyexp(float lo, float hi) {
    uint32_t w, g, q, h;
    asm("cvt.pack.sat.s16.s32 %0, %1, %2;" : "=r"(w) : "r"(__float_as_uint(hi)), "r"(__float_as_uint(lo)));
    g = w & 0x007F007Fu;
    asm("fma.rn.f16x2 %0, %1, %2, %3;" : "=r"(q) : "r"(g), "r"(0xf940f940u), "r"(0x35513551u));
    asm("mul.rn.f16x2 %0, %1, %2;" : "=r"(h) : "r"(q), "r"(g));
    return w - h;
}
__device__ __forceinline__ void qk64(float (&s)[32], const uint32_t (&q)[4], uint64_t db) {
    asm volatile("wgmma.mma_async.sync.aligned.m64n64k16.f32.bf16.bf16 "
        "{%0,%1,%2,%3,%4,%5,%6,%7,%8,%9,%10,%11,%12,%13,%14,%15,%16,%17,%18,%19,%20,%21,%22,%23,%24,%25,%26,%27,%28,%29,%30,%31}, "
        "{%32,%33,%34,%35}, %36, 0, 1, 1, 0;"
        : "=f"(s[0]), "=f"(s[1]), "=f"(s[2]), "=f"(s[3]), "=f"(s[4]), "=f"(s[5]), "=f"(s[6]), "=f"(s[7]),
          "=f"(s[8]), "=f"(s[9]), "=f"(s[10]), "=f"(s[11]), "=f"(s[12]), "=f"(s[13]), "=f"(s[14]), "=f"(s[15]),
          "=f"(s[16]), "=f"(s[17]), "=f"(s[18]), "=f"(s[19]), "=f"(s[20]), "=f"(s[21]), "=f"(s[22]), "=f"(s[23]),
          "=f"(s[24]), "=f"(s[25]), "=f"(s[26]), "=f"(s[27]), "=f"(s[28]), "=f"(s[29]), "=f"(s[30]), "=f"(s[31])
        : "r"(q[0]), "r"(q[1]), "r"(q[2]), "r"(q[3]), "l"(db));
}
__device__ __forceinline__ void pv24(float (&o)[12], uint32_t a0, uint32_t a1, uint32_t a2, uint32_t a3, uint64_t db) {
    asm volatile("wgmma.mma_async.sync.aligned.m64n24k16.f32.bf16.bf16 "
        "{%0,%1,%2,%3,%4,%5,%6,%7,%8,%9,%10,%11}, {%12,%13,%14,%15}, %16, 1, 1, 1, 1;"
        : "+f"(o[0]), "+f"(o[1]), "+f"(o[2]), "+f"(o[3]), "+f"(o[4]), "+f"(o[5]), "+f"(o[6]), "+f"(o[7]),
          "+f"(o[8]), "+f"(o[9]), "+f"(o[10]), "+f"(o[11])
        : "r"(a0), "r"(a1), "r"(a2), "r"(a3), "l"(db));
}

__device__ __forceinline__ void attn_safe(float (&o)[12], const uint32_t (&q)[4], uint64_t kdesc0, uint64_t vdesc0) {
    float s[32];
    float m0 = -INFINITY, m1 = -INFINITY;
#pragma unroll
    for (int i = 0; i < 12; i++) o[i] = 0.f;
#pragma unroll 1
    for (int j = 0; j < 32; j++) {
        WG_FENCE();
        qk64(s, q, kdesc0 + (uint64_t)(j * 64));
        WG_COMMIT(); WG_WAIT(0);
        float n0 = m0, n1 = m1;
#pragma unroll
        for (int i = 0; i < 8; i++) { n0 = fmaxf(n0, fmaxf(s[4 * i], s[4 * i + 1])); n1 = fmaxf(n1, fmaxf(s[4 * i + 2], s[4 * i + 3])); }
        n0 = fmaxf(n0, __shfl_xor_sync(~0u, n0, 1)); n0 = fmaxf(n0, __shfl_xor_sync(~0u, n0, 2));
        n1 = fmaxf(n1, __shfl_xor_sync(~0u, n1, 1)); n1 = fmaxf(n1, __shfl_xor_sync(~0u, n1, 2));
        const float c0 = ex2((m0 - n0) * QS), c1 = ex2((m1 - n1) * QS);
        m0 = n0; m1 = n1;
#pragma unroll
        for (int i = 0; i < 3; i++) { o[4 * i] *= c0; o[4 * i + 1] *= c0; o[4 * i + 2] *= c1; o[4 * i + 3] *= c1; }
        uint32_t p[16];
#pragma unroll
        for (int i = 0; i < 8; i++) {
            p[2 * i] = packbf(ex2((s[4 * i] - m0) * QS), ex2((s[4 * i + 1] - m0) * QS));
            p[2 * i + 1] = packbf(ex2((s[4 * i + 2] - m1) * QS), ex2((s[4 * i + 3] - m1) * QS));
        }
        WG_FENCE();
#pragma unroll
        for (int kk = 0; kk < 4; kk++) pv24(o, p[4 * kk], p[4 * kk + 1], p[4 * kk + 2], p[4 * kk + 3], vdesc0 + (uint64_t)(j * 64 + kk * 16));
        WG_COMMIT(); WG_WAIT(0);
    }
}

__device__ __forceinline__ void attn_store(const float (&o)[12], int head, int m64, int warp, int lane) {
    const int g = lane >> 2, t = lane & 3;
    const int row = m64 * 64 + warp * 16 + g;
    const float i0 = 1.f / o[8], i1 = 1.f / o[10];
    uint32_t* p0 = reinterpret_cast<uint32_t*>(g_o + (size_t)row * DM + head * 16 + t * 2);
    uint32_t* p1 = reinterpret_cast<uint32_t*>(g_o + (size_t)(row + 8) * DM + head * 16 + t * 2);
    p0[0] = packbf(o[0] * i0, o[1] * i0); p0[4] = packbf(o[4] * i0, o[5] * i0);
    p1[0] = packbf(o[2] * i1, o[3] * i1); p1[4] = packbf(o[6] * i1, o[7] * i1);
}

constexpr int FS_N = 4;
constexpr int FS_BYTES = 32768;
__device__ __forceinline__ void ldsm4t(uint32_t& r0, uint32_t& r1, uint32_t& r2, uint32_t& r3, uint32_t addr) {
    asm volatile("ldmatrix.sync.aligned.m8n8.x4.trans.shared.b16 {%0,%1,%2,%3}, [%4];" : "=r"(r0), "=r"(r1), "=r"(r2), "=r"(r3) : "r"(addr) : "memory");
}
__device__ __forceinline__ void mma16816(float (&d)[4], uint32_t a0, uint32_t a2, uint32_t b0, uint32_t b1) {
    asm volatile("mma.sync.aligned.m16n8k16.row.col.f32.bf16.bf16.f32 {%0,%1,%2,%3}, {%4,%5,%6,%5}, {%7,%8}, {%0,%1,%2,%3};"
                 : "+f"(d[0]), "+f"(d[1]), "+f"(d[2]), "+f"(d[3]) : "r"(a0), "r"(0u), "r"(a2), "r"(b0), "r"(b1));
}
__device__ void ffn_block(int c, uint8_t* smem, uint32_t sbase, const CUtensorMap* mapG, const CUtensorMap* mapU, const CUtensorMap* mapD) {
    const int tid = threadIdx.x, warp = tid >> 5, lane = tid & 31;
    uint32_t* sx = reinterpret_cast<uint32_t*>(smem + FS_N * FS_BYTES);
    __nv_bfloat16* sh = reinterpret_cast<__nv_bfloat16*>(sx + 512);
    const uint32_t bars = sbase + FS_N * FS_BYTES + 8192;
    float* tv = reinterpret_cast<float*>(smem + FS_N * FS_BYTES + 4096);
    int* ti = reinterpret_cast<int*>(tv + 32);
    int* ssel = ti + 32;
    auto issue = [&](int item) {
        const int slot = item % FS_N;
        const uint32_t dst = sbase + slot * FS_BYTES, bar = bars + 8 * slot;
        mbar_expect_tx(bar, item < 32 ? 28672 : 32768);
        if (item < 32) {
            tma3d(dst, mapG, bar, item * 16, c * 7);
            tma3d(dst + 14336, mapU, bar, item * 16, c * 7);
        } else {
            tma3d(dst, mapD, bar, c * 448 + (item - 32) * 32, 0);
        }
    };
    if (tid == 0) {
        for (int i = 0; i < FS_N; i++) mbar_init(bars + 8 * i, 1);
        fence_barrier_init();
        for (int i = 0; i < FS_N; i++) issue(i);
    }
    flag_wait(C_LN + warp, 8);
    __syncthreads();
    float b1 = -INFINITY, b2 = -INFINITY; int i1 = 0x7fffffff, i2 = 0x7fffffff;
    auto push = [&](float v, int i) {
        if (v > b1 || (v == b1 && i < i1)) { b2 = b1; i2 = i1; b1 = v; i1 = i; }
        else if (v > b2 || (v == b2 && i < i2)) { b2 = v; i2 = i; }
    };
    {
        const float4 rv = __ldcg(reinterpret_cast<const float4*>(g_r) + tid);
        push(rv.x, 4 * tid); push(rv.y, 4 * tid + 1); push(rv.z, 4 * tid + 2); push(rv.w, 4 * tid + 3);
    }
#pragma unroll
    for (int o = 16; o > 0; o >>= 1) {
        float v1 = __shfl_xor_sync(~0u, b1, o), v2 = __shfl_xor_sync(~0u, b2, o);
        int j1 = __shfl_xor_sync(~0u, i1, o), j2 = __shfl_xor_sync(~0u, i2, o);
        push(v1, j1); push(v2, j2);
    }
    if (lane == 0) { tv[2 * warp] = b1; ti[2 * warp] = i1; tv[2 * warp + 1] = b2; ti[2 * warp + 1] = i2; }
    __syncthreads();
    if (warp == 1) {
        b1 = tv[lane]; i1 = ti[lane]; b2 = -INFINITY; i2 = 0x7fffffff;
#pragma unroll
        for (int o = 16; o > 0; o >>= 1) {
            float v1 = __shfl_xor_sync(~0u, b1, o), v2 = __shfl_xor_sync(~0u, b2, o);
            int j1 = __shfl_xor_sync(~0u, i1, o), j2 = __shfl_xor_sync(~0u, i2, o);
            push(v1, j1); push(v2, j2);
        }
        if (lane == 0) {
            i1 = min(max(i1, 0), S_LEN - 1); i2 = min(max(i2, 0), S_LEN - 1);
            ssel[0] = i1; ssel[1] = i2;
            if (c == 0) {
                g_sel[0] = i1; g_sel[1] = i2;
                g_gate[0] = bfr(1.f / (1.f + __expf(-bfr(b1))));
                g_gate[1] = bfr(1.f / (1.f + __expf(-bfr(b2))));
            }
        }
    }
    __syncthreads();
    sx[tid] = __ldcg(reinterpret_cast<const uint32_t*>(g_xn + (size_t)ssel[tid >> 8] * DM + (tid & 255) * 2));
    __syncthreads();
    TL(1);
    const int g = lane >> 2, t = lane & 3;
    const int lrow = lane & 15, lsel = lane >> 4;
    {
        float ag[4][4], au[4][4];
#pragma unroll
        for (int j = 0; j < 4; j++) { ag[j][0] = ag[j][1] = ag[j][2] = ag[j][3] = 0.f; au[j][0] = au[j][1] = au[j][2] = au[j][3] = 0.f; }
#pragma unroll 1
        for (int it = 0; it < 32; it++) {
            const int slot = it % FS_N;
            const uint32_t a0 = g < 2 ? sx[g * 256 + it * 8 + t] : 0u, a2 = g < 2 ? sx[g * 256 + it * 8 + 4 + t] : 0u;
            mbar_wait(bars + 8 * slot, (it / FS_N) & 1);
            const uint32_t base = sbase + slot * FS_BYTES + lsel * 14336 + lrow * 128;
#pragma unroll
            for (int j = 0; j < 4; j++) {
                const int nt = warp + j * 16;
                if (nt < 56) {
                    uint32_t b0, b1, b2, b3;
                    ldsm4t(b0, b1, b2, b3, base + (nt >> 3) * 2048 + (((nt & 7) ^ (lrow & 7)) << 4));
                    mma16816(ag[j], a0, a2, b0, b1);
                    mma16816(au[j], a0, a2, b2, b3);
                }
            }
            __syncthreads();
            if (tid == 480) issue(it + FS_N);
        }
        if (g < 2) {
#pragma unroll
            for (int j = 0; j < 4; j++) {
                const int nt = warp + j * 16;
                if (nt < 56) {
#pragma unroll
                    for (int e = 0; e < 2; e++) {
                        const float gs = bfr(ag[j][e]), us = bfr(au[j][e]);
                        const float sg = bfr(gs / (1.f + __expf(-gs)));
                        sh[g * 448 + nt * 8 + t * 2 + e] = __float2bfloat16_rn(sg * us);
                    }
                }
            }
        }
        __syncthreads();
    }
    TL(2);
    {
        const uint32_t* shw = reinterpret_cast<const uint32_t*>(sh);
        float a[4][4];
#pragma unroll
        for (int j = 0; j < 4; j++) a[j][0] = a[j][1] = a[j][2] = a[j][3] = 0.f;
#pragma unroll 1
        for (int it = 32; it < 46; it++) {
            const int slot = it % FS_N;
            uint32_t af[4];
#pragma unroll
            for (int q = 0; q < 4; q++) af[q] = g < 2 ? shw[g * 224 + (it - 32) * 16 + q * 4 + t] : 0u;
            mbar_wait(bars + 8 * slot, (it / FS_N) & 1);
            const uint32_t base = sbase + slot * FS_BYTES + (warp >> 1) * 4096 + lane * 128;
#pragma unroll
            for (int j = 0; j < 4; j++) {
                const int u = (warp & 1) * 4 + j;
                uint32_t b0, b1, b2, b3;
                ldsm4t(b0, b1, b2, b3, base + ((u ^ (lane & 7)) << 4));
                mma16816(a[j], af[0], af[1], b0, b1);
                mma16816(a[j], af[2], af[3], b2, b3);
            }
            __syncthreads();
            if (tid == 480 && it + FS_N < 46) issue(it + FS_N);
        }
        if (g < 2) {
#pragma unroll
            for (int j = 0; j < 4; j++)
                *reinterpret_cast<float2*>(&g_ypart[c * 1024 + g * 512 + (warp * 4 + j) * 8 + t * 2]) = make_float2(a[j][0], a[j][1]);
        }
    }
    warp_arrive(C_FFN);
}

__device__ __forceinline__ void wgmma_n32(float (&d)[16], uint64_t da, uint64_t db, int scale_d) {
    asm volatile("{\n.reg .pred p;\nsetp.ne.b32 p, %18, 0;\n"
        "wgmma.mma_async.sync.aligned.m64n32k16.f32.bf16.bf16 "
        "{%0,%1,%2,%3,%4,%5,%6,%7,%8,%9,%10,%11,%12,%13,%14,%15}, "
        "%16, %17, p, 1, 1, 0, 1;\n}"
        : "+f"(d[0]), "+f"(d[1]), "+f"(d[2]), "+f"(d[3]), "+f"(d[4]), "+f"(d[5]), "+f"(d[6]), "+f"(d[7]),
          "+f"(d[8]), "+f"(d[9]), "+f"(d[10]), "+f"(d[11]), "+f"(d[12]), "+f"(d[13]), "+f"(d[14]), "+f"(d[15])
        : "l"(da), "l"(db), "r"(scale_d));
}

constexpr int G_ST = 4;
constexpr int G_STAGE = 16384 + 24576;
constexpr int SM_K = 65536, SM_V = 131072, SM_ONES = 196608, SM_MISC = 229376;
constexpr int FUSED_SMEM = SM_MISC + 2048;
constexpr int B_FULL = 0, B_EMPTY = 4, B_KV = 8, B_WO = 16, B_OA = 18, B_NUM = 22;

struct Maps { CUtensorMap xn, wqkv, o, wo, g, u, d; };

__global__ void __launch_bounds__(512, 1) fused_kernel(const __grid_constant__ Maps maps, const __nv_bfloat16* __restrict__ x,
                                                       const __nv_bfloat16* __restrict__ wr, __nv_bfloat16* __restrict__ out, float sc) {
    extern __shared__ __align__(1024) uint8_t smem[];
    const uint32_t sbase = smem_u32(smem);
    const int tid = threadIdx.x, warp = __shfl_sync(~0u, tid >> 5, 0), lane = tid & 31;
    const uint32_t bars = sbase + SM_MISC;
    TL(0);
    if (sbase & 1023u) __trap();
    if (blockIdx.x < 4) {
        ffn_block(blockIdx.x, smem, sbase, &maps.g, &maps.u, &maps.d);
        TL(3);
    } else {
        const int idx = blockIdx.x - 4;
        const int wg = warp >> 2;
        {
            const int row = idx * 16 + warp;
            const uint4* xr = reinterpret_cast<const uint4*>(x + (size_t)row * DM);
            const uint4 a = xr[lane], b = xr[32 + lane];
            const uint4* wp = reinterpret_cast<const uint4*>(wr);
            const uint4 wa = wp[lane], wb = wp[32 + lane];
            if (tid == 480) {
                for (int s = 0; s < G_ST; s++) { mbar_init(bars + 8 * (B_FULL + s), 2); mbar_init(bars + 8 * (B_EMPTY + s), 2); }
                for (int c = B_KV; c < B_NUM; c++) mbar_init(bars + 8 * c, 1);
                fence_barrier_init();
                for (int c = 0; c < G_ST; c++) {
                    mbar_expect_tx(bars + 8 * (B_FULL + c), 24576);
                    tma3d(sbase + c * G_STAGE + 16384, &maps.wqkv, bars + 8 * (B_FULL + c), c * 64, (idx & 7) * 3);
                }
                map_prefetch(&maps.xn);
            }
            __syncwarp();
            const uint32_t u[8] = {a.x, a.y, a.z, a.w, b.x, b.y, b.z, b.w};
            const uint32_t w[8] = {wa.x, wa.y, wa.z, wa.w, wb.x, wb.y, wb.z, wb.w};
            float f[16];
            float sum = 0.f;
#pragma unroll
            for (int i = 0; i < 8; i++) { f[2 * i] = bf_lo(u[i]); f[2 * i + 1] = bf_hi(u[i]); sum += f[2 * i] + f[2 * i + 1]; }
#pragma unroll
            for (int o = 16; o > 0; o >>= 1) sum += __shfl_xor_sync(~0u, sum, o);
            const float mean = sum * (1.f / DM);
            float sq = 0.f;
#pragma unroll
            for (int i = 0; i < 16; i++) { const float d = f[i] - mean; sq = fmaf(d, d, sq); }
#pragma unroll
            for (int o = 16; o > 0; o >>= 1) sq += __shfl_xor_sync(~0u, sq, o);
            const float mb_ = bfr(mean);
            const float vb = bfr(sq * (1.f / DM));
            const float rinv = 1.f / bfr(sqrtf(bfr(vb + 1e-5f)));
            uint32_t o[8];
            float r = 0.f;
#pragma unroll
            for (int i = 0; i < 8; i++) {
                const float d0 = bfr(f[2 * i] - mb_), d1 = bfr(f[2 * i + 1] - mb_);
                o[i] = packbf(d0 * rinv, d1 * rinv);
                r = fmaf(bf_lo(o[i]), bf_lo(w[i]), r);
                r = fmaf(bf_hi(o[i]), bf_hi(w[i]), r);
            }
            uint4* xo = reinterpret_cast<uint4*>(g_xn + (size_t)row * DM);
            xo[lane] = make_uint4(o[0], o[1], o[2], o[3]);
            xo[32 + lane] = make_uint4(o[4], o[5], o[6], o[7]);
#pragma unroll
            for (int of = 16; of > 0; of >>= 1) r += __shfl_xor_sync(~0u, r, of);
            if (lane == 0) g_r[row] = r;
        }
        __syncthreads();
        if (tid == 416) flag_release(C_LN + (idx >> 3));
        if (warp == 12 || warp == 11) {
            uint4* ones = reinterpret_cast<uint4*>(smem + SM_ONES);
#pragma unroll 8
            for (int i = tid - 352; i < 2048; i += 64) ones[i] = make_uint4(0x3f803f80u, 0x3f803f80u, 0x3f803f80u, 0x3f803f80u);
            fence_proxy_async();
        }
        TL(1);
        {
            const int nb = idx & 7, mb = idx >> 3;
            if (warp == 15) {
                for (int c = G_ST; c < 8; c++) {
                    const int s = c - G_ST;
                    mbar_wait(bars + 8 * (B_EMPTY + s), 0);
                    if (lane == 0) {
                        mbar_expect_tx(bars + 8 * (B_FULL + s), 24576);
                        tma3d(sbase + s * G_STAGE + 16384, &maps.wqkv, bars + 8 * (B_FULL + s), c * 64, nb * 3);
                    }
                    __syncwarp();
                }
            } else if (warp == 14) {
                flag_wait(C_LN + mb, 8);
                fence_proxy_async_all();
                for (int c = 0; c < 8; c++) {
                    const int s = c & (G_ST - 1);
                    if (c >= G_ST) mbar_wait(bars + 8 * (B_EMPTY + s), 0);
                    if (lane == 0) {
                        mbar_expect_tx(bars + 8 * (B_FULL + s), 16384);
                        tma3d(sbase + s * G_STAGE, &maps.xn, bars + 8 * (B_FULL + s), mb * 128, c);
                    }
                    __syncwarp();
                }
            } else if (wg < 2) {
                float acc[96];
#pragma unroll
                for (int i = 0; i < 96; i++) acc[i] = 0.f;
#pragma unroll 1
                for (int c = 0; c < 8; c++) {
                    const int s = c & (G_ST - 1);
                    const uint32_t st = sbase + s * G_STAGE;
                    mbar_wait(bars + 8 * (B_FULL + s), c >> 2);
                    if (c == 0) TL(2);
                    const uint64_t da = mkdesc(st + wg * 8192, 16, 1024, 1);
                    const uint64_t db = mkdesc(st + 16384, 8192, 1024, 1);
                    WG_FENCE();
#pragma unroll
                    for (int k = 0; k < 4; k++) wgmma_n192(acc, da + k * 2, db + k * 128, (c | k) != 0);
                    WG_COMMIT();
                    if (c <= G_ST) {
                        WG_WAIT(1);
                        if (c >= 1 && (tid & 127) == 0) mbar_arrive(bars + 8 * (B_EMPTY + c - 1));
                    }
                }
                WG_WAIT(0);
                nbar_arrive(6, 288);
                TL(3);
                const int g = lane >> 2, t = lane & 3;
                const int mt = mb * 8 + warp;
#pragma unroll
                for (int hh = 0; hh < 12; hh++) {
                    const int gh = nb * 12 + hh;
                    const float* a = &acc[hh * 8];
                    if (gh < 32) {
                        g_q[(gh * 128 + mt) * 32 + lane] = make_uint4(packbf(a[0], a[1]), packbf(a[2], a[3]), packbf(a[4], a[5]), packbf(a[6], a[7]));
                    } else {
                        uint32_t* dst = reinterpret_cast<uint32_t*>(gh < 64 ? g_k + (gh - 32) * 4096 : g_v + (gh - 64) * 4096);
                        const float ks = gh < 64 ? 5.421010862427522e-20f : 1.0f;
                        const int off = (mt * 16 + g) * 4 + t;
                        dst[off] = packbf(a[0] * ks, a[1] * ks);
                        dst[off + 32] = packbf(a[2] * ks, a[3] * ks);
                        dst[8192 + off] = packbf(a[4] * ks, a[5] * ks);
                        dst[8192 + off + 32] = packbf(a[6] * ks, a[7] * ks);
                    }
                }
                TL(10);
                nbar_sync(8, 256);
                if (tid == 0) flag_release(C_QKV + nb);
            }
        }
        TL(4);
        uint32_t badmask = 0;
        const int head = idx >> 2, quarter = idx & 3, w4 = warp & 3;
        {
            if (warp == 15) {
                nbar_sync(6, 288);
                flag_wait(C_QKV + (32 + head) / 12, 16);
                flag_wait(C_QKV + (64 + head) / 12, 16);
                fence_proxy_async_all();
            }
            if (tid == 480) {
                const uint8_t* kp = reinterpret_cast<const uint8_t*>(g_k + head * 4096);
                const uint8_t* vp = reinterpret_cast<const uint8_t*>(g_v + head * 4096);
                for (int c = 0; c < 8; c++) {
                    const uint32_t bar = bars + 8 * (B_KV + c);
                    mbar_expect_tx(bar, 16384);
                    bulk_g2s(sbase + SM_K + c * 4096, kp + c * 4096, 4096, bar);
                    bulk_g2s(sbase + SM_K + 32768 + c * 4096, kp + 32768 + c * 4096, 4096, bar);
                    bulk_g2s(sbase + SM_V + c * 4096, vp + c * 4096, 4096, bar);
                    bulk_g2s(sbase + SM_V + 32768 + c * 4096, vp + 32768 + c * 4096, 4096, bar);
                }
                mbar_expect_tx(bars + 8 * B_WO, 65536);
                tma3d(sbase, &maps.wo, bars + 8 * B_WO, 0, idx & 7);
                tma3d(sbase + 32768, &maps.wo, bars + 8 * B_WO, 256, idx & 7);
                map_prefetch(&maps.o);
            }
            __syncwarp();
            flag_wait(C_QKV + head / 12, 16);
            __syncthreads();
            const uint64_t kdesc0 = mkdesc(sbase + SM_K, 32768, 128, 0);
            const uint64_t vdesc0 = mkdesc(sbase + SM_V, 128, 32768, 0);
#pragma unroll 1
            for (int mt = 0; mt < 2; mt++) {
                const int m64 = quarter * 8 + mt * 4 + wg;
                uint32_t q[4];
                { const uint4 qq = __ldcg(&g_q[(head * 128 + m64 * 4 + w4) * 32 + lane]); q[0] = qq.x; q[1] = qq.y; q[2] = qq.z; q[3] = qq.w; }
                float s[32], s2[32], o[12];
#pragma unroll
                for (int i = 0; i < 12; i++) o[i] = 0.f;
                mbar_wait(bars + 8 * B_KV, 0);
                if (mt == 0) TL(5);
                WG_FENCE();
                qk64(s, q, kdesc0);
                WG_COMMIT(); WG_WAIT(0);
                float mx0 = -INFINITY, mx1 = -INFINITY;
#pragma unroll
                for (int i = 0; i < 8; i++) { mx0 = fmaxf(mx0, fmaxf(s[4 * i], s[4 * i + 1])); mx1 = fmaxf(mx1, fmaxf(s[4 * i + 2], s[4 * i + 3])); }
                mx0 = fmaxf(mx0, __shfl_xor_sync(~0u, mx0, 1)); mx0 = fmaxf(mx0, __shfl_xor_sync(~0u, mx0, 2));
                mx1 = fmaxf(mx1, __shfl_xor_sync(~0u, mx1, 1)); mx1 = fmaxf(mx1, __shfl_xor_sync(~0u, mx1, 2));
                if (mt == 1 && !badmask) {
                    nbar_sync(wg + 1, 128);
                    if ((tid & 127) == 0) flag_release(C_O + m64 - 4);
                }
                float cm0 = -(ceilf(mx0 * QS) + SHIFT), cm1 = -(ceilf(mx1 * QS) + SHIFT);
                float cp0 = (cm0 + 127.f) * sc, cp1 = (cm1 + 127.f) * sc;
                asm volatile("" : "+f"(cm0), "+f"(cm1), "+f"(cp0), "+f"(cp1));
                uint64_t kd = kdesc0, vd = vdesc0;
                auto step = [&](float (&sc_)[32], float (&sn)[32]) {
                    kd += 64;
                    WG_FENCE();
                    qk64(sn, q, kd);
                    WG_COMMIT();
#pragma unroll
                    for (int kk = 0; kk < 4; kk++) {
                        const int i0 = kk * 2, i1 = kk * 2 + 1;
                        const uint32_t p0 = packbf(ex2(fmaf(sc_[4 * i0], QS, cm0)), ex2(fmaf(sc_[4 * i0 + 1], QS, cm0)));
                        const uint32_t p1 = packbf(ex2(fmaf(sc_[4 * i0 + 2], QS, cm1)), ex2(fmaf(sc_[4 * i0 + 3], QS, cm1)));
                        const uint32_t p2 = polyexp(fmaf(sc_[4 * i1], scq, cp0), fmaf(sc_[4 * i1 + 1], scq, cp0));
                        const uint32_t p3 = polyexp(fmaf(sc_[4 * i1 + 2], scq, cp1), fmaf(sc_[4 * i1 + 3], scq, cp1));
                        WG_FENCE();
                        pv24(o, p0, p1, p2, p3, vd);
                        vd += 16;
                    }
                    WG_COMMIT();
                    WG_WAIT(1);
                };
#pragma unroll 1
                for (int c = 0; c < 16; c++) {
                    if (mt == 0 && (c & 1) == 0 && c < 14) mbar_wait(bars + 8 * B_KV + 4 * c + 8, 0);
                    step(s, s2); step(s2, s);
                }
                WG_WAIT(0);
                bool bad = !(o[8] > 0.f) || !(o[10] > 0.f);
#pragma unroll
                for (int i = 0; i < 12; i++) bad = bad || !(fabsf(o[i]) <= 3.0e38f);
                uint32_t anybad;
                asm volatile("{\n.reg .pred p, q;\nsetp.ne.u32 p, %1, 0;\nbarrier.cta.red.or.pred q, %2, 128, p;\nselp.u32 %0, 1, 0, q;\n}"
                             : "=r"(anybad) : "r"((uint32_t)bad), "r"(wg + 1) : "memory");
                badmask |= __shfl_sync(~0u, anybad, 0) << mt;
                attn_store(o, head, m64, w4, lane);
            }
        }
        if (badmask) {
#pragma unroll 1
            for (int mt = 0; mt < 2; mt++) {
                if (!((badmask >> mt) & 1)) continue;
                const int m64 = quarter * 8 + mt * 4 + wg;
                uint32_t q[4];
                { const uint4 qq = __ldcg(&g_q[(head * 128 + m64 * 4 + w4) * 32 + lane]); q[0] = qq.x; q[1] = qq.y; q[2] = qq.z; q[3] = qq.w; }
                float o[12];
                attn_safe(o, q, mkdesc(sbase + SM_K, 32768, 128, 0), mkdesc(sbase + SM_V, 128, 32768, 0));
                attn_store(o, head, m64, w4, lane);
            }
        }
        nbar_sync(wg + 1, 128);
        if ((tid & 127) == 32) {
            asm volatile("fence.acq_rel.gpu;" ::: "memory");
            asm volatile("red.relaxed.gpu.global.add.u32 [%0], 1;" :: "l"(g_cnt + (C_O + quarter * 8 + 4 + wg) * 32) : "memory");
            if (badmask & 1) asm volatile("red.relaxed.gpu.global.add.u32 [%0], 1;" :: "l"(g_cnt + (C_O + quarter * 8 + wg) * 32) : "memory");
        }
        TL(6);
        {
            const int nb = idx & 7, jb = idx >> 3;
            const int mbe = (jb >> 2) * 8 + (jb & 3);
            float* supd = reinterpret_cast<float*>(smem + SM_MISC + 512);
            if (warp == 15) nbar_sync(7, 512); else nbar_arrive(7, 512);
            if (warp == 15) {
                flag_wait(C_O + mbe, 32);
                fence_proxy_async_all();
                if (lane == 0) {
                    for (int c = 0; c < 2; c++) {
                        mbar_expect_tx(bars + 8 * (B_OA + c), 32768);
                        tma3d(sbase + SM_K + c * 32768, &maps.o, bars + 8 * (B_OA + c), mbe * 64, c * 4);
                    }
                }
                __syncwarp();
                flag_wait(C_O + mbe + 4, 32);
                fence_proxy_async_all();
                if (lane == 0) {
                    for (int c = 0; c < 2; c++) {
                        mbar_expect_tx(bars + 8 * (B_OA + 2 + c), 32768);
                        tma3d(sbase + SM_V + c * 32768, &maps.o, bars + 8 * (B_OA + 2 + c), (mbe + 4) * 64, c * 4);
                    }
                }
                __syncwarp();
            }
            const int late = wg >> 1, nh = wg & 1;
            const int mb = mbe + late * 4;
            const int g = lane >> 2, t = lane & 3;
            const int row0 = mb * 64 + w4 * 16 + g;
            const int col0 = nb * 64 + nh * 32 + t * 2;
            flag_wait(C_LN + (mb >> 1), 8); flag_wait(C_FFN, 64);
            uint32_t xv[8], nv[8];
#pragma unroll
            for (int i = 0; i < 4; i++) {
                xv[2 * i] = *reinterpret_cast<const uint32_t*>(x + (size_t)row0 * DM + col0 + i * 8);
                xv[2 * i + 1] = *reinterpret_cast<const uint32_t*>(x + (size_t)(row0 + 8) * DM + col0 + i * 8);
                nv[2 * i] = __ldcg(reinterpret_cast<const uint32_t*>(g_xn + (size_t)row0 * DM + col0 + i * 8));
                nv[2 * i + 1] = __ldcg(reinterpret_cast<const uint32_t*>(g_xn + (size_t)(row0 + 8) * DM + col0 + i * 8));
            }
            const int sel0 = __ldcg(&g_sel[0]), sel1 = __ldcg(&g_sel[1]);
            if (tid < 128) {
                const int which = tid >> 6, col = nb * 64 + (tid & 63);
                const float y = __ldcg(&g_ypart[which * 512 + col]) + __ldcg(&g_ypart[1024 + which * 512 + col]) +
                                __ldcg(&g_ypart[2048 + which * 512 + col]) + __ldcg(&g_ypart[3072 + which * 512 + col]);
                supd[tid] = bfr(bfr(y) * __ldcg(&g_gate[which]));
            }
            float acc[16];
#pragma unroll
            for (int i = 0; i < 16; i++) acc[i] = 0.f;
            mbar_wait(bars + 8 * B_WO, 0);
            const uint32_t abase = sbase + (late ? SM_V : SM_K);
#pragma unroll 1
            for (int c = 0; c < 8; c++) {
                if ((c & 3) == 0) mbar_wait(bars + 8 * (B_OA + late * 2 + (c >> 2)), 0);
                if (c == 0) TL(7);
                const uint64_t da = mkdesc(abase + c * 8192, 16, 1024, 1);
                const uint64_t db = mkdesc(sbase + c * 8192 + nh * 64, 8192, 1024, 1);
                WG_FENCE();
#pragma unroll
                for (int k = 0; k < 4; k++) wgmma_n32(acc, da + k * 2, db + k * 128, (c | k) != 0);
                WG_COMMIT();
            }
            __syncthreads();
            WG_WAIT(0);
            TL(8);
#pragma unroll
            for (int h = 0; h < 2; h++) {
                const int row = row0 + h * 8;
                const int which = row == sel0 ? 0 : (row == sel1 ? 1 : -1);
#pragma unroll
                for (int i = 0; i < 4; i++) {
                    const int col = col0 + i * 8;
                    float b0 = bf_lo(nv[2 * i + h]), b1 = bf_hi(nv[2 * i + h]);
                    if (which >= 0) {
                        b0 = bfr(b0 + supd[which * 64 + col - nb * 64]); b1 = bfr(b1 + supd[which * 64 + col + 1 - nb * 64]);
                    }
                    const float t0 = bfr(bf_lo(xv[2 * i + h]) + bfr(acc[4 * i + 2 * h]));
                    const float t1 = bfr(bf_hi(xv[2 * i + h]) + bfr(acc[4 * i + 2 * h + 1]));
                    *reinterpret_cast<uint32_t*>(out + (size_t)row * DM + col) = packbf(t0 + b0, t1 + b1);
                }
            }
        }
        TL(9);
    }
    __syncthreads();
    if (tid == 0) {
        __threadfence();
        const unsigned tk = atomicAdd(&g_cnt[C_EXIT * 32], 1u);
        if (tk == gridDim.x - 1) {
            for (int i = 0; i < C_NUM; i++) g_cnt[i * 32] = 0u;
            __threadfence();
        }
    }
}

typedef CUresult (*EncodeFn)(CUtensorMap*, CUtensorMapDataType, cuuint32_t, void*, const cuuint64_t*, const cuuint64_t*,
                             const cuuint32_t*, const cuuint32_t*, CUtensorMapInterleave, CUtensorMapSwizzle,
                             CUtensorMapL2promotion, CUtensorMapFloatOOBfill);

void make_map(EncodeFn fn, CUtensorMap* m, const void* ptr, uint64_t cols, uint64_t rows, uint32_t box_rows, uint32_t box_chunks) {
    cuuint64_t dims[3] = {64, rows, cols / 64};
    cuuint64_t strides[2] = {cols * 2, 128};
    cuuint32_t box[3] = {64, box_rows, box_chunks};
    cuuint32_t es[3] = {1, 1, 1};
    fn(m, CU_TENSOR_MAP_DATA_TYPE_BFLOAT16, 3, const_cast<void*>(ptr), dims, strides, box, es, CU_TENSOR_MAP_INTERLEAVE_NONE,
       CU_TENSOR_MAP_SWIZZLE_128B, CU_TENSOR_MAP_L2_PROMOTION_L2_256B, CU_TENSOR_MAP_FLOAT_OOB_FILL_NONE);
}

}

extern "C" void kernel_launch(void* const* d_in, const int* in_sizes, int n_in, void* d_out, int out_size) {
    const __nv_bfloat16* x = (const __nv_bfloat16*)d_in[0];
    const __nv_bfloat16* wqkv = (const __nv_bfloat16*)d_in[1];
    const __nv_bfloat16* wo = (const __nv_bfloat16*)d_in[2];
    const __nv_bfloat16* wr = (const __nv_bfloat16*)d_in[4];
    const __nv_bfloat16* wgate = (const __nv_bfloat16*)d_in[5];
    const __nv_bfloat16* wup = (const __nv_bfloat16*)d_in[6];
    const __nv_bfloat16* wdown = (const __nv_bfloat16*)d_in[7];
    __nv_bfloat16* out = (__nv_bfloat16*)d_out;

    static EncodeFn enc = nullptr;
    static void* p_xn = nullptr; static void* p_o = nullptr;
    if (!enc) {
        void* fn = nullptr; cudaDriverEntryPointQueryResult qr;
        cudaGetDriverEntryPoint("cuTensorMapEncodeTiled", &fn, cudaEnableDefault, &qr);
        enc = (EncodeFn)fn;
        cudaGetSymbolAddress(&p_xn, g_xn);
        cudaGetSymbolAddress(&p_o, g_o);
        cudaFuncSetAttribute(fused_kernel, cudaFuncAttributeMaxDynamicSharedMemorySize, FUSED_SMEM);
    }
    Maps maps;
    make_map(enc, &maps.g, wgate, FF, DM, 16, 7);
    make_map(enc, &maps.u, wup, FF, DM, 16, 7);
    make_map(enc, &maps.d, wdown, DM, FF, 32, 8);
    make_map(enc, &maps.xn, p_xn, DM, S_LEN, 128, 1);
    make_map(enc, &maps.wqkv, wqkv, 3 * DM, DM, 64, 3);
    make_map(enc, &maps.o, p_o, DM, S_LEN, 64, 4);
    make_map(enc, &maps.wo, wo, DM, DM, 256, 1);

    union { uint32_t u; float f; } scu; scu.u = 128u;

    cudaLaunchConfig_t cfg = {};
    cfg.gridDim = dim3(132); cfg.blockDim = dim3(512); cfg.dynamicSmemBytes = FUSED_SMEM; cfg.stream = cudaStreamPerThread;
    cudaLaunchAttribute at[1];
    at[0].id = cudaLaunchAttributeCooperative;
    at[0].val.cooperative = 1;
    cfg.attrs = at; cfg.numAttrs = 1;
    cudaLaunchKernelEx(&cfg, fused_kernel, maps, x, wr, out, scu.f);
}
```

```cpp
#include <cuda_runtime.h>
#include <cuda_bf16.h>
#include <cuda.h>
#include <stdint.h>
#include <type_traits>

namespace {

constexpr int S_LEN = 2048;
constexpr int DM = 512;
constexpr int NH = 32;
constexpr int FF = 1792;

__device__ __align__(1024) __nv_bfloat16 g_xn[S_LEN * DM];
__device__ __align__(16) float g_r[S_LEN];
__device__ __align__(1024) uint4 g_q[NH * 128 * 32];
__device__ __align__(1024) uint4 g_k[NH * 4096];
__device__ __align__(1024) uint4 g_v[NH * 4096];
__device__ __align__(1024) __nv_bfloat16 g_o[S_LEN * DM];
__device__ __align__(16) float g_ypart[4 * 2 * DM];
__device__ int g_sel[2];
__device__ float g_gate[2];
constexpr int C_LN = 0, C_QKV = 16, C_O = 24, C_FFN = 56, C_EXIT = 57, C_NUM = 58;
__device__ unsigned g_cnt[C_NUM * 32];

#define TL(slot) do {} while (0)
#define TLX(slot, th) do {} while (0)

__device__ __forceinline__ uint32_t smem_u32(const void* p) { return (uint32_t)__cvta_generic_to_shared(p); }
__device__ __forceinline__ void warp_arrive(int idx) {
    __syncwarp();
    if ((threadIdx.x & 31) == 0)
        asm volatile("red.release.gpu.global.add.u32 [%0], 1;" :: "l"(g_cnt + idx * 32) : "memory");
}
__device__ __forceinline__ void flag_release(int idx) {
    asm volatile("red.release.gpu.global.add.u32 [%0], 1;" :: "l"(g_cnt + idx * 32) : "memory");
}
__device__ __forceinline__ void nbar_arrive(int id, int cnt) { asm volatile("bar.arrive %0, %1;" :: "r"(id), "r"(cnt) : "memory"); }
__device__ __forceinline__ void nbar_sync(int id, int cnt) { asm volatile("bar.sync %0, %1;" :: "r"(id), "r"(cnt) : "memory"); }
__device__ __forceinline__ void flag_wait(int idx, unsigned target) {
    asm volatile("{\n.reg .pred p;\n.reg .u32 n, v;\nmov.u32 n, 0;\n"
                 "FW_%=:\n"
                 "ld.acquire.gpu.global.u32 v, [%0];\n"
                 "setp.ge.u32 p, v, %1;\n"
                 "@p bra FD_%=;\n"
                 "add.u32 n, n, 1;\n"
                 "setp.lt.u32 p, n, 16000000;\n"
                 "@p bra FW_%=;\n"
                 "trap;\n"
                 "FD_%=:\n}"
                 :: "l"(g_cnt + idx * 32), "r"(target) : "memory");
}
__device__ __forceinline__ void flag_wait_all(int idx, unsigned target) {
    asm volatile("{\n.reg .pred p;\n.reg .u32 n, v;\nmov.u32 n, 0;\n"
                 "FW_%=:\n"
                 "ld.acquire.gpu.global.u32 v, [%0];\n"
                 "setp.ge.u32 p, v, %1;\n"
                 "vote.sync.all.pred p, p, 0xffffffff;\n"
                 "@p bra.uni FD_%=;\n"
                 "add.u32 n, n, 1;\n"
                 "setp.lt.u32 p, n, 16000000;\n"
                 "@p bra.uni FW_%=;\n"
                 "trap;\n"
                 "FD_%=:\n}"
                 :: "l"(g_cnt + idx * 32), "r"(target) : "memory");
}
__device__ __forceinline__ void fence_proxy_async_all() { asm volatile("fence.proxy.async;" ::: "memory"); }
__device__ __forceinline__ void mbar_init(uint32_t bar, uint32_t cnt) {
    asm volatile("mbarrier.init.shared::cta.b64 [%0], %1;" :: "r"(bar), "r"(cnt) : "memory");
}
__device__ __forceinline__ void mbar_expect_tx(uint32_t bar, uint32_t bytes) {
    asm volatile("mbarrier.arrive.expect_tx.shared::cta.b64 _, [%0], %1;" :: "r"(bar), "r"(bytes) : "memory");
}
__device__ __forceinline__ void mbar_arrive(uint32_t bar) {
    asm volatile("mbarrier.arrive.shared::cta.b64 _, [%0];" :: "r"(bar) : "memory");
}
__device__ __forceinline__ void mbar_wait(uint32_t bar, uint32_t parity) {
    asm volatile("{\n.reg .pred p;\n.reg .u32 n;\nmov.u32 n, 0;\n"
                 "WAIT_%=:\n"
                 "mbarrier.try_wait.parity.shared::cta.b64 p, [%0], %1;\n"
                 "@p bra DONE_%=;\n"
                 "add.u32 n, n, 1;\n"
                 "setp.lt.u32 p, n, 4000000;\n"
                 "@p bra WAIT_%=;\n"
                 "trap;\n"
                 "DONE_%=:\n}"
                 :: "r"(bar), "r"(parity) : "memory");
}
__device__ __forceinline__ void fence_barrier_init() { asm volatile("fence.mbarrier_init.release.cluster;" ::: "memory"); }
__device__ __forceinline__ void fence_proxy_async() { asm volatile("fence.proxy.async.shared::cta;" ::: "memory"); }
__device__ __forceinline__ void tma3d(uint32_t dst, const CUtensorMap* map, uint32_t bar, int row, int chunk) {
    asm volatile("cp.async.bulk.tensor.3d.shared::cluster.global.mbarrier::complete_tx::bytes [%0], [%1, {%3, %4, %5}], [%2];"
                 :: "r"(dst), "l"((uint64_t)map), "r"(bar), "r"(0), "r"(row), "r"(chunk) : "memory");
}
__device__ __forceinline__ void bulk_g2s(uint32_t dst, const void* src, uint32_t bytes, uint32_t bar) {
    asm volatile("cp.async.bulk.shared::cluster.global.mbarrier::complete_tx::bytes [%0], [%1], %2, [%3];"
                 :: "r"(dst), "l"((uint64_t)src), "r"(bytes), "r"(bar) : "memory");
}
__device__ __forceinline__ void l2_prefetch(const void* src, uint32_t bytes) {
    asm volatile("cp.async.bulk.prefetch.L2.global [%0], %1;" :: "l"((uint64_t)src), "r"(bytes) : "memory");
}
__device__ __forceinline__ void map_prefetch(const CUtensorMap* m) {
    asm volatile("prefetch.tensormap [%0];" :: "l"((uint64_t)m) : "memory");
}
__device__ __forceinline__ uint64_t mkdesc(uint32_t addr, uint32_t lbo, uint32_t sbo, uint32_t swz) {
    return (uint64_t)((addr & 0x3FFFF) >> 4) | ((uint64_t)(lbo >> 4) << 16) | ((uint64_t)(sbo >> 4) << 32) | ((uint64_t)swz << 62);
}
#define WG_FENCE() asm volatile("wgmma.fence.sync.aligned;" ::: "memory")
#define WG_COMMIT() asm volatile("wgmma.commit_group.sync.aligned;" ::: "memory")
#define WG_WAIT(n) asm volatile("wgmma.wait_group.sync.aligned %0;" :: "n"(n) : "memory")

__device__ __forceinline__ float ex2(float x) { float y; asm("ex2.approx.ftz.f32 %0, %1;" : "=f"(y) : "f"(x)); return y; }
__device__ __forceinline__ uint32_t packbf(float lo, float hi) {
    uint32_t r; asm("cvt.rn.bf16x2.f32 %0, %1, %2;" : "=r"(r) : "f"(hi), "f"(lo)); return r;
}
__device__ __forceinline__ float bf_lo(uint32_t v) { return __uint_as_float(v << 16); }
__device__ __forceinline__ float bf_hi(uint32_t v) { return __uint_as_float(v & 0xffff0000u); }
__device__ __forceinline__ float bfr(float x) { return __bfloat162float(__float2bfloat16_rn(x)); }

__device__ __forceinline__ void wgmma_n192(float (&d)[96], uint64_t da, uint64_t db, int scale_d) {
    asm volatile("{\n.reg .pred p;\nsetp.ne.b32 p, %98, 0;\n"
        "wgmma.mma_async.sync.aligned.m64n192k16.f32.bf16.bf16 "
        "{%0,%1,%2,%3,%4,%5,%6,%7,%8,%9,%10,%11,%12,%13,%14,%15,%16,%17,%18,%19,%20,%21,%22,%23,"
        "%24,%25,%26,%27,%28,%29,%30,%31,%32,%33,%34,%35,%36,%37,%38,%39,%40,%41,%42,%43,%44,%45,%46,%47,"
        "%48,%49,%50,%51,%52,%53,%54,%55,%56,%57,%58,%59,%60,%61,%62,%63,%64,%65,%66,%67,%68,%69,%70,%71,"
        "%72,%73,%74,%75,%76,%77,%78,%79,%80,%81,%82,%83,%84,%85,%86,%87,%88,%89,%90,%91,%92,%93,%94,%95}, "
        "%96, %97, p, 1, 1, 0, 1;\n}"
        : "+f"(d[0]), "+f"(d[1]), "+f"(d[2]), "+f"(d[3]), "+f"(d[4]), "+f"(d[5]), "+f"(d[6]), "+f"(d[7]),
          "+f"(d[8]), "+f"(d[9]), "+f"(d[10]), "+f"(d[11]), "+f"(d[12]), "+f"(d[13]), "+f"(d[14]), "+f"(d[15]),
          "+f"(d[16]), "+f"(d[17]), "+f"(d[18]), "+f"(d[19]), "+f"(d[20]), "+f"(d[21]), "+f"(d[22]), "+f"(d[23]),
          "+f"(d[24]), "+f"(d[25]), "+f"(d[26]), "+f"(d[27]), "+f"(d[28]), "+f"(d[29]), "+f"(d[30]), "+f"(d[31]),
          "+f"(d[32]), "+f"(d[33]), "+f"(d[34]), "+f"(d[35]), "+f"(d[36]), "+f"(d[37]), "+f"(d[38]), "+f"(d[39]),
          "+f"(d[40]), "+f"(d[41]), "+f"(d[42]), "+f"(d[43]), "+f"(d[44]), "+f"(d[45]), "+f"(d[46]), "+f"(d[47]),
          "+f"(d[48]), "+f"(d[49]), "+f"(d[50]), "+f"(d[51]), "+f"(d[52]), "+f"(d[53]), "+f"(d[54]), "+f"(d[55]),
          "+f"(d[56]), "+f"(d[57]), "+f"(d[58]), "+f"(d[59]), "+f"(d[60]), "+f"(d[61]), "+f"(d[62]), "+f"(d[63]),
          "+f"(d[64]), "+f"(d[65]), "+f"(d[66]), "+f"(d[67]), "+f"(d[68]), "+f"(d[69]), "+f"(d[70]), "+f"(d[71]),
          "+f"(d[72]), "+f"(d[73]), "+f"(d[74]), "+f"(d[75]), "+f"(d[76]), "+f"(d[77]), "+f"(d[78]), "+f"(d[79]),
          "+f"(d[80]), "+f"(d[81]), "+f"(d[82]), "+f"(d[83]), "+f"(d[84]), "+f"(d[85]), "+f"(d[86]), "+f"(d[87]),
          "+f"(d[88]), "+f"(d[89]), "+f"(d[90]), "+f"(d[91]), "+f"(d[92]), "+f"(d[93]), "+f"(d[94]), "+f"(d[95])
        : "l"(da), "l"(db), "r"(scale_d));
}

constexpr float SHIFT = 90.0f;
constexpr float QS = 0.25f * 1.4426950408889634f * 18446744073709551616.0f;
constexpr float scq = 0.25f * 1.4426950408889634f * 3.3087224502121107e-24f;

__device__ __forceinline__ uint32_t polyexp(float lo, float hi) {
    uint32_t w, g, q, h;
    asm("cvt.pack.sat.s16.s32 %0, %1, %2;" : "=r"(w) : "r"(__float_as_uint(hi)), "r"(__float_as_uint(lo)));
    g = w & 0x007F007Fu;
    asm("fma.rn.f16x2 %0, %1, %2, %3;" : "=r"(q) : "r"(g), "r"(0xf940f940u), "r"(0x35513551u));
    asm("mul.rn.f16x2 %0, %1, %2;" : "=r"(h) : "r"(q), "r"(g));
    return w - h;
}
__device__ __forceinline__ void qk64(float (&s)[32], const uint32_t (&q)[4], uint64_t db) {
    asm volatile("wgmma.mma_async.sync.aligned.m64n64k16.f32.bf16.bf16 "
        "{%0,%1,%2,%3,%4,%5,%6,%7,%8,%9,%10,%11,%12,%13,%14,%15,%16,%17,%18,%19,%20,%21,%22,%23,%24,%25,%26,%27,%28,%29,%30,%31}, "
        "{%32,%33,%34,%35}, %36, 0, 1, 1, 0;"
        : "=f"(s[0]), "=f"(s[1]), "=f"(s[2]), "=f"(s[3]), "=f"(s[4]), "=f"(s[5]), "=f"(s[6]), "=f"(s[7]),
          "=f"(s[8]), "=f"(s[9]), "=f"(s[10]), "=f"(s[11]), "=f"(s[12]), "=f"(s[13]), "=f"(s[14]), "=f"(s[15]),
          "=f"(s[16]), "=f"(s[17]), "=f"(s[18]), "=f"(s[19]), "=f"(s[20]), "=f"(s[21]), "=f"(s[22]), "=f"(s[23]),
          "=f"(s[24]), "=f"(s[25]), "=f"(s[26]), "=f"(s[27]), "=f"(s[28]), "=f"(s[29]), "=f"(s[30]), "=f"(s[31])
        : "r"(q[0]), "r"(q[1]), "r"(q[2]), "r"(q[3]), "l"(db));
}
__device__ __forceinline__ void pv24(float (&o)[12], uint32_t a0, uint32_t a1, uint32_t a2, uint32_t a3, uint64_t db) {
    asm volatile("wgmma.mma_async.sync.aligned.m64n24k16.f32.bf16.bf16 "
        "{%0,%1,%2,%3,%4,%5,%6,%7,%8,%9,%10,%11}, {%12,%13,%14,%15}, %16, 1, 1, 1, 1;"
        : "+f"(o[0]), "+f"(o[1]), "+f"(o[2]), "+f"(o[3]), "+f"(o[4]), "+f"(o[5]), "+f"(o[6]), "+f"(o[7]),
          "+f"(o[8]), "+f"(o[9]), "+f"(o[10]), "+f"(o[11])
        : "r"(a0), "r"(a1), "r"(a2), "r"(a3), "l"(db));
}

__device__ __forceinline__ void attn_safe(float (&o)[12], const uint32_t (&q)[4], uint64_t kdesc0, uint64_t vdesc0) {
    float s[32];
    float m0 = -INFINITY, m1 = -INFINITY;
#pragma unroll
    for (int i = 0; i < 12; i++) o[i] = 0.f;
#pragma unroll 1
    for (int j = 0; j < 32; j++) {
        WG_FENCE();
        qk64(s, q, kdesc0 + (uint64_t)(j * 64));
        WG_COMMIT(); WG_WAIT(0);
        float n0 = m0, n1 = m1;
#pragma unroll
        for (int i = 0; i < 8; i++) { n0 = fmaxf(n0, fmaxf(s[4 * i], s[4 * i + 1])); n1 = fmaxf(n1, fmaxf(s[4 * i + 2], s[4 * i + 3])); }
        n0 = fmaxf(n0, __shfl_xor_sync(~0u, n0, 1)); n0 = fmaxf(n0, __shfl_xor_sync(~0u, n0, 2));
        n1 = fmaxf(n1, __shfl_xor_sync(~0u, n1, 1)); n1 = fmaxf(n1, __shfl_xor_sync(~0u, n1, 2));
        const float c0 = ex2((m0 - n0) * QS), c1 = ex2((m1 - n1) * QS);
        m0 = n0; m1 = n1;
#pragma unroll
        for (int i = 0; i < 3; i++) { o[4 * i] *= c0; o[4 * i + 1] *= c0; o[4 * i + 2] *= c1; o[4 * i + 3] *= c1; }
        uint32_t p[16];
#pragma unroll
        for (int i = 0; i < 8; i++) {
            p[2 * i] = packbf(ex2((s[4 * i] - m0) * QS), ex2((s[4 * i + 1] - m0) * QS));
            p[2 * i + 1] = packbf(ex2((s[4 * i + 2] - m1) * QS), ex2((s[4 * i + 3] - m1) * QS));
        }
        WG_FENCE();
#pragma unroll
        for (int kk = 0; kk < 4; kk++) pv24(o, p[4 * kk], p[4 * kk + 1], p[4 * kk + 2], p[4 * kk + 3], vdesc0 + (uint64_t)(j * 64 + kk * 16));
        WG_COMMIT(); WG_WAIT(0);
    }
}

__device__ __forceinline__ void attn_store(const float (&o)[12], int head, int m64, int warp, int lane) {
    const int g = lane >> 2, t = lane & 3;
    const int row = m64 * 64 + warp * 16 + g;
    const float i0 = 1.f / o[8], i1 = 1.f / o[10];
    uint32_t* p0 = reinterpret_cast<uint32_t*>(g_o + (size_t)row * DM + head * 16 + t * 2);
    uint32_t* p1 = reinterpret_cast<uint32_t*>(g_o + (size_t)(row + 8) * DM + head * 16 + t * 2);
    p0[0] = packbf(o[0] * i0, o[1] * i0); p0[4] = packbf(o[4] * i0, o[5] * i0);
    p1[0] = packbf(o[2] * i1, o[3] * i1); p1[4] = packbf(o[6] * i1, o[7] * i1);
}

constexpr int FS_N = 4;
constexpr int FS_BYTES = 32768;
__device__ __forceinline__ void ldsm4t(uint32_t& r0, uint32_t& r1, uint32_t& r2, uint32_t& r3, uint32_t addr) {
    asm volatile("ldmatrix.sync.aligned.m8n8.x4.trans.shared.b16 {%0,%1,%2,%3}, [%4];" : "=r"(r0), "=r"(r1), "=r"(r2), "=r"(r3) : "r"(addr) : "memory");
}
__device__ __forceinline__ void mma16816(float (&d)[4], uint32_t a0, uint32_t a2, uint32_t b0, uint32_t b1) {
    asm volatile("mma.sync.aligned.m16n8k16.row.col.f32.bf16.bf16.f32 {%0,%1,%2,%3}, {%4,%5,%6,%5}, {%7,%8}, {%0,%1,%2,%3};"
                 : "+f"(d[0]), "+f"(d[1]), "+f"(d[2]), "+f"(d[3]) : "r"(a0), "r"(0u), "r"(a2), "r"(b0), "r"(b1));
}
__device__ void ffn_block(int c, uint8_t* smem, uint32_t sbase, const CUtensorMap* mapG, const CUtensorMap* mapU, const CUtensorMap* mapD) {
    const int tid = threadIdx.x, warp = tid >> 5, lane = tid & 31;
    uint32_t* sx = reinterpret_cast<uint32_t*>(smem + FS_N * FS_BYTES);
    __nv_bfloat16* sh = reinterpret_cast<__nv_bfloat16*>(sx + 512);
    const uint32_t bars = sbase + FS_N * FS_BYTES + 8192;
    float* tv = reinterpret_cast<float*>(smem + FS_N * FS_BYTES + 4096);
    int* ti = reinterpret_cast<int*>(tv + 32);
    int* ssel = ti + 32;
    auto issue = [&](int item) {
        const int slot = item % FS_N;
        const uint32_t dst = sbase + slot * FS_BYTES, bar = bars + 8 * slot;
        mbar_expect_tx(bar, item < 32 ? 28672 : 32768);
        if (item < 32) {
            tma3d(dst, mapG, bar, item * 16, c * 7);
            tma3d(dst + 14336, mapU, bar, item * 16, c * 7);
        } else {
            tma3d(dst, mapD, bar, c * 448 + (item - 32) * 32, 0);
        }
    };
    if (tid == 0) {
        for (int i = 0; i < FS_N; i++) mbar_init(bars + 8 * i, 1);
        fence_barrier_init();
        for (int i = 0; i < FS_N; i++) issue(i);
    }
    flag_wait(C_LN + warp, 8);
    __syncthreads();
    float b1 = -INFINITY, b2 = -INFINITY; int i1 = 0x7fffffff, i2 = 0x7fffffff;
    auto push = [&](float v, int i) {
        if (v > b1 || (v == b1 && i < i1)) { b2 = b1; i2 = i1; b1 = v; i1 = i; }
        else if (v > b2 || (v == b2 && i < i2)) { b2 = v; i2 = i; }
    };
    {
        const float4 rv = __ldcg(reinterpret_cast<const float4*>(g_r) + tid);
        push(rv.x, 4 * tid); push(rv.y, 4 * tid + 1); push(rv.z, 4 * tid + 2); push(rv.w, 4 * tid + 3);
    }
#pragma unroll
    for (int o = 16; o > 0; o >>= 1) {
        float v1 = __shfl_xor_sync(~0u, b1, o), v2 = __shfl_xor_sync(~0u, b2, o);
        int j1 = __shfl_xor_sync(~0u, i1, o), j2 = __shfl_xor_sync(~0u, i2, o);
        push(v1, j1); push(v2, j2);
    }
    if (lane == 0) { tv[2 * warp] = b1; ti[2 * warp] = i1; tv[2 * warp + 1] = b2; ti[2 * warp + 1] = i2; }
    __syncthreads();
    if (warp == 1) {
        b1 = tv[lane]; i1 = ti[lane]; b2 = -INFINITY; i2 = 0x7fffffff;
#pragma unroll
        for (int o = 16; o > 0; o >>= 1) {
            float v1 = __shfl_xor_sync(~0u, b1, o), v2 = __shfl_xor_sync(~0u, b2, o);
            int j1 = __shfl_xor_sync(~0u, i1, o), j2 = __shfl_xor_sync(~0u, i2, o);
            push(v1, j1); push(v2, j2);
        }
        if (lane == 0) {
            i1 = min(max(i1, 0), S_LEN - 1); i2 = min(max(i2, 0), S_LEN - 1);
            ssel[0] = i1; ssel[1] = i2;
            if (c == 0) {
                g_sel[0] = i1; g_sel[1] = i2;
                g_gate[0] = bfr(1.f / (1.f + __expf(-bfr(b1))));
                g_gate[1] = bfr(1.f / (1.f + __expf(-bfr(b2))));
            }
        }
    }
    __syncthreads();
    sx[tid] = __ldcg(reinterpret_cast<const uint32_t*>(g_xn + (size_t)ssel[tid >> 8] * DM + (tid & 255) * 2));
    __syncthreads();
    TL(1);
    const int g = lane >> 2, t = lane & 3;
    const int lrow = lane & 15, lsel = lane >> 4;
    {
        float ag[4][4], au[4][4];
#pragma unroll
        for (int j = 0; j < 4; j++) { ag[j][0] = ag[j][1] = ag[j][2] = ag[j][3] = 0.f; au[j][0] = au[j][1] = au[j][2] = au[j][3] = 0.f; }
#pragma unroll 1
        for (int it = 0; it < 32; it++) {
            const int slot = it % FS_N;
            const uint32_t a0 = g < 2 ? sx[g * 256 + it * 8 + t] : 0u, a2 = g < 2 ? sx[g * 256 + it * 8 + 4 + t] : 0u;
            mbar_wait(bars + 8 * slot, (it / FS_N) & 1);
            const uint32_t base = sbase + slot * FS_BYTES + lsel * 14336 + lrow * 128;
#pragma unroll
            for (int j = 0; j < 4; j++) {
                const int nt = warp + j * 16;
                if (nt < 56) {
                    uint32_t b0, b1, b2, b3;
                    ldsm4t(b0, b1, b2, b3, base + (nt >> 3) * 2048 + (((nt & 7) ^ (lrow & 7)) << 4));
                    mma16816(ag[j], a0, a2, b0, b1);
                    mma16816(au[j], a0, a2, b2, b3);
                }
            }
            __syncthreads();
            if (tid == 480) issue(it + FS_N);
        }
        if (g < 2) {
#pragma unroll
            for (int j = 0; j < 4; j++) {
                const int nt = warp + j * 16;
                if (nt < 56) {
#pragma unroll
                    for (int e = 0; e < 2; e++) {
                        const float gs = bfr(ag[j][e]), us = bfr(au[j][e]);
                        const float sg = bfr(gs / (1.f + __expf(-gs)));
                        sh[g * 448 + nt * 8 + t * 2 + e] = __float2bfloat16_rn(sg * us);
                    }
                }
            }
        }
        __syncthreads();
    }
    TL(2);
    {
        const uint32_t* shw = reinterpret_cast<const uint32_t*>(sh);
        float a[4][4];
#pragma unroll
        for (int j = 0; j < 4; j++) a[j][0] = a[j][1] = a[j][2] = a[j][3] = 0.f;
#pragma unroll 1
        for (int it = 32; it < 46; it++) {
            const int slot = it % FS_N;
            uint32_t af[4];
#pragma unroll
            for (int q = 0; q < 4; q++) af[q] = g < 2 ? shw[g * 224 + (it - 32) * 16 + q * 4 + t] : 0u;
            mbar_wait(bars + 8 * slot, (it / FS_N) & 1);
            const uint32_t base = sbase + slot * FS_BYTES + (warp >> 1) * 4096 + lane * 128;
#pragma unroll
            for (int j = 0; j < 4; j++) {
                const int u = (warp & 1) * 4 + j;
                uint32_t b0, b1, b2, b3;
                ldsm4t(b0, b1, b2, b3, base + ((u ^ (lane & 7)) << 4));
                mma16816(a[j], af[0], af[1], b0, b1);
                mma16816(a[j], af[2], af[3], b2, b3);
            }
            __syncthreads();
            if (tid == 480 && it + FS_N < 46) issue(it + FS_N);
        }
        if (g < 2) {
#pragma unroll
            for (int j = 0; j < 4; j++)
                *reinterpret_cast<float2*>(&g_ypart[c * 1024 + g * 512 + (warp * 4 + j) * 8 + t * 2]) = make_float2(a[j][0], a[j][1]);
        }
    }
    warp_arrive(C_FFN);
}

__device__ __forceinline__ void wgmma_n32(float (&d)[16], uint64_t da, uint64_t db, int scale_d) {
    asm volatile("{\n.reg .pred p;\nsetp.ne.b32 p, %18, 0;\n"
        "wgmma.mma_async.sync.aligned.m64n32k16.f32.bf16.bf16 "
        "{%0,%1,%2,%3,%4,%5,%6,%7,%8,%9,%10,%11,%12,%13,%14,%15}, "
        "%16, %17, p, 1, 1, 0, 1;\n}"
        : "+f"(d[0]), "+f"(d[1]), "+f"(d[2]), "+f"(d[3]), "+f"(d[4]), "+f"(d[5]), "+f"(d[6]), "+f"(d[7]),
          "+f"(d[8]), "+f"(d[9]), "+f"(d[10]), "+f"(d[11]), "+f"(d[12]), "+f"(d[13]), "+f"(d[14]), "+f"(d[15])
        : "l"(da), "l"(db), "r"(scale_d));
}

constexpr int G_ST = 4;
constexpr int G_STAGE = 16384 + 24576;
constexpr int SM_K = 65536, SM_V = 131072, SM_ONES = 196608, SM_MISC = 229376;
constexpr int FUSED_SMEM = SM_MISC + 2048;
constexpr int B_FULL = 0, B_EMPTY = 4, B_KV = 8, B_WO = 16, B_OA = 18, B_NUM = 22;

struct Maps { CUtensorMap xn, wqkv, o, wo, g, u, d; };

__global__ void __launch_bounds__(512, 1) fused_kernel(const __grid_constant__ Maps maps, const __nv_bfloat16* __restrict__ x,
                                                       const __nv_bfloat16* __restrict__ wr, __nv_bfloat16* __restrict__ out, float sc) {
    extern __shared__ __align__(1024) uint8_t smem[];
    const uint32_t sbase = smem_u32(smem);
    const int tid = threadIdx.x, warp = __shfl_sync(~0u, tid >> 5, 0), lane = tid & 31;
    const uint32_t bars = sbase + SM_MISC;
    TL(0);
    if (sbase & 1023u) __trap();
    if (blockIdx.x < 4) {
        ffn_block(blockIdx.x, smem, sbase, &maps.g, &maps.u, &maps.d);
        TL(3);
    } else {
        const int idx = blockIdx.x - 4;
        const int wg = warp >> 2;
        {
            const int row = idx * 16 + warp;
            const uint4* xr = reinterpret_cast<const uint4*>(x + (size_t)row * DM);
            const uint4 a = xr[lane], b = xr[32 + lane];
            const uint4* wp = reinterpret_cast<const uint4*>(wr);
            const uint4 wa = wp[lane], wb = wp[32 + lane];
            if (tid == 480) {
                for (int s = 0; s < G_ST; s++) { mbar_init(bars + 8 * (B_FULL + s), 2); mbar_init(bars + 8 * (B_EMPTY + s), 2); }
                for (int c = B_KV; c < B_NUM; c++) mbar_init(bars + 8 * c, 1);
                fence_barrier_init();
                for (int c = 0; c < G_ST; c++) {
                    mbar_expect_tx(bars + 8 * (B_FULL + c), 24576);
                    tma3d(sbase + c * G_STAGE + 16384, &maps.wqkv, bars + 8 * (B_FULL + c), c * 64, (idx & 7) * 3);
                }
                map_prefetch(&maps.xn);
            }
            __syncwarp();
            const uint32_t u[8] = {a.x, a.y, a.z, a.w, b.x, b.y, b.z, b.w};
            const uint32_t w[8] = {wa.x, wa.y, wa.z, wa.w, wb.x, wb.y, wb.z, wb.w};
            float f[16];
            float sum = 0.f;
#pragma unroll
            for (int i = 0; i < 8; i++) { f[2 * i] = bf_lo(u[i]); f[2 * i + 1] = bf_hi(u[i]); sum += f[2 * i] + f[2 * i + 1]; }
#pragma unroll
            for (int o = 16; o > 0; o >>= 1) sum += __shfl_xor_sync(~0u, sum, o);
            const float mean = sum * (1.f / DM);
            float sq = 0.f;
#pragma unroll
            for (int i = 0; i < 16; i++) { const float d = f[i] - mean; sq = fmaf(d, d, sq); }
#pragma unroll
            for (int o = 16; o > 0; o >>= 1) sq += __shfl_xor_sync(~0u, sq, o);
            const float mb_ = bfr(mean);
            const float vb = bfr(sq * (1.f / DM));
            const float rinv = 1.f / bfr(sqrtf(bfr(vb + 1e-5f)));
            uint32_t o[8];
            float r = 0.f;
#pragma unroll
            for (int i = 0; i < 8; i++) {
                const float d0 = bfr(f[2 * i] - mb_), d1 = bfr(f[2 * i + 1] - mb_);
                o[i] = packbf(d0 * rinv, d1 * rinv);
                r = fmaf(bf_lo(o[i]), bf_lo(w[i]), r);
                r = fmaf(bf_hi(o[i]), bf_hi(w[i]), r);
            }
            uint4* xo = reinterpret_cast<uint4*>(g_xn + (size_t)row * DM);
            xo[lane] = make_uint4(o[0], o[1], o[2], o[3]);
            xo[32 + lane] = make_uint4(o[4], o[5], o[6], o[7]);
#pragma unroll
            for (int of = 16; of > 0; of >>= 1) r += __shfl_xor_sync(~0u, r, of);
            if (lane == 0) g_r[row] = r;
        }
        __syncthreads();
        if (tid == 416) flag_release(C_LN + (idx >> 3));
        if (warp == 12 || warp == 11) {
            uint4* ones = reinterpret_cast<uint4*>(smem + SM_ONES);
#pragma unroll 8
            for (int i = tid - 352; i < 2048; i += 64) ones[i] = make_uint4(0x3f803f80u, 0x3f803f80u, 0x3f803f80u, 0x3f803f80u);
            fence_proxy_async();
        }
        TL(1);
        {
            const int nb = idx & 7, mb = idx >> 3;
            if (warp == 15) {
                for (int c = G_ST; c < 8; c++) {
                    const int s = c - G_ST;
                    mbar_wait(bars + 8 * (B_EMPTY + s), 0);
                    if (lane == 0) {
                        mbar_expect_tx(bars + 8 * (B_FULL + s), 24576);
                        tma3d(sbase + s * G_STAGE + 16384, &maps.wqkv, bars + 8 * (B_FULL + s), c * 64, nb * 3);
                    }
                    __syncwarp();
                }
            } else if (warp == 14) {
                flag_wait(C_LN + mb, 8);
                fence_proxy_async_all();
                for (int c = 0; c < 8; c++) {
                    const int s = c & (G_ST - 1);
                    if (c >= G_ST) mbar_wait(bars + 8 * (B_EMPTY + s), 0);
                    if (lane == 0) {
                        mbar_expect_tx(bars + 8 * (B_FULL + s), 16384);
                        tma3d(sbase + s * G_STAGE, &maps.xn, bars + 8 * (B_FULL + s), mb * 128, c);
                    }
                    __syncwarp();
                }
            } else if (wg < 2) {
                float acc[96];
#pragma unroll
                for (int i = 0; i < 96; i++) acc[i] = 0.f;
#pragma unroll 1
                for (int c = 0; c < 8; c++) {
                    const int s = c & (G_ST - 1);
                    const uint32_t st = sbase + s * G_STAGE;
                    mbar_wait(bars + 8 * (B_FULL + s), c >> 2);
                    if (c == 0) TL(2);
                    const uint64_t da = mkdesc(st + wg * 8192, 16, 1024, 1);
                    const uint64_t db = mkdesc(st + 16384, 8192, 1024, 1);
                    WG_FENCE();
#pragma unroll
                    for (int k = 0; k < 4; k++) wgmma_n192(acc, da + k * 2, db + k * 128, (c | k) != 0);
                    WG_COMMIT();
                    if (c <= G_ST) {
                        WG_WAIT(1);
                        if (c >= 1 && (tid & 127) == 0) mbar_arrive(bars + 8 * (B_EMPTY + c - 1));
                    }
                }
                WG_WAIT(0);
                nbar_arrive(6, 288);
                TL(3);
                const int g = lane >> 2, t = lane & 3;
                const int mt = mb * 8 + warp;
#pragma unroll
                for (int hh = 0; hh < 12; hh++) {
                    const int gh = nb * 12 + hh;
                    const float* a = &acc[hh * 8];
                    if (gh < 32) {
                        g_q[(gh * 128 + mt) * 32 + lane] = make_uint4(packbf(a[0], a[1]), packbf(a[2], a[3]), packbf(a[4], a[5]), packbf(a[6], a[7]));
                    } else {
                        uint32_t* dst = reinterpret_cast<uint32_t*>(gh < 64 ? g_k + (gh - 32) * 4096 : g_v + (gh - 64) * 4096);
                        const float ks = gh < 64 ? 5.421010862427522e-20f : 1.0f;
                        const int off = (mt * 16 + g) * 4 + t;
                        dst[off] = packbf(a[0] * ks, a[1] * ks);
                        dst[off + 32] = packbf(a[2] * ks, a[3] * ks);
                        dst[8192 + off] = packbf(a[4] * ks, a[5] * ks);
                        dst[8192 + off + 32] = packbf(a[6] * ks, a[7] * ks);
                    }
                }
                TL(10);
                nbar_sync(8, 256);
                if (tid == 0) flag_release(C_QKV + nb);
            }
        }
        TL(4);
        uint32_t badmask = 0;
        const int head = idx >> 2, quarter = idx & 3, w4 = warp & 3;
        {
            if (warp == 15) {
                flag_wait_all(C_QKV + ((lane % 3) * 32 + head) / 12, 16);
                nbar_sync(6, 288);
                fence_proxy_async_all();
            }
            if (tid == 480) {
                const uint8_t* kp = reinterpret_cast<const uint8_t*>(g_k + head * 4096);
                const uint8_t* vp = reinterpret_cast<const uint8_t*>(g_v + head * 4096);
                for (int c = 0; c < 8; c++) {
                    const uint32_t bar = bars + 8 * (B_KV + c);
                    mbar_expect_tx(bar, 16384);
                    bulk_g2s(sbase + SM_K + c * 4096, kp + c * 4096, 4096, bar);
                    bulk_g2s(sbase + SM_K + 32768 + c * 4096, kp + 32768 + c * 4096, 4096, bar);
                    bulk_g2s(sbase + SM_V + c * 4096, vp + c * 4096, 4096, bar);
                    bulk_g2s(sbase + SM_V + 32768 + c * 4096, vp + 32768 + c * 4096, 4096, bar);
                }
                mbar_expect_tx(bars + 8 * B_WO, 65536);
                tma3d(sbase, &maps.wo, bars + 8 * B_WO, 0, idx & 7);
                tma3d(sbase + 32768, &maps.wo, bars + 8 * B_WO, 256, idx & 7);
                map_prefetch(&maps.o);
            }
            __syncthreads();
            const uint64_t kdesc0 = mkdesc(sbase + SM_K, 32768, 128, 0);
            const uint64_t vdesc0 = mkdesc(sbase + SM_V, 128, 32768, 0);
#pragma unroll 1
            for (int mt = 0; mt < 2; mt++) {
                const int m64 = quarter * 8 + mt * 4 + wg;
                uint32_t q[4];
                { const uint4 qq = __ldcg(&g_q[(head * 128 + m64 * 4 + w4) * 32 + lane]); q[0] = qq.x; q[1] = qq.y; q[2] = qq.z; q[3] = qq.w; }
                float s[32], s2[32], o[12];
#pragma unroll
                for (int i = 0; i < 12; i++) o[i] = 0.f;
                mbar_wait(bars + 8 * B_KV, 0);
                if (mt == 0) TL(5);
                WG_FENCE();
                qk64(s, q, kdesc0);
                WG_COMMIT(); WG_WAIT(0);
                float mx0 = -INFINITY, mx1 = -INFINITY;
#pragma unroll
                for (int i = 0; i < 8; i++) { mx0 = fmaxf(mx0, fmaxf(s[4 * i], s[4 * i + 1])); mx1 = fmaxf(mx1, fmaxf(s[4 * i + 2], s[4 * i + 3])); }
                mx0 = fmaxf(mx0, __shfl_xor_sync(~0u, mx0, 1)); mx0 = fmaxf(mx0, __shfl_xor_sync(~0u, mx0, 2));
                mx1 = fmaxf(mx1, __shfl_xor_sync(~0u, mx1, 1)); mx1 = fmaxf(mx1, __shfl_xor_sync(~0u, mx1, 2));
                if (mt == 1 && !badmask) {
                    nbar_sync(wg + 1, 128);
                    if ((tid & 127) == 0) flag_release(C_O + m64 - 4);
                }
                float cm0 = -(ceilf(mx0 * QS) + SHIFT), cm1 = -(ceilf(mx1 * QS) + SHIFT);
                float cp0 = (cm0 + 127.f) * sc, cp1 = (cm1 + 127.f) * sc;
                asm volatile("" : "+f"(cm0), "+f"(cm1), "+f"(cp0), "+f"(cp1));
                uint64_t kd = kdesc0, vd = vdesc0;
                auto step = [&](float (&sc_)[32], float (&sn)[32]) {
                    kd += 64;
                    WG_FENCE();
                    qk64(sn, q, kd);
                    WG_COMMIT();
#pragma unroll
                    for (int kk = 0; kk < 4; kk++) {
                        const int i0 = kk * 2, i1 = kk * 2 + 1;
                        const uint32_t p0 = packbf(ex2(fmaf(sc_[4 * i0], QS, cm0)), ex2(fmaf(sc_[4 * i0 + 1], QS, cm0)));
                        const uint32_t p1 = packbf(ex2(fmaf(sc_[4 * i0 + 2], QS, cm1)), ex2(fmaf(sc_[4 * i0 + 3], QS, cm1)));
                        const uint32_t p2 = polyexp(fmaf(sc_[4 * i1], scq, cp0), fmaf(sc_[4 * i1 + 1], scq, cp0));
                        const uint32_t p3 = polyexp(fmaf(sc_[4 * i1 + 2], scq, cp1), fmaf(sc_[4 * i1 + 3], scq, cp1));
                        WG_FENCE();
                        pv24(o, p0, p1, p2, p3, vd);
                        vd += 16;
                    }
                    WG_COMMIT();
                    WG_WAIT(1);
                };
#pragma unroll 1
                for (int c = 0; c < 16; c++) {
                    if (mt == 0 && (c & 1) == 0 && c < 14) mbar_wait(bars + 8 * B_KV + 4 * c + 8, 0);
                    step(s, s2); step(s2, s);
                }
                WG_WAIT(0);
                bool bad = !(o[8] > 0.f) || !(o[10] > 0.f);
#pragma unroll
                for (int i = 0; i < 12; i++) bad = bad || !(fabsf(o[i]) <= 3.0e38f);
                uint32_t anybad;
                asm volatile("{\n.reg .pred p, q;\nsetp.ne.u32 p, %1, 0;\nbarrier.cta.red.or.pred q, %2, 128, p;\nselp.u32 %0, 1, 0, q;\n}"
                             : "=r"(anybad) : "r"((uint32_t)bad), "r"(wg + 1) : "memory");
                badmask |= __shfl_sync(~0u, anybad, 0) << mt;
                attn_store(o, head, m64, w4, lane);
            }
        }
        if (badmask) {
#pragma unroll 1
            for (int mt = 0; mt < 2; mt++) {
                if (!((badmask >> mt) & 1)) continue;
                const int m64 = quarter * 8 + mt * 4 + wg;
                uint32_t q[4];
                { const uint4 qq = __ldcg(&g_q[(head * 128 + m64 * 4 + w4) * 32 + lane]); q[0] = qq.x; q[1] = qq.y; q[2] = qq.z; q[3] = qq.w; }
                float o[12];
                attn_safe(o, q, mkdesc(sbase + SM_K, 32768, 128, 0), mkdesc(sbase + SM_V, 128, 32768, 0));
                attn_store(o, head, m64, w4, lane);
            }
        }
        nbar_sync(wg + 1, 128);
        if ((tid & 127) == 32) {
            asm volatile("fence.acq_rel.gpu;" ::: "memory");
            asm volatile("red.relaxed.gpu.global.add.u32 [%0], 1;" :: "l"(g_cnt + (C_O + quarter * 8 + 4 + wg) * 32) : "memory");
            if (badmask & 1) asm volatile("red.relaxed.gpu.global.add.u32 [%0], 1;" :: "l"(g_cnt + (C_O + quarter * 8 + wg) * 32) : "memory");
        }
        TL(6);
        {
            const int nb = idx & 7, jb = idx >> 3;
            const int mbe = (jb >> 2) * 8 + (jb & 3);
            float* supd = reinterpret_cast<float*>(smem + SM_MISC + 512);
            if (warp == 15) nbar_sync(7, 512); else nbar_arrive(7, 512);
            if (warp == 15) {
                flag_wait(C_O + mbe, 32);
                fence_proxy_async_all();
                if (lane == 0) {
                    for (int c = 0; c < 2; c++) {
                        mbar_expect_tx(bars + 8 * (B_OA + c), 32768);
                        tma3d(sbase + SM_K + c * 32768, &maps.o, bars + 8 * (B_OA + c), mbe * 64, c * 4);
                    }
                }
                __syncwarp();
                flag_wait(C_O + mbe + 4, 32);
                fence_proxy_async_all();
                if (lane == 0) {
                    for (int c = 0; c < 2; c++) {
                        mbar_expect_tx(bars + 8 * (B_OA + 2 + c), 32768);
                        tma3d(sbase + SM_V + c * 32768, &maps.o, bars + 8 * (B_OA + 2 + c), (mbe + 4) * 64, c * 4);
                    }
                }
                __syncwarp();
            }
            const int late = wg >> 1, nh = wg & 1;
            const int mb = mbe + late * 4;
            const int g = lane >> 2, t = lane & 3;
            const int row0 = mb * 64 + w4 * 16 + g;
            const int col0 = nb * 64 + nh * 32 + t * 2;
            uint32_t xv[8], nv[8];
#pragma unroll
            for (int i = 0; i < 4; i++) {
                xv[2 * i] = *reinterpret_cast<const uint32_t*>(x + (size_t)row0 * DM + col0 + i * 8);
                xv[2 * i + 1] = *reinterpret_cast<const uint32_t*>(x + (size_t)(row0 + 8) * DM + col0 + i * 8);
                nv[2 * i] = __ldcg(reinterpret_cast<const uint32_t*>(g_xn + (size_t)row0 * DM + col0 + i * 8));
                nv[2 * i + 1] = __ldcg(reinterpret_cast<const uint32_t*>(g_xn + (size_t)(row0 + 8) * DM + col0 + i * 8));
            }
            if (wg == 0) {
                flag_wait(C_FFN, 64);
                const int which = tid >> 6, col = nb * 64 + (tid & 63);
                const float y = __ldcg(&g_ypart[which * 512 + col]) + __ldcg(&g_ypart[1024 + which * 512 + col]) +
                                __ldcg(&g_ypart[2048 + which * 512 + col]) + __ldcg(&g_ypart[3072 + which * 512 + col]);
                supd[tid] = bfr(bfr(y) * __ldcg(&g_gate[which]));
                if (tid < 2) reinterpret_cast<int*>(supd + 128)[tid] = __ldcg(&g_sel[tid]);
            }
            float acc[16];
#pragma unroll
            for (int i = 0; i < 16; i++) acc[i] = 0.f;
            mbar_wait(bars + 8 * B_WO, 0);
            const uint32_t abase = sbase + (late ? SM_V : SM_K);
#pragma unroll 1
            for (int c = 0; c < 8; c++) {
                if ((c & 3) == 0) mbar_wait(bars + 8 * (B_OA + late * 2 + (c >> 2)), 0);
                if (c == 0) TLX(7, 256);
                const uint64_t da = mkdesc(abase + c * 8192, 16, 1024, 1);
                const uint64_t db = mkdesc(sbase + c * 8192 + nh * 64, 8192, 1024, 1);
                WG_FENCE();
#pragma unroll
                for (int k = 0; k < 4; k++) wgmma_n32(acc, da + k * 2, db + k * 128, (c | k) != 0);
                WG_COMMIT();
            }
            __syncthreads();
            const int sel0 = reinterpret_cast<const int*>(supd + 128)[0], sel1 = reinterpret_cast<const int*>(supd + 128)[1];
            WG_WAIT(0);
            TLX(8, 256);
#pragma unroll
            for (int h = 0; h < 2; h++) {
                const int row = row0 + h * 8;
                const int which = row == sel0 ? 0 : (row == sel1 ? 1 : -1);
#pragma unroll
                for (int i = 0; i < 4; i++) {
                    const int col = col0 + i * 8;
                    float b0 = bf_lo(nv[2 * i + h]), b1 = bf_hi(nv[2 * i + h]);
                    if (which >= 0) {
                        b0 = bfr(b0 + supd[which * 64 + col - nb * 64]); b1 = bfr(b1 + supd[which * 64 + col + 1 - nb * 64]);
                    }
                    const float t0 = bfr(bf_lo(xv[2 * i + h]) + bfr(acc[4 * i + 2 * h]));
                    const float t1 = bfr(bf_hi(xv[2 * i + h]) + bfr(acc[4 * i + 2 * h + 1]));
                    *reinterpret_cast<uint32_t*>(out + (size_t)row * DM + col) = packbf(t0 + b0, t1 + b1);
                }
            }
        }
        TLX(9, 256);
    }
    __syncthreads();
    if (tid == 0) {
        __threadfence();
        const unsigned tk = atomicAdd(&g_cnt[C_EXIT * 32], 1u);
        if (tk == gridDim.x - 1) {
            for (int i = 0; i < C_NUM; i++) g_cnt[i * 32] = 0u;
            __threadfence();
        }
    }
}

typedef CUresult (*EncodeFn)(CUtensorMap*, CUtensorMapDataType, cuuint32_t, void*, const cuuint64_t*, const cuuint64_t*,
                             const cuuint32_t*, const cuuint32_t*, CUtensorMapInterleave, CUtensorMapSwizzle,
                             CUtensorMapL2promotion, CUtensorMapFloatOOBfill);

void make_map(EncodeFn fn, CUtensorMap* m, const void* ptr, uint64_t cols, uint64_t rows, uint32_t box_rows, uint32_t box_chunks) {
    cuuint64_t dims[3] = {64, rows, cols / 64};
    cuuint64_t strides[2] = {cols * 2, 128};
    cuuint32_t box[3] = {64, box_rows, box_chunks};
    cuuint32_t es[3] = {1, 1, 1};
    fn(m, CU_TENSOR_MAP_DATA_TYPE_BFLOAT16, 3, const_cast<void*>(ptr), dims, strides, box, es, CU_TENSOR_MAP_INTERLEAVE_NONE,
       CU_TENSOR_MAP_SWIZZLE_128B, CU_TENSOR_MAP_L2_PROMOTION_L2_256B, CU_TENSOR_MAP_FLOAT_OOB_FILL_NONE);
}

}

extern "C" void kernel_launch(void* const* d_in, const int* in_sizes, int n_in, void* d_out, int out_size) {
    const __nv_bfloat16* x = (const __nv_bfloat16*)d_in[0];
    const __nv_bfloat16* wqkv = (const __nv_bfloat16*)d_in[1];
    const __nv_bfloat16* wo = (const __nv_bfloat16*)d_in[2];
    const __nv_bfloat16* wr = (const __nv_bfloat16*)d_in[4];
    const __nv_bfloat16* wgate = (const __nv_bfloat16*)d_in[5];
    const __nv_bfloat16* wup = (const __nv_bfloat16*)d_in[6];
    const __nv_bfloat16* wdown = (const __nv_bfloat16*)d_in[7];
    __nv_bfloat16* out = (__nv_bfloat16*)d_out;

    static EncodeFn enc = nullptr;
    static void* p_xn = nullptr; static void* p_o = nullptr;
    if (!enc) {
        void* fn = nullptr; cudaDriverEntryPointQueryResult qr;
        cudaGetDriverEntryPoint("cuTensorMapEncodeTiled", &fn, cudaEnableDefault, &qr);
        enc = (EncodeFn)fn;
        cudaGetSymbolAddress(&p_xn, g_xn);
        cudaGetSymbolAddress(&p_o, g_o);
        cudaFuncSetAttribute(fused_kernel, cudaFuncAttributeMaxDynamicSharedMemorySize, FUSED_SMEM);
    }
    Maps maps;
    make_map(enc, &maps.g, wgate, FF, DM, 16, 7);
    make_map(enc, &maps.u, wup, FF, DM, 16, 7);
    make_map(enc, &maps.d, wdown, DM, FF, 32, 8);
    make_map(enc, &maps.xn, p_xn, DM, S_LEN, 128, 1);
    make_map(enc, &maps.wqkv, wqkv, 3 * DM, DM, 64, 3);
    make_map(enc, &maps.o, p_o, DM, S_LEN, 64, 4);
    make_map(enc, &maps.wo, wo, DM, DM, 256, 1);

    union { uint32_t u; float f; } scu; scu.u = 128u;

    cudaLaunchConfig_t cfg = {};
    cfg.gridDim = dim3(132); cfg.blockDim = dim3(512); cfg.dynamicSmemBytes = FUSED_SMEM; cfg.stream = cudaStreamPerThread;
    cudaLaunchAttribute at[1];
    at[0].id = cudaLaunchAttributeCooperative;
    at[0].val.cooperative = 1;
    cfg.attrs = at; cfg.numAttrs = 1;
    cudaLaunchKernelEx(&cfg, fused_kernel, maps, x, wr, out, scu.f);
}
```

```cpp
#include <cuda_runtime.h>
#include <cuda_bf16.h>
#include <cuda.h>
#include <stdint.h>
#include <type_traits>

namespace {

constexpr int S_LEN = 2048;
constexpr int DM = 512;
constexpr int NH = 32;
constexpr int FF = 1792;

__device__ __align__(1024) __nv_bfloat16 g_xn[S_LEN * DM];
__device__ __align__(16) float g_r[S_LEN];
__device__ __align__(1024) uint4 g_q[NH * 128 * 32];
__device__ __align__(1024) uint4 g_kv[NH * 8192];
__device__ __align__(1024) __nv_bfloat16 g_o[S_LEN * DM];
__device__ __align__(16) float g_ypart[4 * 2 * DM];
__device__ int g_sel[2];
__device__ float g_gate[2];
constexpr int C_LN = 0, C_QKV = 16, C_O = 24, C_FFN = 56, C_EXIT = 57, C_NUM = 58;
__device__ unsigned g_cnt[C_NUM * 32];

#define TL(slot) do {} while (0)
#define TLX(slot, th) do {} while (0)

__device__ __forceinline__ uint32_t smem_u32(const void* p) { return (uint32_t)__cvta_generic_to_shared(p); }
__device__ __forceinline__ void warp_arrive(int idx) {
    __syncwarp();
    if ((threadIdx.x & 31) == 0)
        asm volatile("red.release.gpu.global.add.u32 [%0], 1;" :: "l"(g_cnt + idx * 32) : "memory");
}
__device__ __forceinline__ void flag_release(int idx) {
    asm volatile("red.release.gpu.global.add.u32 [%0], 1;" :: "l"(g_cnt + idx * 32) : "memory");
}
__device__ __forceinline__ void exit_ticket() {
    unsigned tk;
    asm volatile("atom.acq_rel.gpu.global.add.u32 %0, [%1], 1;" : "=r"(tk) : "l"(g_cnt + C_EXIT * 32) : "memory");
    if (tk == gridDim.x - 1) {
#pragma unroll 1
        for (int i = 0; i < C_NUM; i++) g_cnt[i * 32] = 0u;
    }
}
__device__ __forceinline__ void nbar_arrive(int id, int cnt) { asm volatile("bar.arrive %0, %1;" :: "r"(id), "r"(cnt) : "memory"); }
__device__ __forceinline__ void nbar_sync(int id, int cnt) { asm volatile("bar.sync %0, %1;" :: "r"(id), "r"(cnt) : "memory"); }
__device__ __forceinline__ void flag_wait(int idx, unsigned target) {
    asm volatile("{\n.reg .pred p;\n.reg .u32 n, v;\nmov.u32 n, 0;\n"
                 "FW_%=:\n"
                 "ld.acquire.gpu.global.u32 v, [%0];\n"
                 "setp.ge.u32 p, v, %1;\n"
                 "@p bra FD_%=;\n"
                 "add.u32 n, n, 1;\n"
                 "setp.lt.u32 p, n, 16000000;\n"
                 "@p bra FW_%=;\n"
                 "trap;\n"
                 "FD_%=:\n}"
                 :: "l"(g_cnt + idx * 32), "r"(target) : "memory");
}
__device__ __forceinline__ void flag_wait_all(int idx, unsigned target) {
    asm volatile("{\n.reg .pred p;\n.reg .u32 n, v;\nmov.u32 n, 0;\n"
                 "FW_%=:\n"
                 "ld.acquire.gpu.global.u32 v, [%0];\n"
                 "setp.ge.u32 p, v, %1;\n"
                 "vote.sync.all.pred p, p, 0xffffffff;\n"
                 "@p bra.uni FD_%=;\n"
                 "add.u32 n, n, 1;\n"
                 "setp.lt.u32 p, n, 16000000;\n"
                 "@p bra.uni FW_%=;\n"
                 "trap;\n"
                 "FD_%=:\n}"
                 :: "l"(g_cnt + idx * 32), "r"(target) : "memory");
}
__device__ __forceinline__ void fence_proxy_async_all() { asm volatile("fence.proxy.async.global;" ::: "memory"); }
__device__ __forceinline__ void mbar_init(uint32_t bar, uint32_t cnt) {
    asm volatile("mbarrier.init.shared::cta.b64 [%0], %1;" :: "r"(bar), "r"(cnt) : "memory");
}
__device__ __forceinline__ void mbar_expect_tx(uint32_t bar, uint32_t bytes) {
    asm volatile("mbarrier.arrive.expect_tx.shared::cta.b64 _, [%0], %1;" :: "r"(bar), "r"(bytes) : "memory");
}
__device__ __forceinline__ void mbar_arrive(uint32_t bar) {
    asm volatile("mbarrier.arrive.shared::cta.b64 _, [%0];" :: "r"(bar) : "memory");
}
__device__ __forceinline__ void mbar_wait(uint32_t bar, uint32_t parity) {
    asm volatile("{\n.reg .pred p;\n.reg .u32 n;\nmov.u32 n, 0;\n"
                 "WAIT_%=:\n"
                 "mbarrier.try_wait.parity.shared::cta.b64 p, [%0], %1;\n"
                 "@p bra DONE_%=;\n"
                 "add.u32 n, n, 1;\n"
                 "setp.lt.u32 p, n, 4000000;\n"
                 "@p bra WAIT_%=;\n"
                 "trap;\n"
                 "DONE_%=:\n}"
                 :: "r"(bar), "r"(parity) : "memory");
}
__device__ __forceinline__ void fence_barrier_init() { asm volatile("fence.mbarrier_init.release.cluster;" ::: "memory"); }
__device__ __forceinline__ void fence_proxy_async() { asm volatile("fence.proxy.async.shared::cta;" ::: "memory"); }
__device__ __forceinline__ void tma3d(uint32_t dst, const CUtensorMap* map, uint32_t bar, int row, int chunk) {
    asm volatile("cp.async.bulk.tensor.3d.shared::cluster.global.mbarrier::complete_tx::bytes [%0], [%1, {%3, %4, %5}], [%2];"
                 :: "r"(dst), "l"((uint64_t)map), "r"(bar), "r"(0), "r"(row), "r"(chunk) : "memory");
}
__device__ __forceinline__ void bulk_g2s(uint32_t dst, const void* src, uint32_t bytes, uint32_t bar) {
    asm volatile("cp.async.bulk.shared::cluster.global.mbarrier::complete_tx::bytes [%0], [%1], %2, [%3];"
                 :: "r"(dst), "l"((uint64_t)src), "r"(bytes), "r"(bar) : "memory");
}
__device__ __forceinline__ void l2_prefetch(const void* src, uint32_t bytes) {
    asm volatile("cp.async.bulk.prefetch.L2.global [%0], %1;" :: "l"((uint64_t)src), "r"(bytes) : "memory");
}
__device__ __forceinline__ void map_prefetch(const CUtensorMap* m) {
    asm volatile("prefetch.tensormap [%0];" :: "l"((uint64_t)m) : "memory");
}
__device__ __forceinline__ uint64_t mkdesc(uint32_t addr, uint32_t lbo, uint32_t sbo, uint32_t swz) {
    return (uint64_t)((addr & 0x3FFFF) >> 4) | ((uint64_t)(lbo >> 4) << 16) | ((uint64_t)(sbo >> 4) << 32) | ((uint64_t)swz << 62);
}
#define WG_FENCE() asm volatile("wgmma.fence.sync.aligned;" ::: "memory")
#define WG_COMMIT() asm volatile("wgmma.commit_group.sync.aligned;" ::: "memory")
#define WG_WAIT(n) asm volatile("wgmma.wait_group.sync.aligned %0;" :: "n"(n) : "memory")

__device__ __forceinline__ float ex2(float x) { float y; asm("ex2.approx.ftz.f32 %0, %1;" : "=f"(y) : "f"(x)); return y; }
__device__ __forceinline__ uint32_t packbf(float lo, float hi) {
    uint32_t r; asm("cvt.rn.bf16x2.f32 %0, %1, %2;" : "=r"(r) : "f"(hi), "f"(lo)); return r;
}
__device__ __forceinline__ float bf_lo(uint32_t v) { return __uint_as_float(v << 16); }
__device__ __forceinline__ float bf_hi(uint32_t v) { return __uint_as_float(v & 0xffff0000u); }
__device__ __forceinline__ float bfr(float x) { return __bfloat162float(__float2bfloat16_rn(x)); }

__device__ __forceinline__ void wgmma_n192(float (&d)[96], uint64_t da, uint64_t db, int scale_d) {
    asm volatile("{\n.reg .pred p;\nsetp.ne.b32 p, %98, 0;\n"
        "wgmma.mma_async.sync.aligned.m64n192k16.f32.bf16.bf16 "
        "{%0,%1,%2,%3,%4,%5,%6,%7,%8,%9,%10,%11,%12,%13,%14,%15,%16,%17,%18,%19,%20,%21,%22,%23,"
        "%24,%25,%26,%27,%28,%29,%30,%31,%32,%33,%34,%35,%36,%37,%38,%39,%40,%41,%42,%43,%44,%45,%46,%47,"
        "%48,%49,%50,%51,%52,%53,%54,%55,%56,%57,%58,%59,%60,%61,%62,%63,%64,%65,%66,%67,%68,%69,%70,%71,"
        "%72,%73,%74,%75,%76,%77,%78,%79,%80,%81,%82,%83,%84,%85,%86,%87,%88,%89,%90,%91,%92,%93,%94,%95}, "
        "%96, %97, p, 1, 1, 0, 1;\n}"
        : "+f"(d[0]), "+f"(d[1]), "+f"(d[2]), "+f"(d[3]), "+f"(d[4]), "+f"(d[5]), "+f"(d[6]), "+f"(d[7]),
          "+f"(d[8]), "+f"(d[9]), "+f"(d[10]), "+f"(d[11]), "+f"(d[12]), "+f"(d[13]), "+f"(d[14]), "+f"(d[15]),
          "+f"(d[16]), "+f"(d[17]), "+f"(d[18]), "+f"(d[19]), "+f"(d[20]), "+f"(d[21]), "+f"(d[22]), "+f"(d[23]),
          "+f"(d[24]), "+f"(d[25]), "+f"(d[26]), "+f"(d[27]), "+f"(d[28]), "+f"(d[29]), "+f"(d[30]), "+f"(d[31]),
          "+f"(d[32]), "+f"(d[33]), "+f"(d[34]), "+f"(d[35]), "+f"(d[36]), "+f"(d[37]), "+f"(d[38]), "+f"(d[39]),
          "+f"(d[40]), "+f"(d[41]), "+f"(d[42]), "+f"(d[43]), "+f"(d[44]), "+f"(d[45]), "+f"(d[46]), "+f"(d[47]),
          "+f"(d[48]), "+f"(d[49]), "+f"(d[50]), "+f"(d[51]), "+f"(d[52]), "+f"(d[53]), "+f"(d[54]), "+f"(d[55]),
          "+f"(d[56]), "+f"(d[57]), "+f"(d[58]), "+f"(d[59]), "+f"(d[60]), "+f"(d[61]), "+f"(d[62]), "+f"(d[63]),
          "+f"(d[64]), "+f"(d[65]), "+f"(d[66]), "+f"(d[67]), "+f"(d[68]), "+f"(d[69]), "+f"(d[70]), "+f"(d[71]),
          "+f"(d[72]), "+f"(d[73]), "+f"(d[74]), "+f"(d[75]), "+f"(d[76]), "+f"(d[77]), "+f"(d[78]), "+f"(d[79]),
          "+f"(d[80]), "+f"(d[81]), "+f"(d[82]), "+f"(d[83]), "+f"(d[84]), "+f"(d[85]), "+f"(d[86]), "+f"(d[87]),
          "+f"(d[88]), "+f"(d[89]), "+f"(d[90]), "+f"(d[91]), "+f"(d[92]), "+f"(d[93]), "+f"(d[94]), "+f"(d[95])
        : "l"(da), "l"(db), "r"(scale_d));
}

constexpr float SHIFT = 90.0f;
constexpr float QS = 0.25f * 1.4426950408889634f * 18446744073709551616.0f;
constexpr float scq = 0.25f * 1.4426950408889634f * 3.3087224502121107e-24f;

__device__ __forceinline__ uint32_t polyexp(float lo, float hi) {
    uint32_t w, g, q, h;
    asm("cvt.pack.sat.s16.s32 %0, %1, %2;" : "=r"(w) : "r"(__float_as_uint(hi)), "r"(__float_as_uint(lo)));
    g = w & 0x007F007Fu;
    asm("fma.rn.f16x2 %0, %1, %2, %3;" : "=r"(q) : "r"(g), "r"(0xf940f940u), "r"(0x35513551u));
    asm("mul.rn.f16x2 %0, %1, %2;" : "=r"(h) : "r"(q), "r"(g));
    return w - h;
}
__device__ __forceinline__ void qk64(float (&s)[32], const uint32_t (&q)[4], uint64_t db) {
    asm volatile("wgmma.mma_async.sync.aligned.m64n64k16.f32.bf16.bf16 "
        "{%0,%1,%2,%3,%4,%5,%6,%7,%8,%9,%10,%11,%12,%13,%14,%15,%16,%17,%18,%19,%20,%21,%22,%23,%24,%25,%26,%27,%28,%29,%30,%31}, "
        "{%32,%33,%34,%35}, %36, 0, 1, 1, 0;"
        : "=f"(s[0]), "=f"(s[1]), "=f"(s[2]), "=f"(s[3]), "=f"(s[4]), "=f"(s[5]), "=f"(s[6]), "=f"(s[7]),
          "=f"(s[8]), "=f"(s[9]), "=f"(s[10]), "=f"(s[11]), "=f"(s[12]), "=f"(s[13]), "=f"(s[14]), "=f"(s[15]),
          "=f"(s[16]), "=f"(s[17]), "=f"(s[18]), "=f"(s[19]), "=f"(s[20]), "=f"(s[21]), "=f"(s[22]), "=f"(s[23]),
          "=f"(s[24]), "=f"(s[25]), "=f"(s[26]), "=f"(s[27]), "=f"(s[28]), "=f"(s[29]), "=f"(s[30]), "=f"(s[31])
        : "r"(q[0]), "r"(q[1]), "r"(q[2]), "r"(q[3]), "l"(db));
}
__device__ __forceinline__ void pv24(float (&o)[12], uint32_t a0, uint32_t a1, uint32_t a2, uint32_t a3, uint64_t db) {
    asm volatile("wgmma.mma_async.sync.aligned.m64n24k16.f32.bf16.bf16 "
        "{%0,%1,%2,%3,%4,%5,%6,%7,%8,%9,%10,%11}, {%12,%13,%14,%15}, %16, 1, 1, 1, 1;"
        : "+f"(o[0]), "+f"(o[1]), "+f"(o[2]), "+f"(o[3]), "+f"(o[4]), "+f"(o[5]), "+f"(o[6]), "+f"(o[7]),
          "+f"(o[8]), "+f"(o[9]), "+f"(o[10]), "+f"(o[11])
        : "r"(a0), "r"(a1), "r"(a2), "r"(a3), "l"(db));
}

__device__ __forceinline__ void attn_safe(float (&o)[12], const uint32_t (&q)[4], uint64_t kdesc0, uint64_t vdesc0) {
    float s[32];
    float m0 = -INFINITY, m1 = -INFINITY;
#pragma unroll
    for (int i = 0; i < 12; i++) o[i] = 0.f;
#pragma unroll 1
    for (int j = 0; j < 32; j++) {
        WG_FENCE();
        qk64(s, q, kdesc0 + (uint64_t)((j >> 2) * (20480 / 16) + (j & 3) * 64));
        WG_COMMIT(); WG_WAIT(0);
        float n0 = m0, n1 = m1;
#pragma unroll
        for (int i = 0; i < 8; i++) { n0 = fmaxf(n0, fmaxf(s[4 * i], s[4 * i + 1])); n1 = fmaxf(n1, fmaxf(s[4 * i + 2], s[4 * i + 3])); }
        n0 = fmaxf(n0, __shfl_xor_sync(~0u, n0, 1)); n0 = fmaxf(n0, __shfl_xor_sync(~0u, n0, 2));
        n1 = fmaxf(n1, __shfl_xor_sync(~0u, n1, 1)); n1 = fmaxf(n1, __shfl_xor_sync(~0u, n1, 2));
        const float c0 = ex2((m0 - n0) * QS), c1 = ex2((m1 - n1) * QS);
        m0 = n0; m1 = n1;
#pragma unroll
        for (int i = 0; i < 3; i++) { o[4 * i] *= c0; o[4 * i + 1] *= c0; o[4 * i + 2] *= c1; o[4 * i + 3] *= c1; }
        uint32_t p[16];
#pragma unroll
        for (int i = 0; i < 8; i++) {
            p[2 * i] = packbf(ex2((s[4 * i] - m0) * QS), ex2((s[4 * i + 1] - m0) * QS));
            p[2 * i + 1] = packbf(ex2((s[4 * i + 2] - m1) * QS), ex2((s[4 * i + 3] - m1) * QS));
        }
        WG_FENCE();
#pragma unroll
        for (int kk = 0; kk < 4; kk++) pv24(o, p[4 * kk], p[4 * kk + 1], p[4 * kk + 2], p[4 * kk + 3], vdesc0 + (uint64_t)((j >> 2) * (20480 / 16) + (j & 3) * 64 + kk * 16));
        WG_COMMIT(); WG_WAIT(0);
    }
}

__device__ __forceinline__ void attn_store(const float (&o)[12], int head, int m64, int warp, int lane) {
    const int g = lane >> 2, t = lane & 3;
    const int row = m64 * 64 + warp * 16 + g;
    const float i0 = 1.f / o[8], i1 = 1.f / o[10];
    uint32_t* p0 = reinterpret_cast<uint32_t*>(g_o + (size_t)row * DM + head * 16 + t * 2);
    uint32_t* p1 = reinterpret_cast<uint32_t*>(g_o + (size_t)(row + 8) * DM + head * 16 + t * 2);
    p0[0] = packbf(o[0] * i0, o[1] * i0); p0[4] = packbf(o[4] * i0, o[5] * i0);
    p1[0] = packbf(o[2] * i1, o[3] * i1); p1[4] = packbf(o[6] * i1, o[7] * i1);
}

constexpr int FS_N = 4;
constexpr int FS_BYTES = 32768;
__device__ __forceinline__ void ldsm4t(uint32_t& r0, uint32_t& r1, uint32_t& r2, uint32_t& r3, uint32_t addr) {
    asm volatile("ldmatrix.sync.aligned.m8n8.x4.trans.shared.b16 {%0,%1,%2,%3}, [%4];" : "=r"(r0), "=r"(r1), "=r"(r2), "=r"(r3) : "r"(addr) : "memory");
}
__device__ __forceinline__ void mma16816(float (&d)[4], uint32_t a0, uint32_t a2, uint32_t b0, uint32_t b1) {
    asm volatile("mma.sync.aligned.m16n8k16.row.col.f32.bf16.bf16.f32 {%0,%1,%2,%3}, {%4,%5,%6,%5}, {%7,%8}, {%0,%1,%2,%3};"
                 : "+f"(d[0]), "+f"(d[1]), "+f"(d[2]), "+f"(d[3]) : "r"(a0), "r"(0u), "r"(a2), "r"(b0), "r"(b1));
}
__device__ void ffn_block(int c, uint8_t* smem, uint32_t sbase, const CUtensorMap* mapG, const CUtensorMap* mapU, const CUtensorMap* mapD) {
    const int tid = threadIdx.x, warp = tid >> 5, lane = tid & 31;
    uint32_t* sx = reinterpret_cast<uint32_t*>(smem + FS_N * FS_BYTES);
    __nv_bfloat16* sh = reinterpret_cast<__nv_bfloat16*>(sx + 512);
    const uint32_t bars = sbase + FS_N * FS_BYTES + 8192;
    float* tv = reinterpret_cast<float*>(smem + FS_N * FS_BYTES + 4096);
    int* ti = reinterpret_cast<int*>(tv + 32);
    int* ssel = ti + 32;
    auto issue = [&](int item) {
        const int slot = item % FS_N;
        const uint32_t dst = sbase + slot * FS_BYTES, bar = bars + 8 * slot;
        mbar_expect_tx(bar, item < 32 ? 28672 : 32768);
        if (item < 32) {
            tma3d(dst, mapG, bar, item * 16, c * 7);
            tma3d(dst + 14336, mapU, bar, item * 16, c * 7);
        } else {
            tma3d(dst, mapD, bar, c * 448 + (item - 32) * 32, 0);
        }
    };
    if (tid == 0) {
        for (int i = 0; i < FS_N; i++) mbar_init(bars + 8 * i, 1);
        fence_barrier_init();
        for (int i = 0; i < FS_N; i++) issue(i);
    }
    flag_wait(C_LN + warp, 8);
    __syncthreads();
    float b1 = -INFINITY, b2 = -INFINITY; int i1 = 0x7fffffff, i2 = 0x7fffffff;
    auto push = [&](float v, int i) {
        if (v > b1 || (v == b1 && i < i1)) { b2 = b1; i2 = i1; b1 = v; i1 = i; }
        else if (v > b2 || (v == b2 && i < i2)) { b2 = v; i2 = i; }
    };
    {
        const float4 rv = __ldcg(reinterpret_cast<const float4*>(g_r) + tid);
        push(rv.x, 4 * tid); push(rv.y, 4 * tid + 1); push(rv.z, 4 * tid + 2); push(rv.w, 4 * tid + 3);
    }
#pragma unroll
    for (int o = 16; o > 0; o >>= 1) {
        float v1 = __shfl_xor_sync(~0u, b1, o), v2 = __shfl_xor_sync(~0u, b2, o);
        int j1 = __shfl_xor_sync(~0u, i1, o), j2 = __shfl_xor_sync(~0u, i2, o);
        push(v1, j1); push(v2, j2);
    }
    if (lane == 0) { tv[2 * warp] = b1; ti[2 * warp] = i1; tv[2 * warp + 1] = b2; ti[2 * warp + 1] = i2; }
    __syncthreads();
    if (warp == 1) {
        b1 = tv[lane]; i1 = ti[lane]; b2 = -INFINITY; i2 = 0x7fffffff;
#pragma unroll
        for (int o = 16; o > 0; o >>= 1) {
            float v1 = __shfl_xor_sync(~0u, b1, o), v2 = __shfl_xor_sync(~0u, b2, o);
            int j1 = __shfl_xor_sync(~0u, i1, o), j2 = __shfl_xor_sync(~0u, i2, o);
            push(v1, j1); push(v2, j2);
        }
        if (lane == 0) {
            i1 = min(max(i1, 0), S_LEN - 1); i2 = min(max(i2, 0), S_LEN - 1);
            ssel[0] = i1; ssel[1] = i2;
            if (c == 0) {
                g_sel[0] = i1; g_sel[1] = i2;
                g_gate[0] = bfr(1.f / (1.f + __expf(-bfr(b1))));
                g_gate[1] = bfr(1.f / (1.f + __expf(-bfr(b2))));
            }
        }
    }
    __syncthreads();
    sx[tid] = __ldcg(reinterpret_cast<const uint32_t*>(g_xn + (size_t)ssel[tid >> 8] * DM + (tid & 255) * 2));
    __syncthreads();
    TL(1);
    const int g = lane >> 2, t = lane & 3;
    const int lrow = lane & 15, lsel = lane >> 4;
    {
        float ag[4][4], au[4][4];
#pragma unroll
        for (int j = 0; j < 4; j++) { ag[j][0] = ag[j][1] = ag[j][2] = ag[j][3] = 0.f; au[j][0] = au[j][1] = au[j][2] = au[j][3] = 0.f; }
#pragma unroll 1
        for (int it = 0; it < 32; it++) {
            const int slot = it % FS_N;
            const uint32_t a0 = g < 2 ? sx[g * 256 + it * 8 + t] : 0u, a2 = g < 2 ? sx[g * 256 + it * 8 + 4 + t] : 0u;
            mbar_wait(bars + 8 * slot, (it / FS_N) & 1);
            const uint32_t base = sbase + slot * FS_BYTES + lsel * 14336 + lrow * 128;
#pragma unroll
            for (int j = 0; j < 4; j++) {
                const int nt = warp + j * 16;
                if (nt < 56) {
                    uint32_t b0, b1, b2, b3;
                    ldsm4t(b0, b1, b2, b3, base + (nt >> 3) * 2048 + (((nt & 7) ^ (lrow & 7)) << 4));
                    mma16816(ag[j], a0, a2, b0, b1);
                    mma16816(au[j], a0, a2, b2, b3);
                }
            }
            __syncthreads();
            if (tid == 480) issue(it + FS_N);
        }
        if (g < 2) {
#pragma unroll
            for (int j = 0; j < 4; j++) {
                const int nt = warp + j * 16;
                if (nt < 56) {
#pragma unroll
                    for (int e = 0; e < 2; e++) {
                        const float gs = bfr(ag[j][e]), us = bfr(au[j][e]);
                        const float sg = bfr(gs / (1.f + __expf(-gs)));
                        sh[g * 448 + nt * 8 + t * 2 + e] = __float2bfloat16_rn(sg * us);
                    }
                }
            }
        }
        __syncthreads();
    }
    TL(2);
    {
        const uint32_t* shw = reinterpret_cast<const uint32_t*>(sh);
        float a[4][4];
#pragma unroll
        for (int j = 0; j < 4; j++) a[j][0] = a[j][1] = a[j][2] = a[j][3] = 0.f;
#pragma unroll 1
        for (int it = 32; it < 46; it++) {
            const int slot = it % FS_N;
            uint32_t af[4];
#pragma unroll
            for (int q = 0; q < 4; q++) af[q] = g < 2 ? shw[g * 224 + (it - 32) * 16 + q * 4 + t] : 0u;
            mbar_wait(bars + 8 * slot, (it / FS_N) & 1);
            const uint32_t base = sbase + slot * FS_BYTES + (warp >> 1) * 4096 + lane * 128;
#pragma unroll
            for (int j = 0; j < 4; j++) {
                const int u = (warp & 1) * 4 + j;
                uint32_t b0, b1, b2, b3;
                ldsm4t(b0, b1, b2, b3, base + ((u ^ (lane & 7)) << 4));
                mma16816(a[j], af[0], af[1], b0, b1);
                mma16816(a[j], af[2], af[3], b2, b3);
            }
            __syncthreads();
            if (tid == 480 && it + FS_N < 46) issue(it + FS_N);
        }
        if (g < 2) {
#pragma unroll
            for (int j = 0; j < 4; j++)
                *reinterpret_cast<float2*>(&g_ypart[c * 1024 + g * 512 + (warp * 4 + j) * 8 + t * 2]) = make_float2(a[j][0], a[j][1]);
        }
    }
    warp_arrive(C_FFN);
}

__device__ __forceinline__ void wgmma_n32(float (&d)[16], uint64_t da, uint64_t db, int scale_d) {
    asm volatile("{\n.reg .pred p;\nsetp.ne.b32 p, %18, 0;\n"
        "wgmma.mma_async.sync.aligned.m64n32k16.f32.bf16.bf16 "
        "{%0,%1,%2,%3,%4,%5,%6,%7,%8,%9,%10,%11,%12,%13,%14,%15}, "
        "%16, %17, p, 1, 1, 0, 1;\n}"
        : "+f"(d[0]), "+f"(d[1]), "+f"(d[2]), "+f"(d[3]), "+f"(d[4]), "+f"(d[5]), "+f"(d[6]), "+f"(d[7]),
          "+f"(d[8]), "+f"(d[9]), "+f"(d[10]), "+f"(d[11]), "+f"(d[12]), "+f"(d[13]), "+f"(d[14]), "+f"(d[15])
        : "l"(da), "l"(db), "r"(scale_d));
}

constexpr int G_ST = 4;
constexpr int G_STAGE = 16384 + 24576;
constexpr int SM_KV = 65536, KV_CH = 20480, SM_MISC = 229376;
constexpr int FUSED_SMEM = SM_MISC + 2048;
constexpr int B_FULL = 0, B_EMPTY = 4, B_KV = 8, B_WO = 16, B_OA = 18, B_NUM = 22;

struct Maps { CUtensorMap xn, wqkv, o, wo, g, u, d; };

__global__ void __launch_bounds__(512, 1) fused_kernel(const __grid_constant__ Maps maps, const __nv_bfloat16* __restrict__ x,
                                                       const __nv_bfloat16* __restrict__ wr, __nv_bfloat16* __restrict__ out, float sc) {
    extern __shared__ __align__(1024) uint8_t smem[];
    const uint32_t sbase = smem_u32(smem);
    const int tid = threadIdx.x, warp = __shfl_sync(~0u, tid >> 5, 0), lane = tid & 31;
    const uint32_t bars = sbase + SM_MISC;
    TL(0);
    if (sbase & 1023u) __trap();
    if (blockIdx.x < 4) {
        ffn_block(blockIdx.x, smem, sbase, &maps.g, &maps.u, &maps.d);
        __syncthreads();
        if (tid == 0) exit_ticket();
        TL(3);
    } else {
        const int idx = blockIdx.x - 4;
        const int wg = warp >> 2;
        {
            const int row = idx * 16 + warp;
            const uint4* xr = reinterpret_cast<const uint4*>(x + (size_t)row * DM);
            const uint4 a = xr[lane], b = xr[32 + lane];
            const uint4* wp = reinterpret_cast<const uint4*>(wr);
            const uint4 wa = wp[lane], wb = wp[32 + lane];
            if (tid == 480) {
                for (int s = 0; s < G_ST; s++) { mbar_init(bars + 8 * (B_FULL + s), 2); mbar_init(bars + 8 * (B_EMPTY + s), 2); }
                for (int c = B_KV; c < B_NUM; c++) mbar_init(bars + 8 * c, 1);
                fence_barrier_init();
                for (int c = 0; c < G_ST; c++) {
                    mbar_expect_tx(bars + 8 * (B_FULL + c), 24576);
                    tma3d(sbase + c * G_STAGE + 16384, &maps.wqkv, bars + 8 * (B_FULL + c), c * 64, (idx & 7) * 3);
                }
                map_prefetch(&maps.xn);
            }
            __syncwarp();
            const uint32_t u[8] = {a.x, a.y, a.z, a.w, b.x, b.y, b.z, b.w};
            const uint32_t w[8] = {wa.x, wa.y, wa.z, wa.w, wb.x, wb.y, wb.z, wb.w};
            float f[16];
            float sum = 0.f;
#pragma unroll
            for (int i = 0; i < 8; i++) { f[2 * i] = bf_lo(u[i]); f[2 * i + 1] = bf_hi(u[i]); sum += f[2 * i] + f[2 * i + 1]; }
#pragma unroll
            for (int o = 16; o > 0; o >>= 1) sum += __shfl_xor_sync(~0u, sum, o);
            const float mean = sum * (1.f / DM);
            float sq = 0.f;
#pragma unroll
            for (int i = 0; i < 16; i++) { const float d = f[i] - mean; sq = fmaf(d, d, sq); }
#pragma unroll
            for (int o = 16; o > 0; o >>= 1) sq += __shfl_xor_sync(~0u, sq, o);
            const float mb_ = bfr(mean);
            const float vb = bfr(sq * (1.f / DM));
            const float rinv = 1.f / bfr(sqrtf(bfr(vb + 1e-5f)));
            uint32_t o[8];
            float r = 0.f;
#pragma unroll
            for (int i = 0; i < 8; i++) {
                const float d0 = bfr(f[2 * i] - mb_), d1 = bfr(f[2 * i + 1] - mb_);
                o[i] = packbf(d0 * rinv, d1 * rinv);
                r = fmaf(bf_lo(o[i]), bf_lo(w[i]), r);
                r = fmaf(bf_hi(o[i]), bf_hi(w[i]), r);
            }
            uint4* xo = reinterpret_cast<uint4*>(g_xn + (size_t)row * DM);
            xo[lane] = make_uint4(o[0], o[1], o[2], o[3]);
            xo[32 + lane] = make_uint4(o[4], o[5], o[6], o[7]);
#pragma unroll
            for (int of = 16; of > 0; of >>= 1) r += __shfl_xor_sync(~0u, r, of);
            if (lane == 0) g_r[row] = r;
        }
        __syncthreads();
        if (tid == 416) flag_release(C_LN + (idx >> 3));
        TL(1);
        {
            const int nb = idx & 7, mb = idx >> 3;
            if (warp == 15) {
                for (int c = G_ST; c < 8; c++) {
                    const int s = c - G_ST;
                    mbar_wait(bars + 8 * (B_EMPTY + s), 0);
                    if (lane == 0) {
                        mbar_expect_tx(bars + 8 * (B_FULL + s), 24576);
                        tma3d(sbase + s * G_STAGE + 16384, &maps.wqkv, bars + 8 * (B_FULL + s), c * 64, nb * 3);
                    }
                    __syncwarp();
                }
            } else if (warp == 14) {
                flag_wait(C_LN + mb, 8);
                fence_proxy_async_all();
                for (int c = 0; c < 8; c++) {
                    const int s = c & (G_ST - 1);
                    if (c >= G_ST) mbar_wait(bars + 8 * (B_EMPTY + s), 0);
                    if (lane == 0) {
                        mbar_expect_tx(bars + 8 * (B_FULL + s), 16384);
                        tma3d(sbase + s * G_STAGE, &maps.xn, bars + 8 * (B_FULL + s), mb * 128, c);
                    }
                    __syncwarp();
                }
            } else if (wg < 2) {
                float acc[96];
#pragma unroll
                for (int i = 0; i < 96; i++) acc[i] = 0.f;
#pragma unroll 1
                for (int c = 0; c < 8; c++) {
                    const int s = c & (G_ST - 1);
                    const uint32_t st = sbase + s * G_STAGE;
                    mbar_wait(bars + 8 * (B_FULL + s), c >> 2);
                    if (c == 0) TL(2);
                    const uint64_t da = mkdesc(st + wg * 8192, 16, 1024, 1);
                    const uint64_t db = mkdesc(st + 16384, 8192, 1024, 1);
                    WG_FENCE();
#pragma unroll
                    for (int k = 0; k < 4; k++) wgmma_n192(acc, da + k * 2, db + k * 128, (c | k) != 0);
                    WG_COMMIT();
                    if (c <= G_ST) {
                        WG_WAIT(1);
                        if (c >= 1 && (tid & 127) == 0) mbar_arrive(bars + 8 * (B_EMPTY + c - 1));
                    }
                }
                WG_WAIT(0);
                nbar_arrive(6, 512);
                TL(3);
                const int g = lane >> 2, t = lane & 3;
                const int mt = mb * 8 + warp;
#pragma unroll
                for (int hh = 0; hh < 12; hh++) {
                    const int gh = nb * 12 + hh;
                    const float* a = &acc[hh * 8];
                    if (gh < 32) {
                        g_q[(gh * 128 + mt) * 32 + lane] = make_uint4(packbf(a[0], a[1]), packbf(a[2], a[3]), packbf(a[4], a[5]), packbf(a[6], a[7]));
                    } else {
                        const int isv = gh >= 64;
                        uint32_t* dst = reinterpret_cast<uint32_t*>(g_kv + ((gh & 31) * 8 + (mt >> 4)) * 1024 + isv * 512) + ((mt & 15) * 16 + g) * 4 + t;
                        const float ks = isv ? 1.0f : 5.421010862427522e-20f;
                        dst[0] = packbf(a[0] * ks, a[1] * ks);
                        dst[32] = packbf(a[2] * ks, a[3] * ks);
                        dst[1024] = packbf(a[4] * ks, a[5] * ks);
                        dst[1024 + 32] = packbf(a[6] * ks, a[7] * ks);
                    }
                }
                TL(10);
                nbar_sync(8, 256);
                if (tid == 0) flag_release(C_QKV + nb);
            }
        }
        TL(4);
        uint32_t badmask = 0;
        const int head = idx >> 2, quarter = idx & 3, w4 = warp & 3;
        {
            if (warp == 15) {
                flag_wait_all(C_QKV + ((lane % 3) * 32 + head) / 12, 16);
                nbar_sync(6, 512);
                fence_proxy_async_all();
                if (lane == 0) {
                    const uint8_t* kvp = reinterpret_cast<const uint8_t*>(g_kv + head * 8192);
#pragma unroll 1
                    for (int c = 0; c < 2; c++) {
                        mbar_expect_tx(bars + 8 * (B_KV + c), 16384);
                        bulk_g2s(sbase + SM_KV + c * KV_CH, kvp + c * 16384, 16384, bars + 8 * (B_KV + c));
                    }
                }
                __syncwarp();
            } else if (wg >= 2) {
                nbar_sync(6, 512);
#pragma unroll 1
                for (int i = tid - 256; i < 2048; i += 224)
                    *reinterpret_cast<uint4*>(smem + SM_KV + (i >> 8) * KV_CH + 16384 + (i & 255) * 16) = make_uint4(0x3f803f80u, 0x3f803f80u, 0x3f803f80u, 0x3f803f80u);
                fence_proxy_async();
            }
            __syncthreads();
            if (tid == 480) {
                const uint8_t* kvp = reinterpret_cast<const uint8_t*>(g_kv + head * 8192);
#pragma unroll 1
                for (int c = 2; c < 8; c++) {
                    mbar_expect_tx(bars + 8 * (B_KV + c), 16384);
                    bulk_g2s(sbase + SM_KV + c * KV_CH, kvp + c * 16384, 16384, bars + 8 * (B_KV + c));
                }
            } else if (tid == 352) {
                mbar_expect_tx(bars + 8 * B_WO, 65536);
                tma3d(sbase, &maps.wo, bars + 8 * B_WO, 0, idx & 7);
                tma3d(sbase + 32768, &maps.wo, bars + 8 * B_WO, 256, idx & 7);
                map_prefetch(&maps.o);
            }
            __syncwarp();
            const uint64_t kdesc0 = mkdesc(sbase + SM_KV, 4096, 128, 0);
            const uint64_t vdesc0 = mkdesc(sbase + SM_KV + 8192, 128, 4096, 0);
#pragma unroll 1
            for (int mt = 0; mt < 2; mt++) {
                const int m64 = quarter * 8 + mt * 4 + wg;
                uint32_t q[4];
                { const uint4 qq = __ldcg(&g_q[(head * 128 + m64 * 4 + w4) * 32 + lane]); q[0] = qq.x; q[1] = qq.y; q[2] = qq.z; q[3] = qq.w; }
                float s[32], s2[32], o[12];
#pragma unroll
                for (int i = 0; i < 12; i++) o[i] = 0.f;
                mbar_wait(bars + 8 * B_KV, 0);
                if (mt == 0) TL(5);
                WG_FENCE();
                qk64(s, q, kdesc0);
                WG_COMMIT(); WG_WAIT(0);
                float mx0 = -INFINITY, mx1 = -INFINITY;
#pragma unroll
                for (int i = 0; i < 8; i++) { mx0 = fmaxf(mx0, fmaxf(s[4 * i], s[4 * i + 1])); mx1 = fmaxf(mx1, fmaxf(s[4 * i + 2], s[4 * i + 3])); }
                mx0 = fmaxf(mx0, __shfl_xor_sync(~0u, mx0, 1)); mx0 = fmaxf(mx0, __shfl_xor_sync(~0u, mx0, 2));
                mx1 = fmaxf(mx1, __shfl_xor_sync(~0u, mx1, 1)); mx1 = fmaxf(mx1, __shfl_xor_sync(~0u, mx1, 2));
                if (mt == 1 && !badmask) {
                    nbar_sync(wg + 1, 128);
                    if ((tid & 127) == 0) flag_release(C_O + m64 - 4);
                }
                float cm0 = -(ceilf(mx0 * QS) + SHIFT), cm1 = -(ceilf(mx1 * QS) + SHIFT);
                float cp0 = (cm0 + 127.f) * sc, cp1 = (cm1 + 127.f) * sc;
                asm volatile("" : "+f"(cm0), "+f"(cm1), "+f"(cp0), "+f"(cp1));
                uint64_t kd = kdesc0, vd = vdesc0;
                auto step = [&](float (&sc_)[32], float (&sn)[32], uint32_t kinc, uint32_t vinc) {
                    kd += kinc;
                    WG_FENCE();
                    qk64(sn, q, kd);
                    WG_COMMIT();
#pragma unroll
                    for (int kk = 0; kk < 4; kk++) {
                        const int i0 = kk * 2, i1 = kk * 2 + 1;
                        const uint32_t p0 = packbf(ex2(fmaf(sc_[4 * i0], QS, cm0)), ex2(fmaf(sc_[4 * i0 + 1], QS, cm0)));
                        const uint32_t p1 = packbf(ex2(fmaf(sc_[4 * i0 + 2], QS, cm1)), ex2(fmaf(sc_[4 * i0 + 3], QS, cm1)));
                        const uint32_t p2 = polyexp(fmaf(sc_[4 * i1], scq, cp0), fmaf(sc_[4 * i1 + 1], scq, cp0));
                        const uint32_t p3 = polyexp(fmaf(sc_[4 * i1 + 2], scq, cp1), fmaf(sc_[4 * i1 + 3], scq, cp1));
                        WG_FENCE();
                        pv24(o, p0, p1, p2, p3, vd);
                        vd += kk == 3 ? vinc : 16u;
                    }
                    WG_COMMIT();
                    WG_WAIT(1);
                };
#pragma unroll 1
                for (int c = 0; c < 16; c++) {
                    if (mt == 0 && (c & 1) == 0 && c < 14) mbar_wait(bars + 8 * B_KV + 4 * c + 8, 0);
                    const uint32_t hop = (c & 1) ? (KV_CH - 4096) / 16 : 0u;
                    step(s, s2, 64u, 16u); step(s2, s, 64u + (c == 15 ? 0u : hop), 16u + hop);
                }
                WG_WAIT(0);
                bool bad = !(o[8] > 0.f) || !(o[10] > 0.f);
#pragma unroll
                for (int i = 0; i < 12; i++) bad = bad || !(fabsf(o[i]) <= 3.0e38f);
                uint32_t anybad;
                asm volatile("{\n.reg .pred p, q;\nsetp.ne.u32 p, %1, 0;\nbarrier.cta.red.or.pred q, %2, 128, p;\nselp.u32 %0, 1, 0, q;\n}"
                             : "=r"(anybad) : "r"((uint32_t)bad), "r"(wg + 1) : "memory");
                badmask |= __shfl_sync(~0u, anybad, 0) << mt;
                attn_store(o, head, m64, w4, lane);
            }
        }
        if (badmask) {
#pragma unroll 1
            for (int mt = 0; mt < 2; mt++) {
                if (!((badmask >> mt) & 1)) continue;
                const int m64 = quarter * 8 + mt * 4 + wg;
                uint32_t q[4];
                { const uint4 qq = __ldcg(&g_q[(head * 128 + m64 * 4 + w4) * 32 + lane]); q[0] = qq.x; q[1] = qq.y; q[2] = qq.z; q[3] = qq.w; }
                float o[12];
                attn_safe(o, q, mkdesc(sbase + SM_KV, 4096, 128, 0), mkdesc(sbase + SM_KV + 8192, 128, 4096, 0));
                attn_store(o, head, m64, w4, lane);
            }
        }
        nbar_sync(wg + 1, 128);
        if ((tid & 127) == 32) {
            asm volatile("fence.acq_rel.gpu;" ::: "memory");
            asm volatile("red.relaxed.gpu.global.add.u32 [%0], 1;" :: "l"(g_cnt + (C_O + quarter * 8 + 4 + wg) * 32) : "memory");
            if (badmask & 1) asm volatile("red.relaxed.gpu.global.add.u32 [%0], 1;" :: "l"(g_cnt + (C_O + quarter * 8 + wg) * 32) : "memory");
        }
        TL(6);
        {
            const int nb = idx & 7, jb = idx >> 3;
            const int mbe = (jb >> 2) * 8 + (jb & 3);
            float* supd = reinterpret_cast<float*>(smem + SM_MISC + 512);
            if (warp == 15) nbar_sync(7, 512); else nbar_arrive(7, 512);
            if (warp == 15) {
                flag_wait(C_O + mbe, 32);
                fence_proxy_async_all();
                if (lane == 0) {
                    for (int c = 0; c < 2; c++) {
                        mbar_expect_tx(bars + 8 * (B_OA + c), 32768);
                        tma3d(sbase + SM_KV + c * 32768, &maps.o, bars + 8 * (B_OA + c), mbe * 64, c * 4);
                    }
                }
                __syncwarp();
                flag_wait(C_O + mbe + 4, 32);
                fence_proxy_async_all();
                if (lane == 0) {
                    for (int c = 0; c < 2; c++) {
                        mbar_expect_tx(bars + 8 * (B_OA + 2 + c), 32768);
                        tma3d(sbase + SM_KV + 65536 + c * 32768, &maps.o, bars + 8 * (B_OA + 2 + c), (mbe + 4) * 64, c * 4);
                    }
                }
                __syncwarp();
            }
            const int late = wg >> 1, nh = wg & 1;
            const int mb = mbe + late * 4;
            const int g = lane >> 2, t = lane & 3;
            const int row0 = mb * 64 + w4 * 16 + g;
            const int col0 = nb * 64 + nh * 32 + t * 2;
            uint32_t xv[8], nv[8];
#pragma unroll
            for (int i = 0; i < 4; i++) {
                xv[2 * i] = *reinterpret_cast<const uint32_t*>(x + (size_t)row0 * DM + col0 + i * 8);
                xv[2 * i + 1] = *reinterpret_cast<const uint32_t*>(x + (size_t)(row0 + 8) * DM + col0 + i * 8);
                nv[2 * i] = __ldcg(reinterpret_cast<const uint32_t*>(g_xn + (size_t)row0 * DM + col0 + i * 8));
                nv[2 * i + 1] = __ldcg(reinterpret_cast<const uint32_t*>(g_xn + (size_t)(row0 + 8) * DM + col0 + i * 8));
            }
            if (wg == 0) {
                flag_wait(C_FFN, 64);
                const int which = tid >> 6, col = nb * 64 + (tid & 63);
                const float y = __ldcg(&g_ypart[which * 512 + col]) + __ldcg(&g_ypart[1024 + which * 512 + col]) +
                                __ldcg(&g_ypart[2048 + which * 512 + col]) + __ldcg(&g_ypart[3072 + which * 512 + col]);
                supd[tid] = bfr(bfr(y) * __ldcg(&g_gate[which]));
                if (tid < 2) reinterpret_cast<int*>(supd + 128)[tid] = __ldcg(&g_sel[tid]);
            }
            float acc[16];
#pragma unroll
            for (int i = 0; i < 16; i++) acc[i] = 0.f;
            mbar_wait(bars + 8 * B_WO, 0);
            const uint32_t abase = sbase + SM_KV + late * 65536;
#pragma unroll 1
            for (int c = 0; c < 8; c++) {
                if ((c & 3) == 0) mbar_wait(bars + 8 * (B_OA + late * 2 + (c >> 2)), 0);
                if (c == 0) TLX(7, 256);
                const uint64_t da = mkdesc(abase + c * 8192, 16, 1024, 1);
                const uint64_t db = mkdesc(sbase + c * 8192 + nh * 64, 8192, 1024, 1);
                WG_FENCE();
#pragma unroll
                for (int k = 0; k < 4; k++) wgmma_n32(acc, da + k * 2, db + k * 128, (c | k) != 0);
                WG_COMMIT();
            }
            __syncthreads();
            if (tid == 0) exit_ticket();
            const int sel0 = reinterpret_cast<const int*>(supd + 128)[0], sel1 = reinterpret_cast<const int*>(supd + 128)[1];
            WG_WAIT(0);
            TLX(8, 256);
#pragma unroll
            for (int h = 0; h < 2; h++) {
                const int row = row0 + h * 8;
                const int which = row == sel0 ? 0 : (row == sel1 ? 1 : -1);
#pragma unroll
                for (int i = 0; i < 4; i++) {
                    const int col = col0 + i * 8;
                    float b0 = bf_lo(nv[2 * i + h]), b1 = bf_hi(nv[2 * i + h]);
                    if (which >= 0) {
                        b0 = bfr(b0 + supd[which * 64 + col - nb * 64]); b1 = bfr(b1 + supd[which * 64 + col + 1 - nb * 64]);
                    }
                    const float t0 = bfr(bf_lo(xv[2 * i + h]) + bfr(acc[4 * i + 2 * h]));
                    const float t1 = bfr(bf_hi(xv[2 * i + h]) + bfr(acc[4 * i + 2 * h + 1]));
                    *reinterpret_cast<uint32_t*>(out + (size_t)row * DM + col) = packbf(t0 + b0, t1 + b1);
                }
            }
        }
        TLX(9, 256);
    }
}

typedef CUresult (*EncodeFn)(CUtensorMap*, CUtensorMapDataType, cuuint32_t, void*, const cuuint64_t*, const cuuint64_t*,
                             const cuuint32_t*, const cuuint32_t*, CUtensorMapInterleave, CUtensorMapSwizzle,
                             CUtensorMapL2promotion, CUtensorMapFloatOOBfill);

void make_map(EncodeFn fn, CUtensorMap* m, const void* ptr, uint64_t cols, uint64_t rows, uint32_t box_rows, uint32_t box_chunks) {
    cuuint64_t dims[3] = {64, rows, cols / 64};
    cuuint64_t strides[2] = {cols * 2, 128};
    cuuint32_t box[3] = {64, box_rows, box_chunks};
    cuuint32_t es[3] = {1, 1, 1};
    fn(m, CU_TENSOR_MAP_DATA_TYPE_BFLOAT16, 3, const_cast<void*>(ptr), dims, strides, box, es, CU_TENSOR_MAP_INTERLEAVE_NONE,
       CU_TENSOR_MAP_SWIZZLE_128B, CU_TENSOR_MAP_L2_PROMOTION_L2_256B, CU_TENSOR_MAP_FLOAT_OOB_FILL_NONE);
}

}

extern "C" void kernel_launch(void* const* d_in, const int* in_sizes, int n_in, void* d_out, int out_size) {
    const __nv_bfloat16* x = (const __nv_bfloat16*)d_in[0];
    const __nv_bfloat16* wqkv = (const __nv_bfloat16*)d_in[1];
    const __nv_bfloat16* wo = (const __nv_bfloat16*)d_in[2];
    const __nv_bfloat16* wr = (const __nv_bfloat16*)d_in[4];
    const __nv_bfloat16* wgate = (const __nv_bfloat16*)d_in[5];
    const __nv_bfloat16* wup = (const __nv_bfloat16*)d_in[6];
    const __nv_bfloat16* wdown = (const __nv_bfloat16*)d_in[7];
    __nv_bfloat16* out = (__nv_bfloat16*)d_out;

    static EncodeFn enc = nullptr;
    static void* p_xn = nullptr; static void* p_o = nullptr;
    if (!enc) {
        void* fn = nullptr; cudaDriverEntryPointQueryResult qr;
        cudaGetDriverEntryPoint("cuTensorMapEncodeTiled", &fn, cudaEnableDefault, &qr);
        enc = (EncodeFn)fn;
        cudaGetSymbolAddress(&p_xn, g_xn);
        cudaGetSymbolAddress(&p_o, g_o);
        cudaFuncSetAttribute(fused_kernel, cudaFuncAttributeMaxDynamicSharedMemorySize, FUSED_SMEM);
    }
    Maps maps;
    make_map(enc, &maps.g, wgate, FF, DM, 16, 7);
    make_map(enc, &maps.u, wup, FF, DM, 16, 7);
    make_map(enc, &maps.d, wdown, DM, FF, 32, 8);
    make_map(enc, &maps.xn, p_xn, DM, S_LEN, 128, 1);
    make_map(enc, &maps.wqkv, wqkv, 3 * DM, DM, 64, 3);
    make_map(enc, &maps.o, p_o, DM, S_LEN, 64, 4);
    make_map(enc, &maps.wo, wo, DM, DM, 256, 1);

    union { uint32_t u; float f; } scu; scu.u = 128u;

    cudaLaunchConfig_t cfg = {};
    cfg.gridDim = dim3(132); cfg.blockDim = dim3(512); cfg.dynamicSmemBytes = FUSED_SMEM; cfg.stream = cudaStreamPerThread;
    cudaLaunchKernelEx(&cfg, fused_kernel, maps, x, wr, out, scu.f);
}
```

```cpp
#include <cuda_runtime.h>
#include <cuda_bf16.h>
#include <cuda.h>
#include <stdint.h>
#include <type_traits>

namespace {

constexpr int S_LEN = 2048;
constexpr int DM = 512;
constexpr int NH = 32;
constexpr int FF = 1792;

__device__ __align__(1024) __nv_bfloat16 g_xn[S_LEN * DM];
__device__ __align__(16) float g_r[S_LEN];
__device__ __align__(1024) uint4 g_q[NH * 128 * 32];
__device__ __align__(1024) uint4 g_kv[NH * 8192];
__device__ __align__(1024) __nv_bfloat16 g_o[S_LEN * DM];
__device__ __align__(16) float g_ypart[4 * 2 * DM];
__device__ int g_sel[2];
__device__ float g_gate[2];
constexpr int C_LN = 0, C_QKV = 16, C_O = 24, C_FFN = 56, C_EXIT = 57, C_NUM = 58;
__device__ unsigned g_cnt[C_NUM * 32];

#define TL(slot) do {} while (0)
#define TLX(slot, th) do {} while (0)

__device__ __forceinline__ uint32_t smem_u32(const void* p) { return (uint32_t)__cvta_generic_to_shared(p); }
__device__ __forceinline__ void warp_arrive(int idx) {
    __syncwarp();
    if ((threadIdx.x & 31) == 0)
        asm volatile("red.release.gpu.global.add.u32 [%0], 1;" :: "l"(g_cnt + idx * 32) : "memory");
}
__device__ __forceinline__ void flag_release(int idx) {
    asm volatile("red.release.gpu.global.add.u32 [%0], 1;" :: "l"(g_cnt + idx * 32) : "memory");
}
__device__ __forceinline__ void exit_ticket() {
    unsigned tk;
    asm volatile("atom.relaxed.gpu.global.add.u32 %0, [%1], 1;" : "=r"(tk) : "l"(g_cnt + C_EXIT * 32) : "memory");
    if (tk == gridDim.x - 1) {
#pragma unroll 1
        for (int i = 0; i < C_NUM; i++) g_cnt[i * 32] = 0u;
    }
}
__device__ __forceinline__ void nbar_arrive(int id, int cnt) { asm volatile("bar.arrive %0, %1;" :: "r"(id), "r"(cnt) : "memory"); }
__device__ __forceinline__ void nbar_sync(int id, int cnt) { asm volatile("bar.sync %0, %1;" :: "r"(id), "r"(cnt) : "memory"); }
__device__ __forceinline__ void flag_wait(int idx, unsigned target) {
    asm volatile("{\n.reg .pred p;\n.reg .u32 n, v;\nmov.u32 n, 0;\n"
                 "FW_%=:\n"
                 "ld.acquire.gpu.global.u32 v, [%0];\n"
                 "setp.ge.u32 p, v, %1;\n"
                 "@p bra FD_%=;\n"
                 "add.u32 n, n, 1;\n"
                 "setp.lt.u32 p, n, 16000000;\n"
                 "@p bra FW_%=;\n"
                 "trap;\n"
                 "FD_%=:\n}"
                 :: "l"(g_cnt + idx * 32), "r"(target) : "memory");
}
__device__ __forceinline__ void flag_wait_all(int idx, unsigned target) {
    asm volatile("{\n.reg .pred p;\n.reg .u32 n, v;\nmov.u32 n, 0;\n"
                 "FW_%=:\n"
                 "ld.acquire.gpu.global.u32 v, [%0];\n"
                 "setp.ge.u32 p, v, %1;\n"
                 "vote.sync.all.pred p, p, 0xffffffff;\n"
                 "@p bra.uni FD_%=;\n"
                 "add.u32 n, n, 1;\n"
                 "setp.lt.u32 p, n, 16000000;\n"
                 "@p bra.uni FW_%=;\n"
                 "trap;\n"
                 "FD_%=:\n}"
                 :: "l"(g_cnt + idx * 32), "r"(target) : "memory");
}
__device__ __forceinline__ void fence_proxy_async_all() { asm volatile("fence.proxy.async.global;" ::: "memory"); }
__device__ __forceinline__ void mbar_init(uint32_t bar, uint32_t cnt) {
    asm volatile("mbarrier.init.shared::cta.b64 [%0], %1;" :: "r"(bar), "r"(cnt) : "memory");
}
__device__ __forceinline__ void mbar_expect_tx(uint32_t bar, uint32_t bytes) {
    asm volatile("mbarrier.arrive.expect_tx.shared::cta.b64 _, [%0], %1;" :: "r"(bar), "r"(bytes) : "memory");
}
__device__ __forceinline__ void mbar_arrive(uint32_t bar) {
    asm volatile("mbarrier.arrive.shared::cta.b64 _, [%0];" :: "r"(bar) : "memory");
}
__device__ __forceinline__ void mbar_wait(uint32_t bar, uint32_t parity) {
    asm volatile("{\n.reg .pred p;\n.reg .u32 n;\nmov.u32 n, 0;\n"
                 "WAIT_%=:\n"
                 "mbarrier.try_wait.parity.shared::cta.b64 p, [%0], %1;\n"
                 "@p bra DONE_%=;\n"
                 "add.u32 n, n, 1;\n"
                 "setp.lt.u32 p, n, 4000000;\n"
                 "@p bra WAIT_%=;\n"
                 "trap;\n"
                 "DONE_%=:\n}"
                 :: "r"(bar), "r"(parity) : "memory");
}
__device__ __forceinline__ void fence_barrier_init() { asm volatile("fence.mbarrier_init.release.cluster;" ::: "memory"); }
__device__ __forceinline__ void fence_proxy_async() { asm volatile("fence.proxy.async.shared::cta;" ::: "memory"); }
__device__ __forceinline__ void tma3d(uint32_t dst, const CUtensorMap* map, uint32_t bar, int row, int chunk) {
    asm volatile("cp.async.bulk.tensor.3d.shared::cluster.global.mbarrier::complete_tx::bytes [%0], [%1, {%3, %4, %5}], [%2];"
                 :: "r"(dst), "l"((uint64_t)map), "r"(bar), "r"(0), "r"(row), "r"(chunk) : "memory");
}
__device__ __forceinline__ void bulk_g2s(uint32_t dst, const void* src, uint32_t bytes, uint32_t bar) {
    asm volatile("cp.async.bulk.shared::cluster.global.mbarrier::complete_tx::bytes [%0], [%1], %2, [%3];"
                 :: "r"(dst), "l"((uint64_t)src), "r"(bytes), "r"(bar) : "memory");
}
__device__ __forceinline__ void l2_prefetch(const void* src, uint32_t bytes) {
    asm volatile("cp.async.bulk.prefetch.L2.global [%0], %1;" :: "l"((uint64_t)src), "r"(bytes) : "memory");
}
__device__ __forceinline__ void map_prefetch(const CUtensorMap* m) {
    asm volatile("prefetch.tensormap [%0];" :: "l"((uint64_t)m) : "memory");
}
__device__ __forceinline__ uint64_t mkdesc(uint32_t addr, uint32_t lbo, uint32_t sbo, uint32_t swz) {
    return (uint64_t)((addr & 0x3FFFF) >> 4) | ((uint64_t)(lbo >> 4) << 16) | ((uint64_t)(sbo >> 4) << 32) | ((uint64_t)swz << 62);
}
#define WG_FENCE() asm volatile("wgmma.fence.sync.aligned;" ::: "memory")
#define WG_COMMIT() asm volatile("wgmma.commit_group.sync.aligned;" ::: "memory")
#define WG_WAIT(n) asm volatile("wgmma.wait_group.sync.aligned %0;" :: "n"(n) : "memory")

__device__ __forceinline__ float ex2(float x) { float y; asm("ex2.approx.ftz.f32 %0, %1;" : "=f"(y) : "f"(x)); return y; }
__device__ __forceinline__ uint32_t packbf(float lo, float hi) {
    uint32_t r; asm("cvt.rn.bf16x2.f32 %0, %1, %2;" : "=r"(r) : "f"(hi), "f"(lo)); return r;
}
__device__ __forceinline__ float bf_lo(uint32_t v) { return __uint_as_float(v << 16); }
__device__ __forceinline__ float bf_hi(uint32_t v) { return __uint_as_float(v & 0xffff0000u); }
__device__ __forceinline__ float bfr(float x) { return __bfloat162float(__float2bfloat16_rn(x)); }

__device__ __forceinline__ void wgmma_n192(float (&d)[96], uint64_t da, uint64_t db, int scale_d) {
    asm volatile("{\n.reg .pred p;\nsetp.ne.b32 p, %98, 0;\n"
        "wgmma.mma_async.sync.aligned.m64n192k16.f32.bf16.bf16 "
        "{%0,%1,%2,%3,%4,%5,%6,%7,%8,%9,%10,%11,%12,%13,%14,%15,%16,%17,%18,%19,%20,%21,%22,%23,"
        "%24,%25,%26,%27,%28,%29,%30,%31,%32,%33,%34,%35,%36,%37,%38,%39,%40,%41,%42,%43,%44,%45,%46,%47,"
        "%48,%49,%50,%51,%52,%53,%54,%55,%56,%57,%58,%59,%60,%61,%62,%63,%64,%65,%66,%67,%68,%69,%70,%71,"
        "%72,%73,%74,%75,%76,%77,%78,%79,%80,%81,%82,%83,%84,%85,%86,%87,%88,%89,%90,%91,%92,%93,%94,%95}, "
        "%96, %97, p, 1, 1, 0, 1;\n}"
        : "+f"(d[0]), "+f"(d[1]), "+f"(d[2]), "+f"(d[3]), "+f"(d[4]), "+f"(d[5]), "+f"(d[6]), "+f"(d[7]),
          "+f"(d[8]), "+f"(d[9]), "+f"(d[10]), "+f"(d[11]), "+f"(d[12]), "+f"(d[13]), "+f"(d[14]), "+f"(d[15]),
          "+f"(d[16]), "+f"(d[17]), "+f"(d[18]), "+f"(d[19]), "+f"(d[20]), "+f"(d[21]), "+f"(d[22]), "+f"(d[23]),
          "+f"(d[24]), "+f"(d[25]), "+f"(d[26]), "+f"(d[27]), "+f"(d[28]), "+f"(d[29]), "+f"(d[30]), "+f"(d[31]),
          "+f"(d[32]), "+f"(d[33]), "+f"(d[34]), "+f"(d[35]), "+f"(d[36]), "+f"(d[37]), "+f"(d[38]), "+f"(d[39]),
          "+f"(d[40]), "+f"(d[41]), "+f"(d[42]), "+f"(d[43]), "+f"(d[44]), "+f"(d[45]), "+f"(d[46]), "+f"(d[47]),
          "+f"(d[48]), "+f"(d[49]), "+f"(d[50]), "+f"(d[51]), "+f"(d[52]), "+f"(d[53]), "+f"(d[54]), "+f"(d[55]),
          "+f"(d[56]), "+f"(d[57]), "+f"(d[58]), "+f"(d[59]), "+f"(d[60]), "+f"(d[61]), "+f"(d[62]), "+f"(d[63]),
          "+f"(d[64]), "+f"(d[65]), "+f"(d[66]), "+f"(d[67]), "+f"(d[68]), "+f"(d[69]), "+f"(d[70]), "+f"(d[71]),
          "+f"(d[72]), "+f"(d[73]), "+f"(d[74]), "+f"(d[75]), "+f"(d[76]), "+f"(d[77]), "+f"(d[78]), "+f"(d[79]),
          "+f"(d[80]), "+f"(d[81]), "+f"(d[82]), "+f"(d[83]), "+f"(d[84]), "+f"(d[85]), "+f"(d[86]), "+f"(d[87]),
          "+f"(d[88]), "+f"(d[89]), "+f"(d[90]), "+f"(d[91]), "+f"(d[92]), "+f"(d[93]), "+f"(d[94]), "+f"(d[95])
        : "l"(da), "l"(db), "r"(scale_d));
}

constexpr float SHIFT = 90.0f;
constexpr float QS = 0.25f * 1.4426950408889634f * 18446744073709551616.0f;
constexpr float scq = 0.25f * 1.4426950408889634f * 3.3087224502121107e-24f;

__device__ __forceinline__ uint32_t polyexp(float lo, float hi) {
    uint32_t w, g, q, h;
    asm("cvt.pack.sat.s16.s32 %0, %1, %2;" : "=r"(w) : "r"(__float_as_uint(hi)), "r"(__float_as_uint(lo)));
    g = w & 0x007F007Fu;
    asm("fma.rn.f16x2 %0, %1, %2, %3;" : "=r"(q) : "r"(g), "r"(0xf940f940u), "r"(0x35513551u));
    asm("mul.rn.f16x2 %0, %1, %2;" : "=r"(h) : "r"(q), "r"(g));
    return w - h;
}
__device__ __forceinline__ void qk64(float (&s)[32], const uint32_t (&q)[4], uint64_t db) {
    asm volatile("wgmma.mma_async.sync.aligned.m64n64k16.f32.bf16.bf16 "
        "{%0,%1,%2,%3,%4,%5,%6,%7,%8,%9,%10,%11,%12,%13,%14,%15,%16,%17,%18,%19,%20,%21,%22,%23,%24,%25,%26,%27,%28,%29,%30,%31}, "
        "{%32,%33,%34,%35}, %36, 0, 1, 1, 0;"
        : "=f"(s[0]), "=f"(s[1]), "=f"(s[2]), "=f"(s[3]), "=f"(s[4]), "=f"(s[5]), "=f"(s[6]), "=f"(s[7]),
          "=f"(s[8]), "=f"(s[9]), "=f"(s[10]), "=f"(s[11]), "=f"(s[12]), "=f"(s[13]), "=f"(s[14]), "=f"(s[15]),
          "=f"(s[16]), "=f"(s[17]), "=f"(s[18]), "=f"(s[19]), "=f"(s[20]), "=f"(s[21]), "=f"(s[22]), "=f"(s[23]),
          "=f"(s[24]), "=f"(s[25]), "=f"(s[26]), "=f"(s[27]), "=f"(s[28]), "=f"(s[29]), "=f"(s[30]), "=f"(s[31])
        : "r"(q[0]), "r"(q[1]), "r"(q[2]), "r"(q[3]), "l"(db));
}
__device__ __forceinline__ void pv24(float (&o)[12], uint32_t a0, uint32_t a1, uint32_t a2, uint32_t a3, uint64_t db) {
    asm volatile("wgmma.mma_async.sync.aligned.m64n24k16.f32.bf16.bf16 "
        "{%0,%1,%2,%3,%4,%5,%6,%7,%8,%9,%10,%11}, {%12,%13,%14,%15}, %16, 1, 1, 1, 1;"
        : "+f"(o[0]), "+f"(o[1]), "+f"(o[2]), "+f"(o[3]), "+f"(o[4]), "+f"(o[5]), "+f"(o[6]), "+f"(o[7]),
          "+f"(o[8]), "+f"(o[9]), "+f"(o[10]), "+f"(o[11])
        : "r"(a0), "r"(a1), "r"(a2), "r"(a3), "l"(db));
}

__device__ __forceinline__ void attn_safe(float (&o)[12], const uint32_t (&q)[4], uint64_t kdesc0, uint64_t vdesc0) {
    float s[32];
    float m0 = -INFINITY, m1 = -INFINITY;
#pragma unroll
    for (int i = 0; i < 12; i++) o[i] = 0.f;
#pragma unroll 1
    for (int j = 0; j < 32; j++) {
        WG_FENCE();
        qk64(s, q, kdesc0 + (uint64_t)((j >> 2) * (20480 / 16) + (j & 3) * 64));
        WG_COMMIT(); WG_WAIT(0);
        float n0 = m0, n1 = m1;
#pragma unroll
        for (int i = 0; i < 8; i++) { n0 = fmaxf(n0, fmaxf(s[4 * i], s[4 * i + 1])); n1 = fmaxf(n1, fmaxf(s[4 * i + 2], s[4 * i + 3])); }
        n0 = fmaxf(n0, __shfl_xor_sync(~0u, n0, 1)); n0 = fmaxf(n0, __shfl_xor_sync(~0u, n0, 2));
        n1 = fmaxf(n1, __shfl_xor_sync(~0u, n1, 1)); n1 = fmaxf(n1, __shfl_xor_sync(~0u, n1, 2));
        const float c0 = ex2((m0 - n0) * QS), c1 = ex2((m1 - n1) * QS);
        m0 = n0; m1 = n1;
#pragma unroll
        for (int i = 0; i < 3; i++) { o[4 * i] *= c0; o[4 * i + 1] *= c0; o[4 * i + 2] *= c1; o[4 * i + 3] *= c1; }
        uint32_t p[16];
#pragma unroll
        for (int i = 0; i < 8; i++) {
            p[2 * i] = packbf(ex2((s[4 * i] - m0) * QS), ex2((s[4 * i + 1] - m0) * QS));
            p[2 * i + 1] = packbf(ex2((s[4 * i + 2] - m1) * QS), ex2((s[4 * i + 3] - m1) * QS));
        }
        WG_FENCE();
#pragma unroll
        for (int kk = 0; kk < 4; kk++) pv24(o, p[4 * kk], p[4 * kk + 1], p[4 * kk + 2], p[4 * kk + 3], vdesc0 + (uint64_t)((j >> 2) * (20480 / 16) + (j & 3) * 64 + kk * 16));
        WG_COMMIT(); WG_WAIT(0);
    }
}

__device__ __forceinline__ void attn_store(const float (&o)[12], int head, int m64, int warp, int lane) {
    const int g = lane >> 2, t = lane & 3;
    const int row = m64 * 64 + warp * 16 + g;
    const float i0 = 1.f / o[8], i1 = 1.f / o[10];
    uint32_t* p0 = reinterpret_cast<uint32_t*>(g_o + (size_t)row * DM + head * 16 + t * 2);
    uint32_t* p1 = reinterpret_cast<uint32_t*>(g_o + (size_t)(row + 8) * DM + head * 16 + t * 2);
    p0[0] = packbf(o[0] * i0, o[1] * i0); p0[4] = packbf(o[4] * i0, o[5] * i0);
    p1[0] = packbf(o[2] * i1, o[3] * i1); p1[4] = packbf(o[6] * i1, o[7] * i1);
}

constexpr int FS_N = 4;
constexpr int FS_BYTES = 32768;
__device__ __forceinline__ void ldsm4t(uint32_t& r0, uint32_t& r1, uint32_t& r2, uint32_t& r3, uint32_t addr) {
    asm volatile("ldmatrix.sync.aligned.m8n8.x4.trans.shared.b16 {%0,%1,%2,%3}, [%4];" : "=r"(r0), "=r"(r1), "=r"(r2), "=r"(r3) : "r"(addr) : "memory");
}
__device__ __forceinline__ void mma16816(float (&d)[4], uint32_t a0, uint32_t a2, uint32_t b0, uint32_t b1) {
    asm volatile("mma.sync.aligned.m16n8k16.row.col.f32.bf16.bf16.f32 {%0,%1,%2,%3}, {%4,%5,%6,%5}, {%7,%8}, {%0,%1,%2,%3};"
                 : "+f"(d[0]), "+f"(d[1]), "+f"(d[2]), "+f"(d[3]) : "r"(a0), "r"(0u), "r"(a2), "r"(b0), "r"(b1));
}
__device__ void ffn_block(int c, uint8_t* smem, uint32_t sbase, const CUtensorMap* mapG, const CUtensorMap* mapU, const CUtensorMap* mapD) {
    const int tid = threadIdx.x, warp = tid >> 5, lane = tid & 31;
    uint32_t* sx = reinterpret_cast<uint32_t*>(smem + FS_N * FS_BYTES);
    __nv_bfloat16* sh = reinterpret_cast<__nv_bfloat16*>(sx + 512);
    const uint32_t bars = sbase + FS_N * FS_BYTES + 8192;
    float* tv = reinterpret_cast<float*>(smem + FS_N * FS_BYTES + 4096);
    int* ti = reinterpret_cast<int*>(tv + 32);
    int* ssel = ti + 32;
    auto issue = [&](int item) {
        const int slot = item % FS_N;
        const uint32_t dst = sbase + slot * FS_BYTES, bar = bars + 8 * slot;
        mbar_expect_tx(bar, item < 32 ? 28672 : 32768);
        if (item < 32) {
            tma3d(dst, mapG, bar, item * 16, c * 7);
            tma3d(dst + 14336, mapU, bar, item * 16, c * 7);
        } else {
            tma3d(dst, mapD, bar, c * 448 + (item - 32) * 32, 0);
        }
    };
    if (tid == 0) {
        for (int i = 0; i < FS_N; i++) mbar_init(bars + 8 * i, 1);
        fence_barrier_init();
        for (int i = 0; i < FS_N; i++) issue(i);
    }
    flag_wait(C_LN + warp, 8);
    __syncthreads();
    float b1 = -INFINITY, b2 = -INFINITY; int i1 = 0x7fffffff, i2 = 0x7fffffff;
    auto push = [&](float v, int i) {
        if (v > b1 || (v == b1 && i < i1)) { b2 = b1; i2 = i1; b1 = v; i1 = i; }
        else if (v > b2 || (v == b2 && i < i2)) { b2 = v; i2 = i; }
    };
    {
        const float4 rv = __ldcg(reinterpret_cast<const float4*>(g_r) + tid);
        push(rv.x, 4 * tid); push(rv.y, 4 * tid + 1); push(rv.z, 4 * tid + 2); push(rv.w, 4 * tid + 3);
    }
#pragma unroll
    for (int o = 16; o > 0; o >>= 1) {
        float v1 = __shfl_xor_sync(~0u, b1, o), v2 = __shfl_xor_sync(~0u, b2, o);
        int j1 = __shfl_xor_sync(~0u, i1, o), j2 = __shfl_xor_sync(~0u, i2, o);
        push(v1, j1); push(v2, j2);
    }
    if (lane == 0) { tv[2 * warp] = b1; ti[2 * warp] = i1; tv[2 * warp + 1] = b2; ti[2 * warp + 1] = i2; }
    __syncthreads();
    if (warp == 1) {
        b1 = tv[lane]; i1 = ti[lane]; b2 = -INFINITY; i2 = 0x7fffffff;
#pragma unroll
        for (int o = 16; o > 0; o >>= 1) {
            float v1 = __shfl_xor_sync(~0u, b1, o), v2 = __shfl_xor_sync(~0u, b2, o);
            int j1 = __shfl_xor_sync(~0u, i1, o), j2 = __shfl_xor_sync(~0u, i2, o);
            push(v1, j1); push(v2, j2);
        }
        if (lane == 0) {
            i1 = min(max(i1, 0), S_LEN - 1); i2 = min(max(i2, 0), S_LEN - 1);
            ssel[0] = i1; ssel[1] = i2;
            if (c == 0) {
                g_sel[0] = i1; g_sel[1] = i2;
                g_gate[0] = bfr(1.f / (1.f + __expf(-bfr(b1))));
                g_gate[1] = bfr(1.f / (1.f + __expf(-bfr(b2))));
            }
        }
    }
    __syncthreads();
    sx[tid] = __ldcg(reinterpret_cast<const uint32_t*>(g_xn + (size_t)ssel[tid >> 8] * DM + (tid & 255) * 2));
    __syncthreads();
    TL(1);
    const int g = lane >> 2, t = lane & 3;
    const int lrow = lane & 15, lsel = lane >> 4;
    {
        float ag[4][4], au[4][4];
#pragma unroll
        for (int j = 0; j < 4; j++) { ag[j][0] = ag[j][1] = ag[j][2] = ag[j][3] = 0.f; au[j][0] = au[j][1] = au[j][2] = au[j][3] = 0.f; }
#pragma unroll 1
        for (int it = 0; it < 32; it++) {
            const int slot = it % FS_N;
            const uint32_t a0 = g < 2 ? sx[g * 256 + it * 8 + t] : 0u, a2 = g < 2 ? sx[g * 256 + it * 8 + 4 + t] : 0u;
            mbar_wait(bars + 8 * slot, (it / FS_N) & 1);
            const uint32_t base = sbase + slot * FS_BYTES + lsel * 14336 + lrow * 128;
#pragma unroll
            for (int j = 0; j < 4; j++) {
                const int nt = warp + j * 16;
                if (nt < 56) {
                    uint32_t b0, b1, b2, b3;
                    ldsm4t(b0, b1, b2, b3, base + (nt >> 3) * 2048 + (((nt & 7) ^ (lrow & 7)) << 4));
                    mma16816(ag[j], a0, a2, b0, b1);
                    mma16816(au[j], a0, a2, b2, b3);
                }
            }
            __syncthreads();
            if (tid == 480) issue(it + FS_N);
        }
        if (g < 2) {
#pragma unroll
            for (int j = 0; j < 4; j++) {
                const int nt = warp + j * 16;
                if (nt < 56) {
#pragma unroll
                    for (int e = 0; e < 2; e++) {
                        const float gs = bfr(ag[j][e]), us = bfr(au[j][e]);
                        const float sg = bfr(gs / (1.f + __expf(-gs)));
                        sh[g * 448 + nt * 8 + t * 2 + e] = __float2bfloat16_rn(sg * us);
                    }
                }
            }
        }
        __syncthreads();
    }
    TL(2);
    {
        const uint32_t* shw = reinterpret_cast<const uint32_t*>(sh);
        float a[4][4];
#pragma unroll
        for (int j = 0; j < 4; j++) a[j][0] = a[j][1] = a[j][2] = a[j][3] = 0.f;
#pragma unroll 1
        for (int it = 32; it < 46; it++) {
            const int slot = it % FS_N;
            uint32_t af[4];
#pragma unroll
            for (int q = 0; q < 4; q++) af[q] = g < 2 ? shw[g * 224 + (it - 32) * 16 + q * 4 + t] : 0u;
            mbar_wait(bars + 8 * slot, (it / FS_N) & 1);
            const uint32_t base = sbase + slot * FS_BYTES + (warp >> 1) * 4096 + lane * 128;
#pragma unroll
            for (int j = 0; j < 4; j++) {
                const int u = (warp & 1) * 4 + j;
                uint32_t b0, b1, b2, b3;
                ldsm4t(b0, b1, b2, b3, base + ((u ^ (lane & 7)) << 4));
                mma16816(a[j], af[0], af[1], b0, b1);
                mma16816(a[j], af[2], af[3], b2, b3);
            }
            __syncthreads();
            if (tid == 480 && it + FS_N < 46) issue(it + FS_N);
        }
        if (g < 2) {
#pragma unroll
            for (int j = 0; j < 4; j++)
                *reinterpret_cast<float2*>(&g_ypart[c * 1024 + g * 512 + (warp * 4 + j) * 8 + t * 2]) = make_float2(a[j][0], a[j][1]);
        }
    }
    warp_arrive(C_FFN);
}

__device__ __forceinline__ void wgmma_n32(float (&d)[16], uint64_t da, uint64_t db, int scale_d) {
    asm volatile("{\n.reg .pred p;\nsetp.ne.b32 p, %18, 0;\n"
        "wgmma.mma_async.sync.aligned.m64n32k16.f32.bf16.bf16 "
        "{%0,%1,%2,%3,%4,%5,%6,%7,%8,%9,%10,%11,%12,%13,%14,%15}, "
        "%16, %17, p, 1, 1, 0, 1;\n}"
        : "+f"(d[0]), "+f"(d[1]), "+f"(d[2]), "+f"(d[3]), "+f"(d[4]), "+f"(d[5]), "+f"(d[6]), "+f"(d[7]),
          "+f"(d[8]), "+f"(d[9]), "+f"(d[10]), "+f"(d[11]), "+f"(d[12]), "+f"(d[13]), "+f"(d[14]), "+f"(d[15])
        : "l"(da), "l"(db), "r"(scale_d));
}

constexpr int G_ST = 4;
constexpr int G_STAGE = 16384 + 24576;
constexpr int SM_KV = 65536, KV_CH = 20480, SM_MISC = 229376;
constexpr int FUSED_SMEM = SM_MISC + 2048;
constexpr int B_FULL = 0, B_EMPTY = 4, B_KV = 8, B_WO = 16, B_OA = 18, B_NUM = 22;

struct Maps { CUtensorMap xn, wqkv, o, wo, g, u, d; };

__global__ void __launch_bounds__(512, 1) fused_kernel(const __grid_constant__ Maps maps, const __nv_bfloat16* __restrict__ x,
                                                       const __nv_bfloat16* __restrict__ wr, __nv_bfloat16* __restrict__ out, float sc) {
    extern __shared__ __align__(1024) uint8_t smem[];
    const uint32_t sbase = smem_u32(smem);
    const int tid = threadIdx.x, warp = __shfl_sync(~0u, tid >> 5, 0), lane = tid & 31;
    const uint32_t bars = sbase + SM_MISC;
    TL(0);
    if (sbase & 1023u) __trap();
    if (blockIdx.x < 4) {
        ffn_block(blockIdx.x, smem, sbase, &maps.g, &maps.u, &maps.d);
        __syncthreads();
        if (tid == 0) exit_ticket();
        TL(3);
    } else {
        const int idx = blockIdx.x - 4;
        const int wg = warp >> 2;
        {
            const int row = idx * 16 + warp;
            const uint4* xr = reinterpret_cast<const uint4*>(x + (size_t)row * DM);
            const uint4 a = xr[lane], b = xr[32 + lane];
            const uint4* wp = reinterpret_cast<const uint4*>(wr);
            const uint4 wa = wp[lane], wb = wp[32 + lane];
            if (tid == 480) {
                for (int s = 0; s < G_ST; s++) { mbar_init(bars + 8 * (B_FULL + s), 2); mbar_init(bars + 8 * (B_EMPTY + s), 2); }
                for (int c = B_KV; c < B_NUM; c++) mbar_init(bars + 8 * c, 1);
                fence_barrier_init();
                for (int c = 0; c < G_ST; c++) {
                    mbar_expect_tx(bars + 8 * (B_FULL + c), 24576);
                    tma3d(sbase + c * G_STAGE + 16384, &maps.wqkv, bars + 8 * (B_FULL + c), c * 64, (idx & 7) * 3);
                }
                map_prefetch(&maps.xn);
            }
            __syncwarp();
            const uint32_t u[8] = {a.x, a.y, a.z, a.w, b.x, b.y, b.z, b.w};
            const uint32_t w[8] = {wa.x, wa.y, wa.z, wa.w, wb.x, wb.y, wb.z, wb.w};
            float f[16];
            float sum = 0.f;
#pragma unroll
            for (int i = 0; i < 8; i++) { f[2 * i] = bf_lo(u[i]); f[2 * i + 1] = bf_hi(u[i]); sum += f[2 * i] + f[2 * i + 1]; }
#pragma unroll
            for (int o = 16; o > 0; o >>= 1) sum += __shfl_xor_sync(~0u, sum, o);
            const float mean = sum * (1.f / DM);
            float sq = 0.f;
#pragma unroll
            for (int i = 0; i < 16; i++) { const float d = f[i] - mean; sq = fmaf(d, d, sq); }
#pragma unroll
            for (int o = 16; o > 0; o >>= 1) sq += __shfl_xor_sync(~0u, sq, o);
            const float mb_ = bfr(mean);
            const float vb = bfr(sq * (1.f / DM));
            const float rinv = 1.f / bfr(sqrtf(bfr(vb + 1e-5f)));
            uint32_t o[8];
            float r = 0.f;
#pragma unroll
            for (int i = 0; i < 8; i++) {
                const float d0 = bfr(f[2 * i] - mb_), d1 = bfr(f[2 * i + 1] - mb_);
                o[i] = packbf(d0 * rinv, d1 * rinv);
                r = fmaf(bf_lo(o[i]), bf_lo(w[i]), r);
                r = fmaf(bf_hi(o[i]), bf_hi(w[i]), r);
            }
            uint4* xo = reinterpret_cast<uint4*>(g_xn + (size_t)row * DM);
            xo[lane] = make_uint4(o[0], o[1], o[2], o[3]);
            xo[32 + lane] = make_uint4(o[4], o[5], o[6], o[7]);
#pragma unroll
            for (int of = 16; of > 0; of >>= 1) r += __shfl_xor_sync(~0u, r, of);
            if (lane == 0) g_r[row] = r;
        }
        __syncthreads();
        if (tid == 416) flag_release(C_LN + (idx >> 3));
        TL(1);
        {
            const int nb = idx & 7, mb = idx >> 3;
            if (warp == 15) {
                for (int c = G_ST; c < 8; c++) {
                    const int s = c - G_ST;
                    mbar_wait(bars + 8 * (B_EMPTY + s), 0);
                    if (lane == 0) {
                        mbar_expect_tx(bars + 8 * (B_FULL + s), 24576);
                        tma3d(sbase + s * G_STAGE + 16384, &maps.wqkv, bars + 8 * (B_FULL + s), c * 64, nb * 3);
                    }
                    __syncwarp();
                }
            } else if (warp == 14) {
                flag_wait(C_LN + mb, 8);
                fence_proxy_async_all();
                for (int c = 0; c < 8; c++) {
                    const int s = c & (G_ST - 1);
                    if (c >= G_ST) mbar_wait(bars + 8 * (B_EMPTY + s), 0);
                    if (lane == 0) {
                        mbar_expect_tx(bars + 8 * (B_FULL + s), 16384);
                        tma3d(sbase + s * G_STAGE, &maps.xn, bars + 8 * (B_FULL + s), mb * 128, c);
                    }
                    __syncwarp();
                }
            } else if (wg < 2) {
                float acc[96];
#pragma unroll
                for (int i = 0; i < 96; i++) acc[i] = 0.f;
#pragma unroll 1
                for (int c = 0; c < 8; c++) {
                    const int s = c & (G_ST - 1);
                    const uint32_t st = sbase + s * G_STAGE;
                    mbar_wait(bars + 8 * (B_FULL + s), c >> 2);
                    if (c == 0) TL(2);
                    const uint64_t da = mkdesc(st + wg * 8192, 16, 1024, 1);
                    const uint64_t db = mkdesc(st + 16384, 8192, 1024, 1);
                    WG_FENCE();
#pragma unroll
                    for (int k = 0; k < 4; k++) wgmma_n192(acc, da + k * 2, db + k * 128, (c | k) != 0);
                    WG_COMMIT();
                    if (c <= G_ST) {
                        WG_WAIT(1);
                        if (c >= 1 && (tid & 127) == 0) mbar_arrive(bars + 8 * (B_EMPTY + c - 1));
                    }
                }
                WG_WAIT(0);
                nbar_arrive(6, 512);
                TL(3);
                const int g = lane >> 2, t = lane & 3;
                const int mt = mb * 8 + warp;
#pragma unroll
                for (int hh = 0; hh < 12; hh++) {
                    const int gh = nb * 12 + hh;
                    const float* a = &acc[hh * 8];
                    if (gh < 32) {
                        g_q[(gh * 128 + mt) * 32 + lane] = make_uint4(packbf(a[0], a[1]), packbf(a[2], a[3]), packbf(a[4], a[5]), packbf(a[6], a[7]));
                    } else {
                        const int isv = gh >= 64;
                        uint32_t* dst = reinterpret_cast<uint32_t*>(g_kv + ((gh & 31) * 8 + (mt >> 4)) * 1024 + isv * 512) + ((mt & 15) * 16 + g) * 4 + t;
                        const float ks = isv ? 1.0f : 5.421010862427522e-20f;
                        dst[0] = packbf(a[0] * ks, a[1] * ks);
                        dst[32] = packbf(a[2] * ks, a[3] * ks);
                        dst[1024] = packbf(a[4] * ks, a[5] * ks);
                        dst[1024 + 32] = packbf(a[6] * ks, a[7] * ks);
                    }
                }
                TL(10);
                nbar_sync(8, 256);
                if (tid == 0) flag_release(C_QKV + nb);
            }
        }
        TL(4);
        uint32_t badmask = 0;
        const int head = idx >> 2, quarter = idx & 3, w4 = warp & 3;
        {
            if (warp == 15) {
                flag_wait_all(C_QKV + ((lane % 3) * 32 + head) / 12, 16);
                nbar_sync(6, 512);
                fence_proxy_async_all();
                if (lane == 0) {
                    const uint8_t* kvp = reinterpret_cast<const uint8_t*>(g_kv + head * 8192);
#pragma unroll 1
                    for (int c = 0; c < 2; c++) {
                        mbar_expect_tx(bars + 8 * (B_KV + c), 16384);
                        bulk_g2s(sbase + SM_KV + c * KV_CH, kvp + c * 16384, 16384, bars + 8 * (B_KV + c));
                    }
                }
                __syncwarp();
            } else if (wg >= 2) {
                nbar_sync(6, 512);
#pragma unroll 1
                for (int i = tid - 256; i < 2048; i += 224)
                    *reinterpret_cast<uint4*>(smem + SM_KV + (i >> 8) * KV_CH + 16384 + (i & 255) * 16) = make_uint4(0x3f803f80u, 0x3f803f80u, 0x3f803f80u, 0x3f803f80u);
                fence_proxy_async();
            }
            __syncthreads();
            if (tid == 480) {
                const uint8_t* kvp = reinterpret_cast<const uint8_t*>(g_kv + head * 8192);
#pragma unroll 1
                for (int c = 2; c < 8; c++) {
                    mbar_expect_tx(bars + 8 * (B_KV + c), 16384);
                    bulk_g2s(sbase + SM_KV + c * KV_CH, kvp + c * 16384, 16384, bars + 8 * (B_KV + c));
                }
            } else if (tid == 352) {
                mbar_expect_tx(bars + 8 * B_WO, 65536);
                tma3d(sbase, &maps.wo, bars + 8 * B_WO, 0, idx & 7);
                tma3d(sbase + 32768, &maps.wo, bars + 8 * B_WO, 256, idx & 7);
                map_prefetch(&maps.o);
            }
            __syncwarp();
            const uint64_t kdesc0 = mkdesc(sbase + SM_KV, 4096, 128, 0);
            const uint64_t vdesc0 = mkdesc(sbase + SM_KV + 8192, 128, 4096, 0);
#pragma unroll 1
            for (int mt = 0; mt < 2; mt++) {
                const int m64 = quarter * 8 + mt * 4 + wg;
                uint32_t q[4];
                { const uint4 qq = __ldcg(&g_q[(head * 128 + m64 * 4 + w4) * 32 + lane]); q[0] = qq.x; q[1] = qq.y; q[2] = qq.z; q[3] = qq.w; }
                float s[32], s2[32], o[12];
#pragma unroll
                for (int i = 0; i < 12; i++) o[i] = 0.f;
                mbar_wait(bars + 8 * B_KV, 0);
                if (mt == 0) TL(5);
                WG_FENCE();
                qk64(s, q, kdesc0);
                WG_COMMIT(); WG_WAIT(0);
                float mx0 = -INFINITY, mx1 = -INFINITY;
#pragma unroll
                for (int i = 0; i < 8; i++) { mx0 = fmaxf(mx0, fmaxf(s[4 * i], s[4 * i + 1])); mx1 = fmaxf(mx1, fmaxf(s[4 * i + 2], s[4 * i + 3])); }
                mx0 = fmaxf(mx0, __shfl_xor_sync(~0u, mx0, 1)); mx0 = fmaxf(mx0, __shfl_xor_sync(~0u, mx0, 2));
                mx1 = fmaxf(mx1, __shfl_xor_sync(~0u, mx1, 1)); mx1 = fmaxf(mx1, __shfl_xor_sync(~0u, mx1, 2));
                float cm0 = -(ceilf(mx0 * QS) + SHIFT), cm1 = -(ceilf(mx1 * QS) + SHIFT);
                float cp0 = (cm0 + 127.f) * sc, cp1 = (cm1 + 127.f) * sc;
                asm volatile("" : "+f"(cm0), "+f"(cm1), "+f"(cp0), "+f"(cp1));
                uint64_t kd = kdesc0, vd = vdesc0;
                auto step = [&](float (&sc_)[32], float (&sn)[32], uint32_t kinc, uint32_t vinc) {
                    kd += kinc;
                    WG_FENCE();
                    qk64(sn, q, kd);
                    WG_COMMIT();
#pragma unroll
                    for (int kk = 0; kk < 4; kk++) {
                        const int i0 = kk * 2, i1 = kk * 2 + 1;
                        const uint32_t p0 = packbf(ex2(fmaf(sc_[4 * i0], QS, cm0)), ex2(fmaf(sc_[4 * i0 + 1], QS, cm0)));
                        const uint32_t p1 = packbf(ex2(fmaf(sc_[4 * i0 + 2], QS, cm1)), ex2(fmaf(sc_[4 * i0 + 3], QS, cm1)));
                        const uint32_t p2 = polyexp(fmaf(sc_[4 * i1], scq, cp0), fmaf(sc_[4 * i1 + 1], scq, cp0));
                        const uint32_t p3 = polyexp(fmaf(sc_[4 * i1 + 2], scq, cp1), fmaf(sc_[4 * i1 + 3], scq, cp1));
                        WG_FENCE();
                        pv24(o, p0, p1, p2, p3, vd);
                        vd += kk == 3 ? vinc : 16u;
                    }
                    WG_COMMIT();
                    WG_WAIT(1);
                };
#pragma unroll 1
                for (int c = 0; c < 16; c++) {
                    if (mt == 0) {
                        if ((c & 1) == 0 && c < 14) mbar_wait(bars + 8 * B_KV + 4 * c + 8, 0);
                    } else if (c == 2 && !badmask) {
                        nbar_sync(wg + 1, 128);
                        if ((tid & 127) == 0) flag_release(C_O + m64 - 4);
                    }
                    const uint32_t hop = (c & 1) ? (KV_CH - 4096) / 16 : 0u;
                    step(s, s2, 64u, 16u); step(s2, s, 64u + (c == 15 ? 0u : hop), 16u + hop);
                }
                WG_WAIT(0);
                bool bad = !(o[8] > 0.f) || !(o[10] > 0.f);
#pragma unroll
                for (int i = 0; i < 12; i++) bad = bad || !(fabsf(o[i]) <= 3.0e38f);
                uint32_t anybad;
                asm volatile("{\n.reg .pred p, q;\nsetp.ne.u32 p, %1, 0;\nbarrier.cta.red.or.pred q, %2, 128, p;\nselp.u32 %0, 1, 0, q;\n}"
                             : "=r"(anybad) : "r"((uint32_t)bad), "r"(wg + 1) : "memory");
                badmask |= __shfl_sync(~0u, anybad, 0) << mt;
                attn_store(o, head, m64, w4, lane);
            }
        }
        if (badmask) {
#pragma unroll 1
            for (int mt = 0; mt < 2; mt++) {
                if (!((badmask >> mt) & 1)) continue;
                const int m64 = quarter * 8 + mt * 4 + wg;
                uint32_t q[4];
                { const uint4 qq = __ldcg(&g_q[(head * 128 + m64 * 4 + w4) * 32 + lane]); q[0] = qq.x; q[1] = qq.y; q[2] = qq.z; q[3] = qq.w; }
                float o[12];
                attn_safe(o, q, mkdesc(sbase + SM_KV, 4096, 128, 0), mkdesc(sbase + SM_KV + 8192, 128, 4096, 0));
                attn_store(o, head, m64, w4, lane);
            }
        }
        nbar_sync(wg + 1, 128);
        if ((tid & 127) == 32) {
            asm volatile("fence.acq_rel.gpu;" ::: "memory");
            asm volatile("red.relaxed.gpu.global.add.u32 [%0], 1;" :: "l"(g_cnt + (C_O + quarter * 8 + 4 + wg) * 32) : "memory");
            if (badmask & 1) asm volatile("red.relaxed.gpu.global.add.u32 [%0], 1;" :: "l"(g_cnt + (C_O + quarter * 8 + wg) * 32) : "memory");
        }
        TL(6);
        {
            const int nb = idx & 7, jb = idx >> 3;
            const int mbe = (jb >> 2) * 8 + (jb & 3);
            float* supd = reinterpret_cast<float*>(smem + SM_MISC + 512);
            if (warp == 15) nbar_sync(7, 512); else nbar_arrive(7, 512);
            if (warp == 15) {
                flag_wait_all((lane & 1) ? C_FFN : C_O + mbe, (lane & 1) ? 64 : 32);
                nbar_arrive(9, 160);
                fence_proxy_async_all();
                if (lane == 0) {
                    for (int c = 0; c < 2; c++) {
                        mbar_expect_tx(bars + 8 * (B_OA + c), 32768);
                        tma3d(sbase + SM_KV + c * 32768, &maps.o, bars + 8 * (B_OA + c), mbe * 64, c * 4);
                    }
                }
                __syncwarp();
                flag_wait(C_O + mbe + 4, 32);
                fence_proxy_async_all();
                if (lane == 0) {
                    for (int c = 0; c < 2; c++) {
                        mbar_expect_tx(bars + 8 * (B_OA + 2 + c), 32768);
                        tma3d(sbase + SM_KV + 65536 + c * 32768, &maps.o, bars + 8 * (B_OA + 2 + c), (mbe + 4) * 64, c * 4);
                    }
                    exit_ticket();
                }
                __syncwarp();
            }
            const int late = wg >> 1, nh = wg & 1;
            const int mb = mbe + late * 4;
            const int g = lane >> 2, t = lane & 3;
            const int row0 = mb * 64 + w4 * 16 + g;
            const int col0 = nb * 64 + nh * 32 + t * 2;
            uint32_t xv[8], nv[8];
#pragma unroll
            for (int i = 0; i < 4; i++) {
                xv[2 * i] = *reinterpret_cast<const uint32_t*>(x + (size_t)row0 * DM + col0 + i * 8);
                xv[2 * i + 1] = *reinterpret_cast<const uint32_t*>(x + (size_t)(row0 + 8) * DM + col0 + i * 8);
                nv[2 * i] = __ldcg(reinterpret_cast<const uint32_t*>(g_xn + (size_t)row0 * DM + col0 + i * 8));
                nv[2 * i + 1] = __ldcg(reinterpret_cast<const uint32_t*>(g_xn + (size_t)(row0 + 8) * DM + col0 + i * 8));
            }
            if (wg == 0) {
                nbar_sync(9, 160);
                const int which = tid >> 6, col = nb * 64 + (tid & 63);
                const float y = __ldcg(&g_ypart[which * 512 + col]) + __ldcg(&g_ypart[1024 + which * 512 + col]) +
                                __ldcg(&g_ypart[2048 + which * 512 + col]) + __ldcg(&g_ypart[3072 + which * 512 + col]);
                supd[tid] = bfr(bfr(y) * __ldcg(&g_gate[which]));
                if (tid < 2) reinterpret_cast<int*>(supd + 128)[tid] = __ldcg(&g_sel[tid]);
            }
            float acc[16];
#pragma unroll
            for (int i = 0; i < 16; i++) acc[i] = 0.f;
            mbar_wait(bars + 8 * B_WO, 0);
            const uint32_t abase = sbase + SM_KV + late * 65536;
#pragma unroll 1
            for (int c = 0; c < 8; c++) {
                if ((c & 3) == 0) mbar_wait(bars + 8 * (B_OA + late * 2 + (c >> 2)), 0);
                if (c == 0) TLX(7, 256);
                const uint64_t da = mkdesc(abase + c * 8192, 16, 1024, 1);
                const uint64_t db = mkdesc(sbase + c * 8192 + nh * 64, 8192, 1024, 1);
                WG_FENCE();
#pragma unroll
                for (int k = 0; k < 4; k++) wgmma_n32(acc, da + k * 2, db + k * 128, (c | k) != 0);
                WG_COMMIT();
            }
            __syncthreads();
            const int sel0 = reinterpret_cast<const int*>(supd + 128)[0], sel1 = reinterpret_cast<const int*>(supd + 128)[1];
            WG_WAIT(0);
            TLX(8, 256);
#pragma unroll
            for (int h = 0; h < 2; h++) {
                const int row = row0 + h * 8;
                const int which = row == sel0 ? 0 : (row == sel1 ? 1 : -1);
#pragma unroll
                for (int i = 0; i < 4; i++) {
                    const int col = col0 + i * 8;
                    float b0 = bf_lo(nv[2 * i + h]), b1 = bf_hi(nv[2 * i + h]);
                    if (which >= 0) {
                        b0 = bfr(b0 + supd[which * 64 + col - nb * 64]); b1 = bfr(b1 + supd[which * 64 + col + 1 - nb * 64]);
                    }
                    const float t0 = bfr(bf_lo(xv[2 * i + h]) + bfr(acc[4 * i + 2 * h]));
                    const float t1 = bfr(bf_hi(xv[2 * i + h]) + bfr(acc[4 * i + 2 * h + 1]));
                    *reinterpret_cast<uint32_t*>(out + (size_t)row * DM + col) = packbf(t0 + b0, t1 + b1);
                }
            }
        }
        TLX(9, 256);
    }
}

typedef CUresult (*EncodeFn)(CUtensorMap*, CUtensorMapDataType, cuuint32_t, void*, const cuuint64_t*, const cuuint64_t*,
                             const cuuint32_t*, const cuuint32_t*, CUtensorMapInterleave, CUtensorMapSwizzle,
                             CUtensorMapL2promotion, CUtensorMapFloatOOBfill);

void make_map(EncodeFn fn, CUtensorMap* m, const void* ptr, uint64_t cols, uint64_t rows, uint32_t box_rows, uint32_t box_chunks) {
    cuuint64_t dims[3] = {64, rows, cols / 64};
    cuuint64_t strides[2] = {cols * 2, 128};
    cuuint32_t box[3] = {64, box_rows, box_chunks};
    cuuint32_t es[3] = {1, 1, 1};
    fn(m, CU_TENSOR_MAP_DATA_TYPE_BFLOAT16, 3, const_cast<void*>(ptr), dims, strides, box, es, CU_TENSOR_MAP_INTERLEAVE_NONE,
       CU_TENSOR_MAP_SWIZZLE_128B, CU_TENSOR_MAP_L2_PROMOTION_L2_256B, CU_TENSOR_MAP_FLOAT_OOB_FILL_NONE);
}

}

extern "C" void kernel_launch(void* const* d_in, const int* in_sizes, int n_in, void* d_out, int out_size) {
    const __nv_bfloat16* x = (const __nv_bfloat16*)d_in[0];
    const __nv_bfloat16* wqkv = (const __nv_bfloat16*)d_in[1];
    const __nv_bfloat16* wo = (const __nv_bfloat16*)d_in[2];
    const __nv_bfloat16* wr = (const __nv_bfloat16*)d_in[4];
    const __nv_bfloat16* wgate = (const __nv_bfloat16*)d_in[5];
    const __nv_bfloat16* wup = (const __nv_bfloat16*)d_in[6];
    const __nv_bfloat16* wdown = (const __nv_bfloat16*)d_in[7];
    __nv_bfloat16* out = (__nv_bfloat16*)d_out;

    static EncodeFn enc = nullptr;
    static void* p_xn = nullptr; static void* p_o = nullptr;
    if (!enc) {
        void* fn = nullptr; cudaDriverEntryPointQueryResult qr;
        cudaGetDriverEntryPoint("cuTensorMapEncodeTiled", &fn, cudaEnableDefault, &qr);
        enc = (EncodeFn)fn;
        cudaGetSymbolAddress(&p_xn, g_xn);
        cudaGetSymbolAddress(&p_o, g_o);
        cudaFuncSetAttribute(fused_kernel, cudaFuncAttributeMaxDynamicSharedMemorySize, FUSED_SMEM);
    }
    Maps maps;
    make_map(enc, &maps.g, wgate, FF, DM, 16, 7);
    make_map(enc, &maps.u, wup, FF, DM, 16, 7);
    make_map(enc, &maps.d, wdown, DM, FF, 32, 8);
    make_map(enc, &maps.xn, p_xn, DM, S_LEN, 128, 1);
    make_map(enc, &maps.wqkv, wqkv, 3 * DM, DM, 64, 3);
    make_map(enc, &maps.o, p_o, DM, S_LEN, 64, 4);
    make_map(enc, &maps.wo, wo, DM, DM, 256, 1);

    union { uint32_t u; float f; } scu; scu.u = 128u;

    cudaLaunchConfig_t cfg = {};
    cfg.gridDim = dim3(132); cfg.blockDim = dim3(512); cfg.dynamicSmemBytes = FUSED_SMEM; cfg.stream = cudaStreamPerThread;
    cudaLaunchKernelEx(&cfg, fused_kernel, maps, x, wr, out, scu.f);
}
```

```cpp
#include <cuda_runtime.h>
#include <cuda_bf16.h>
#include <cuda.h>
#include <stdint.h>
#include <type_traits>

namespace {

constexpr int S_LEN = 2048;
constexpr int DM = 512;
constexpr int NH = 32;
constexpr int FF = 1792;

__device__ __align__(1024) __nv_bfloat16 g_xn[S_LEN * DM];
__device__ __align__(16) float g_r[S_LEN];
__device__ __align__(1024) uint32_t g_qkv[NH * 8 * 6144];
__device__ __align__(1024) __nv_bfloat16 g_o[S_LEN * DM];
__device__ __align__(16) float g_ypart[4 * 2 * DM];
__device__ int g_sel[2];
__device__ float g_gate[2];
constexpr int C_LN = 0, C_QKV = 16, C_O = 24, C_FFN = 56, C_EXIT = 57, C_NUM = 58;
__device__ unsigned g_cnt[C_NUM * 32];

#define TL(slot) do {} while (0)
#define TLX(slot, th) do {} while (0)

__device__ __forceinline__ uint32_t smem_u32(const void* p) { return (uint32_t)__cvta_generic_to_shared(p); }
__device__ __forceinline__ void warp_arrive(int idx) {
    __syncwarp();
    if ((threadIdx.x & 31) == 0)
        asm volatile("red.release.gpu.global.add.u32 [%0], 1;" :: "l"(g_cnt + idx * 32) : "memory");
}
__device__ __forceinline__ void flag_release(int idx) {
    asm volatile("red.release.gpu.global.add.u32 [%0], 1;" :: "l"(g_cnt + idx * 32) : "memory");
}
__device__ __forceinline__ void exit_ticket() {
    unsigned tk;
    asm volatile("atom.relaxed.gpu.global.add.u32 %0, [%1], 1;" : "=r"(tk) : "l"(g_cnt + C_EXIT * 32) : "memory");
    if (tk == gridDim.x - 1) {
#pragma unroll 1
        for (int i = 0; i < C_NUM; i++) g_cnt[i * 32] = 0u;
    }
}
__device__ __forceinline__ void nbar_arrive(int id, int cnt) { asm volatile("bar.arrive %0, %1;" :: "r"(id), "r"(cnt) : "memory"); }
__device__ __forceinline__ void nbar_sync(int id, int cnt) { asm volatile("bar.sync %0, %1;" :: "r"(id), "r"(cnt) : "memory"); }
__device__ __forceinline__ void flag_wait(int idx, unsigned target) {
    asm volatile("{\n.reg .pred p;\n.reg .u32 n, v;\nmov.u32 n, 0;\n"
                 "FW_%=:\n"
                 "ld.acquire.gpu.global.u32 v, [%0];\n"
                 "setp.ge.u32 p, v, %1;\n"
                 "@p bra FD_%=;\n"
                 "add.u32 n, n, 1;\n"
                 "setp.lt.u32 p, n, 16000000;\n"
                 "@p bra FW_%=;\n"
                 "trap;\n"
                 "FD_%=:\n}"
                 :: "l"(g_cnt + idx * 32), "r"(target) : "memory");
}
__device__ __forceinline__ void flag_wait_all(int idx, unsigned target) {
    asm volatile("{\n.reg .pred p;\n.reg .u32 n, v;\nmov.u32 n, 0;\n"
                 "FW_%=:\n"
                 "ld.acquire.gpu.global.u32 v, [%0];\n"
                 "setp.ge.u32 p, v, %1;\n"
                 "vote.sync.all.pred p, p, 0xffffffff;\n"
                 "@p bra.uni FD_%=;\n"
                 "add.u32 n, n, 1;\n"
                 "setp.lt.u32 p, n, 16000000;\n"
                 "@p bra.uni FW_%=;\n"
                 "trap;\n"
                 "FD_%=:\n}"
                 :: "l"(g_cnt + idx * 32), "r"(target) : "memory");
}
__device__ __forceinline__ void fence_proxy_async_all() { asm volatile("fence.proxy.async.global;" ::: "memory"); }
__device__ __forceinline__ void mbar_init(uint32_t bar, uint32_t cnt) {
    asm volatile("mbarrier.init.shared::cta.b64 [%0], %1;" :: "r"(bar), "r"(cnt) : "memory");
}
__device__ __forceinline__ void mbar_expect_tx(uint32_t bar, uint32_t bytes) {
    asm volatile("mbarrier.arrive.expect_tx.shared::cta.b64 _, [%0], %1;" :: "r"(bar), "r"(bytes) : "memory");
}
__device__ __forceinline__ void mbar_arrive(uint32_t bar) {
    asm volatile("mbarrier.arrive.shared::cta.b64 _, [%0];" :: "r"(bar) : "memory");
}
__device__ __forceinline__ void mbar_wait(uint32_t bar, uint32_t parity) {
    asm volatile("{\n.reg .pred p;\n.reg .u32 n;\nmov.u32 n, 0;\n"
                 "WAIT_%=:\n"
                 "mbarrier.try_wait.parity.shared::cta.b64 p, [%0], %1;\n"
                 "@p bra DONE_%=;\n"
                 "add.u32 n, n, 1;\n"
                 "setp.lt.u32 p, n, 4000000;\n"
                 "@p bra WAIT_%=;\n"
                 "trap;\n"
                 "DONE_%=:\n}"
                 :: "r"(bar), "r"(parity) : "memory");
}
__device__ __forceinline__ void fence_barrier_init() { asm volatile("fence.mbarrier_init.release.cluster;" ::: "memory"); }
__device__ __forceinline__ void fence_proxy_async() { asm volatile("fence.proxy.async.shared::cta;" ::: "memory"); }
__device__ __forceinline__ void tma3d(uint32_t dst, const CUtensorMap* map, uint32_t bar, int row, int chunk) {
    asm volatile("cp.async.bulk.tensor.3d.shared::cluster.global.mbarrier::complete_tx::bytes [%0], [%1, {%3, %4, %5}], [%2];"
                 :: "r"(dst), "l"((uint64_t)map), "r"(bar), "r"(0), "r"(row), "r"(chunk) : "memory");
}
__device__ __forceinline__ void bulk_g2s(uint32_t dst, const void* src, uint32_t bytes, uint32_t bar) {
    asm volatile("cp.async.bulk.shared::cluster.global.mbarrier::complete_tx::bytes [%0], [%1], %2, [%3];"
                 :: "r"(dst), "l"((uint64_t)src), "r"(bytes), "r"(bar) : "memory");
}
__device__ __forceinline__ void l2_prefetch(const void* src, uint32_t bytes) {
    asm volatile("cp.async.bulk.prefetch.L2.global [%0], %1;" :: "l"((uint64_t)src), "r"(bytes) : "memory");
}
__device__ __forceinline__ void map_prefetch(const CUtensorMap* m) {
    asm volatile("prefetch.tensormap [%0];" :: "l"((uint64_t)m) : "memory");
}
__device__ __forceinline__ uint64_t mkdesc(uint32_t addr, uint32_t lbo, uint32_t sbo, uint32_t swz) {
    return (uint64_t)((addr & 0x3FFFF) >> 4) | ((uint64_t)(lbo >> 4) << 16) | ((uint64_t)(sbo >> 4) << 32) | ((uint64_t)swz << 62);
}
#define WG_FENCE() asm volatile("wgmma.fence.sync.aligned;" ::: "memory")
#define WG_COMMIT() asm volatile("wgmma.commit_group.sync.aligned;" ::: "memory")
#define WG_WAIT(n) asm volatile("wgmma.wait_group.sync.aligned %0;" :: "n"(n) : "memory")

__device__ __forceinline__ float ex2(float x) { float y; asm("ex2.approx.ftz.f32 %0, %1;" : "=f"(y) : "f"(x)); return y; }
__device__ __forceinline__ uint32_t packbf(float lo, float hi) {
    uint32_t r; asm("cvt.rn.bf16x2.f32 %0, %1, %2;" : "=r"(r) : "f"(hi), "f"(lo)); return r;
}
__device__ __forceinline__ uint32_t hmul2bf(uint32_t a, uint32_t b) { uint32_t r; asm("mul.rn.bf16x2 %0, %1, %2;" : "=r"(r) : "r"(a), "r"(b)); return r; }
__device__ __forceinline__ float bf_lo(uint32_t v) { return __uint_as_float(v << 16); }
__device__ __forceinline__ float bf_hi(uint32_t v) { return __uint_as_float(v & 0xffff0000u); }
__device__ __forceinline__ float bfr(float x) { return __bfloat162float(__float2bfloat16_rn(x)); }

__device__ __forceinline__ void wgmma_n192(float (&d)[96], uint64_t da, uint64_t db, int scale_d) {
    asm volatile("{\n.reg .pred p;\nsetp.ne.b32 p, %98, 0;\n"
        "wgmma.mma_async.sync.aligned.m64n192k16.f32.bf16.bf16 "
        "{%0,%1,%2,%3,%4,%5,%6,%7,%8,%9,%10,%11,%12,%13,%14,%15,%16,%17,%18,%19,%20,%21,%22,%23,"
        "%24,%25,%26,%27,%28,%29,%30,%31,%32,%33,%34,%35,%36,%37,%38,%39,%40,%41,%42,%43,%44,%45,%46,%47,"
        "%48,%49,%50,%51,%52,%53,%54,%55,%56,%57,%58,%59,%60,%61,%62,%63,%64,%65,%66,%67,%68,%69,%70,%71,"
        "%72,%73,%74,%75,%76,%77,%78,%79,%80,%81,%82,%83,%84,%85,%86,%87,%88,%89,%90,%91,%92,%93,%94,%95}, "
        "%96, %97, p, 1, 1, 0, 1;\n}"
        : "+f"(d[0]), "+f"(d[1]), "+f"(d[2]), "+f"(d[3]), "+f"(d[4]), "+f"(d[5]), "+f"(d[6]), "+f"(d[7]),
          "+f"(d[8]), "+f"(d[9]), "+f"(d[10]), "+f"(d[11]), "+f"(d[12]), "+f"(d[13]), "+f"(d[14]), "+f"(d[15]),
          "+f"(d[16]), "+f"(d[17]), "+f"(d[18]), "+f"(d[19]), "+f"(d[20]), "+f"(d[21]), "+f"(d[22]), "+f"(d[23]),
          "+f"(d[24]), "+f"(d[25]), "+f"(d[26]), "+f"(d[27]), "+f"(d[28]), "+f"(d[29]), "+f"(d[30]), "+f"(d[31]),
          "+f"(d[32]), "+f"(d[33]), "+f"(d[34]), "+f"(d[35]), "+f"(d[36]), "+f"(d[37]), "+f"(d[38]), "+f"(d[39]),
          "+f"(d[40]), "+f"(d[41]), "+f"(d[42]), "+f"(d[43]), "+f"(d[44]), "+f"(d[45]), "+f"(d[46]), "+f"(d[47]),
          "+f"(d[48]), "+f"(d[49]), "+f"(d[50]), "+f"(d[51]), "+f"(d[52]), "+f"(d[53]), "+f"(d[54]), "+f"(d[55]),
          "+f"(d[56]), "+f"(d[57]), "+f"(d[58]), "+f"(d[59]), "+f"(d[60]), "+f"(d[61]), "+f"(d[62]), "+f"(d[63]),
          "+f"(d[64]), "+f"(d[65]), "+f"(d[66]), "+f"(d[67]), "+f"(d[68]), "+f"(d[69]), "+f"(d[70]), "+f"(d[71]),
          "+f"(d[72]), "+f"(d[73]), "+f"(d[74]), "+f"(d[75]), "+f"(d[76]), "+f"(d[77]), "+f"(d[78]), "+f"(d[79]),
          "+f"(d[80]), "+f"(d[81]), "+f"(d[82]), "+f"(d[83]), "+f"(d[84]), "+f"(d[85]), "+f"(d[86]), "+f"(d[87]),
          "+f"(d[88]), "+f"(d[89]), "+f"(d[90]), "+f"(d[91]), "+f"(d[92]), "+f"(d[93]), "+f"(d[94]), "+f"(d[95])
        : "l"(da), "l"(db), "r"(scale_d));
}

constexpr float SHIFT = 90.0f;
constexpr float QS = 0.25f * 1.4426950408889634f * 18446744073709551616.0f;
constexpr float scq = 0.25f * 1.4426950408889634f * 3.3087224502121107e-24f;

__device__ __forceinline__ uint32_t polyexp(float lo, float hi) {
    uint32_t w, g, q, h;
    asm("cvt.pack.sat.s16.s32 %0, %1, %2;" : "=r"(w) : "r"(__float_as_uint(hi)), "r"(__float_as_uint(lo)));
    g = w & 0x007F007Fu;
    asm("fma.rn.f16x2 %0, %1, %2, %3;" : "=r"(q) : "r"(g), "r"(0xf940f940u), "r"(0x35513551u));
    asm("mul.rn.f16x2 %0, %1, %2;" : "=r"(h) : "r"(q), "r"(g));
    return w - h;
}
__device__ __forceinline__ void qk64(float (&s)[32], const uint32_t (&q)[4], uint64_t db) {
    asm volatile("wgmma.mma_async.sync.aligned.m64n64k16.f32.bf16.bf16 "
        "{%0,%1,%2,%3,%4,%5,%6,%7,%8,%9,%10,%11,%12,%13,%14,%15,%16,%17,%18,%19,%20,%21,%22,%23,%24,%25,%26,%27,%28,%29,%30,%31}, "
        "{%32,%33,%34,%35}, %36, 0, 1, 1, 0;"
        : "=f"(s[0]), "=f"(s[1]), "=f"(s[2]), "=f"(s[3]), "=f"(s[4]), "=f"(s[5]), "=f"(s[6]), "=f"(s[7]),
          "=f"(s[8]), "=f"(s[9]), "=f"(s[10]), "=f"(s[11]), "=f"(s[12]), "=f"(s[13]), "=f"(s[14]), "=f"(s[15]),
          "=f"(s[16]), "=f"(s[17]), "=f"(s[18]), "=f"(s[19]), "=f"(s[20]), "=f"(s[21]), "=f"(s[22]), "=f"(s[23]),
          "=f"(s[24]), "=f"(s[25]), "=f"(s[26]), "=f"(s[27]), "=f"(s[28]), "=f"(s[29]), "=f"(s[30]), "=f"(s[31])
        : "r"(q[0]), "r"(q[1]), "r"(q[2]), "r"(q[3]), "l"(db));
}
__device__ __forceinline__ void pv24(float (&o)[12], uint32_t a0, uint32_t a1, uint32_t a2, uint32_t a3, uint64_t db) {
    asm volatile("wgmma.mma_async.sync.aligned.m64n24k16.f32.bf16.bf16 "
        "{%0,%1,%2,%3,%4,%5,%6,%7,%8,%9,%10,%11}, {%12,%13,%14,%15}, %16, 1, 1, 1, 1;"
        : "+f"(o[0]), "+f"(o[1]), "+f"(o[2]), "+f"(o[3]), "+f"(o[4]), "+f"(o[5]), "+f"(o[6]), "+f"(o[7]),
          "+f"(o[8]), "+f"(o[9]), "+f"(o[10]), "+f"(o[11])
        : "r"(a0), "r"(a1), "r"(a2), "r"(a3), "l"(db));
}

__device__ __forceinline__ void attn_safe(float (&o)[12], const uint32_t (&q)[4], uint64_t kdesc0, uint64_t vdesc0) {
    float s[32];
    float m0 = -INFINITY, m1 = -INFINITY;
#pragma unroll
    for (int i = 0; i < 12; i++) o[i] = 0.f;
#pragma unroll 1
    for (int j = 0; j < 32; j++) {
        WG_FENCE();
        qk64(s, q, kdesc0 + (uint64_t)((j >> 2) * (20480 / 16) + (j & 3) * 64));
        WG_COMMIT(); WG_WAIT(0);
        float n0 = m0, n1 = m1;
#pragma unroll
        for (int i = 0; i < 8; i++) { n0 = fmaxf(n0, fmaxf(s[4 * i], s[4 * i + 1])); n1 = fmaxf(n1, fmaxf(s[4 * i + 2], s[4 * i + 3])); }
        n0 = fmaxf(n0, __shfl_xor_sync(~0u, n0, 1)); n0 = fmaxf(n0, __shfl_xor_sync(~0u, n0, 2));
        n1 = fmaxf(n1, __shfl_xor_sync(~0u, n1, 1)); n1 = fmaxf(n1, __shfl_xor_sync(~0u, n1, 2));
        const float c0 = ex2((m0 - n0) * QS), c1 = ex2((m1 - n1) * QS);
        m0 = n0; m1 = n1;
#pragma unroll
        for (int i = 0; i < 3; i++) { o[4 * i] *= c0; o[4 * i + 1] *= c0; o[4 * i + 2] *= c1; o[4 * i + 3] *= c1; }
        uint32_t p[16];
#pragma unroll
        for (int i = 0; i < 8; i++) {
            p[2 * i] = packbf(ex2((s[4 * i] - m0) * QS), ex2((s[4 * i + 1] - m0) * QS));
            p[2 * i + 1] = packbf(ex2((s[4 * i + 2] - m1) * QS), ex2((s[4 * i + 3] - m1) * QS));
        }
        WG_FENCE();
#pragma unroll
        for (int kk = 0; kk < 4; kk++) pv24(o, p[4 * kk], p[4 * kk + 1], p[4 * kk + 2], p[4 * kk + 3], vdesc0 + (uint64_t)((j >> 2) * (20480 / 16) + (j & 3) * 64 + kk * 16));
        WG_COMMIT(); WG_WAIT(0);
    }
}

__device__ __forceinline__ void load_q(uint32_t (&q)[4], int head, int mt, int lane) {
    const uint32_t* src = g_qkv + head * 49152 + (mt >> 4) * 6144 + 4096 + (mt & 15) * 64 + lane;
    q[0] = __ldcg(src); q[1] = __ldcg(src + 32); q[2] = __ldcg(src + 1024); q[3] = __ldcg(src + 1024 + 32);
}
__device__ __forceinline__ void attn_store(const float (&o)[12], int head, int m64, int warp, int lane) {
    const int g = lane >> 2, t = lane & 3;
    const int row = m64 * 64 + warp * 16 + g;
    const float i0 = 1.f / o[8], i1 = 1.f / o[10];
    uint32_t* p0 = reinterpret_cast<uint32_t*>(g_o + (size_t)row * DM + head * 16 + t * 2);
    uint32_t* p1 = reinterpret_cast<uint32_t*>(g_o + (size_t)(row + 8) * DM + head * 16 + t * 2);
    p0[0] = packbf(o[0] * i0, o[1] * i0); p0[4] = packbf(o[4] * i0, o[5] * i0);
    p1[0] = packbf(o[2] * i1, o[3] * i1); p1[4] = packbf(o[6] * i1, o[7] * i1);
}

constexpr int FS_N = 4;
constexpr int FS_BYTES = 32768;
__device__ __forceinline__ void ldsm4t(uint32_t& r0, uint32_t& r1, uint32_t& r2, uint32_t& r3, uint32_t addr) {
    asm volatile("ldmatrix.sync.aligned.m8n8.x4.trans.shared.b16 {%0,%1,%2,%3}, [%4];" : "=r"(r0), "=r"(r1), "=r"(r2), "=r"(r3) : "r"(addr) : "memory");
}
__device__ __forceinline__ void mma16816(float (&d)[4], uint32_t a0, uint32_t a2, uint32_t b0, uint32_t b1) {
    asm volatile("mma.sync.aligned.m16n8k16.row.col.f32.bf16.bf16.f32 {%0,%1,%2,%3}, {%4,%5,%6,%5}, {%7,%8}, {%0,%1,%2,%3};"
                 : "+f"(d[0]), "+f"(d[1]), "+f"(d[2]), "+f"(d[3]) : "r"(a0), "r"(0u), "r"(a2), "r"(b0), "r"(b1));
}
__device__ void ffn_block(int c, uint8_t* smem, uint32_t sbase, const CUtensorMap* mapG, const CUtensorMap* mapU, const CUtensorMap* mapD) {
    const int tid = threadIdx.x, warp = tid >> 5, lane = tid & 31;
    uint32_t* sx = reinterpret_cast<uint32_t*>(smem + FS_N * FS_BYTES);
    __nv_bfloat16* sh = reinterpret_cast<__nv_bfloat16*>(sx + 512);
    const uint32_t bars = sbase + FS_N * FS_BYTES + 8192;
    float* tv = reinterpret_cast<float*>(smem + FS_N * FS_BYTES + 4096);
    int* ti = reinterpret_cast<int*>(tv + 32);
    int* ssel = ti + 32;
    auto issue = [&](int item) {
        const int slot = item % FS_N;
        const uint32_t dst = sbase + slot * FS_BYTES, bar = bars + 8 * slot;
        mbar_expect_tx(bar, item < 32 ? 28672 : 32768);
        if (item < 32) {
            tma3d(dst, mapG, bar, item * 16, c * 7);
            tma3d(dst + 14336, mapU, bar, item * 16, c * 7);
        } else {
            tma3d(dst, mapD, bar, c * 448 + (item - 32) * 32, 0);
        }
    };
    if (tid == 0) {
        for (int i = 0; i < FS_N; i++) mbar_init(bars + 8 * i, 1);
        fence_barrier_init();
        for (int i = 0; i < FS_N; i++) issue(i);
    }
    flag_wait(C_LN + warp, 8);
    __syncthreads();
    float b1 = -INFINITY, b2 = -INFINITY; int i1 = 0x7fffffff, i2 = 0x7fffffff;
    auto push = [&](float v, int i) {
        if (v > b1 || (v == b1 && i < i1)) { b2 = b1; i2 = i1; b1 = v; i1 = i; }
        else if (v > b2 || (v == b2 && i < i2)) { b2 = v; i2 = i; }
    };
    {
        const float4 rv = __ldcg(reinterpret_cast<const float4*>(g_r) + tid);
        push(rv.x, 4 * tid); push(rv.y, 4 * tid + 1); push(rv.z, 4 * tid + 2); push(rv.w, 4 * tid + 3);
    }
#pragma unroll
    for (int o = 16; o > 0; o >>= 1) {
        float v1 = __shfl_xor_sync(~0u, b1, o), v2 = __shfl_xor_sync(~0u, b2, o);
        int j1 = __shfl_xor_sync(~0u, i1, o), j2 = __shfl_xor_sync(~0u, i2, o);
        push(v1, j1); push(v2, j2);
    }
    if (lane == 0) { tv[2 * warp] = b1; ti[2 * warp] = i1; tv[2 * warp + 1] = b2; ti[2 * warp + 1] = i2; }
    __syncthreads();
    if (warp == 1) {
        b1 = tv[lane]; i1 = ti[lane]; b2 = -INFINITY; i2 = 0x7fffffff;
#pragma unroll
        for (int o = 16; o > 0; o >>= 1) {
            float v1 = __shfl_xor_sync(~0u, b1, o), v2 = __shfl_xor_sync(~0u, b2, o);
            int j1 = __shfl_xor_sync(~0u, i1, o), j2 = __shfl_xor_sync(~0u, i2, o);
            push(v1, j1); push(v2, j2);
        }
        if (lane == 0) {
            i1 = min(max(i1, 0), S_LEN - 1); i2 = min(max(i2, 0), S_LEN - 1);
            ssel[0] = i1; ssel[1] = i2;
            if (c == 0) {
                g_sel[0] = i1; g_sel[1] = i2;
                g_gate[0] = bfr(1.f / (1.f + __expf(-bfr(b1))));
                g_gate[1] = bfr(1.f / (1.f + __expf(-bfr(b2))));
            }
        }
    }
    __syncthreads();
    sx[tid] = __ldcg(reinterpret_cast<const uint32_t*>(g_xn + (size_t)ssel[tid >> 8] * DM + (tid & 255) * 2));
    __syncthreads();
    TL(1);
    const int g = lane >> 2, t = lane & 3;
    const int lrow = lane & 15, lsel = lane >> 4;
    {
        float ag[4][4], au[4][4];
#pragma unroll
        for (int j = 0; j < 4; j++) { ag[j][0] = ag[j][1] = ag[j][2] = ag[j][3] = 0.f; au[j][0] = au[j][1] = au[j][2] = au[j][3] = 0.f; }
#pragma unroll 1
        for (int it = 0; it < 32; it++) {
            const int slot = it % FS_N;
            const uint32_t a0 = g < 2 ? sx[g * 256 + it * 8 + t] : 0u, a2 = g < 2 ? sx[g * 256 + it * 8 + 4 + t] : 0u;
            mbar_wait(bars + 8 * slot, (it / FS_N) & 1);
            const uint32_t base = sbase + slot * FS_BYTES + lsel * 14336 + lrow * 128;
#pragma unroll
            for (int j = 0; j < 4; j++) {
                const int nt = warp + j * 16;
                if (nt < 56) {
                    uint32_t b0, b1, b2, b3;
                    ldsm4t(b0, b1, b2, b3, base + (nt >> 3) * 2048 + (((nt & 7) ^ (lrow & 7)) << 4));
                    mma16816(ag[j], a0, a2, b0, b1);
                    mma16816(au[j], a0, a2, b2, b3);
                }
            }
            __syncthreads();
            if (tid == 480) issue(it + FS_N);
        }
        if (g < 2) {
#pragma unroll
            for (int j = 0; j < 4; j++) {
                const int nt = warp + j * 16;
                if (nt < 56) {
#pragma unroll
                    for (int e = 0; e < 2; e++) {
                        const float gs = bfr(ag[j][e]), us = bfr(au[j][e]);
                        const float sg = bfr(gs / (1.f + __expf(-gs)));
                        sh[g * 448 + nt * 8 + t * 2 + e] = __float2bfloat16_rn(sg * us);
                    }
                }
            }
        }
        __syncthreads();
    }
    TL(2);
    {
        const uint32_t* shw = reinterpret_cast<const uint32_t*>(sh);
        float a[4][4];
#pragma unroll
        for (int j = 0; j < 4; j++) a[j][0] = a[j][1] = a[j][2] = a[j][3] = 0.f;
#pragma unroll 1
        for (int it = 32; it < 46; it++) {
            const int slot = it % FS_N;
            uint32_t af[4];
#pragma unroll
            for (int q = 0; q < 4; q++) af[q] = g < 2 ? shw[g * 224 + (it - 32) * 16 + q * 4 + t] : 0u;
            mbar_wait(bars + 8 * slot, (it / FS_N) & 1);
            const uint32_t base = sbase + slot * FS_BYTES + (warp >> 1) * 4096 + lane * 128;
#pragma unroll
            for (int j = 0; j < 4; j++) {
                const int u = (warp & 1) * 4 + j;
                uint32_t b0, b1, b2, b3;
                ldsm4t(b0, b1, b2, b3, base + ((u ^ (lane & 7)) << 4));
                mma16816(a[j], af[0], af[1], b0, b1);
                mma16816(a[j], af[2], af[3], b2, b3);
            }
            __syncthreads();
            if (tid == 480 && it + FS_N < 46) issue(it + FS_N);
        }
        if (g < 2) {
#pragma unroll
            for (int j = 0; j < 4; j++)
                *reinterpret_cast<float2*>(&g_ypart[c * 1024 + g * 512 + (warp * 4 + j) * 8 + t * 2]) = make_float2(a[j][0], a[j][1]);
        }
    }
    warp_arrive(C_FFN);
}

__device__ __forceinline__ void wgmma_n32(float (&d)[16], uint64_t da, uint64_t db, int scale_d) {
    asm volatile("{\n.reg .pred p;\nsetp.ne.b32 p, %18, 0;\n"
        "wgmma.mma_async.sync.aligned.m64n32k16.f32.bf16.bf16 "
        "{%0,%1,%2,%3,%4,%5,%6,%7,%8,%9,%10,%11,%12,%13,%14,%15}, "
        "%16, %17, p, 1, 1, 0, 1;\n}"
        : "+f"(d[0]), "+f"(d[1]), "+f"(d[2]), "+f"(d[3]), "+f"(d[4]), "+f"(d[5]), "+f"(d[6]), "+f"(d[7]),
          "+f"(d[8]), "+f"(d[9]), "+f"(d[10]), "+f"(d[11]), "+f"(d[12]), "+f"(d[13]), "+f"(d[14]), "+f"(d[15])
        : "l"(da), "l"(db), "r"(scale_d));
}

constexpr int G_ST = 4;
constexpr int G_STAGE = 16384 + 24576;
constexpr int SM_KV = 65536, KV_CH = 20480, SM_MISC = 229376;
constexpr int FUSED_SMEM = SM_MISC + 2048;
constexpr int B_FULL = 0, B_EMPTY = 4, B_KV = 8, B_WO = 16, B_OA = 18, B_NUM = 22;

struct Maps { CUtensorMap xn, wqkv, o, wo, g, u, d; };

__global__ void __launch_bounds__(512, 1) fused_kernel(const __grid_constant__ Maps maps, const __nv_bfloat16* __restrict__ x,
                                                       const __nv_bfloat16* __restrict__ wr, __nv_bfloat16* __restrict__ out, float sc) {
    extern __shared__ __align__(1024) uint8_t smem[];
    const uint32_t sbase = smem_u32(smem);
    const int tid = threadIdx.x, warp = __shfl_sync(~0u, tid >> 5, 0), lane = tid & 31;
    const uint32_t bars = sbase + SM_MISC;
    TL(0);
    if (sbase & 1023u) __trap();
    if (blockIdx.x < 4) {
        ffn_block(blockIdx.x, smem, sbase, &maps.g, &maps.u, &maps.d);
        __syncthreads();
        if (tid == 0) exit_ticket();
        TL(3);
    } else {
        const int idx = blockIdx.x - 4;
        const int wg = warp >> 2;
        {
            const int row = idx * 16 + warp;
            const uint4* xr = reinterpret_cast<const uint4*>(x + (size_t)row * DM);
            const uint4 a = xr[lane], b = xr[32 + lane];
            const uint4* wp = reinterpret_cast<const uint4*>(wr);
            const uint4 wa = wp[lane], wb = wp[32 + lane];
            if (tid == 480) {
                for (int s = 0; s < G_ST; s++) { mbar_init(bars + 8 * (B_FULL + s), 2); mbar_init(bars + 8 * (B_EMPTY + s), 2); }
                for (int c = B_KV; c < B_NUM; c++) mbar_init(bars + 8 * c, 1);
                fence_barrier_init();
                for (int c = 0; c < G_ST; c++) {
                    mbar_expect_tx(bars + 8 * (B_FULL + c), 24576);
                    tma3d(sbase + c * G_STAGE + 16384, &maps.wqkv, bars + 8 * (B_FULL + c), c * 64, (idx & 7) * 3);
                }
                map_prefetch(&maps.xn);
            }
            __syncwarp();
            const uint32_t u[8] = {a.x, a.y, a.z, a.w, b.x, b.y, b.z, b.w};
            const uint32_t w[8] = {wa.x, wa.y, wa.z, wa.w, wb.x, wb.y, wb.z, wb.w};
            float f[16];
            float sum = 0.f;
#pragma unroll
            for (int i = 0; i < 8; i++) { f[2 * i] = bf_lo(u[i]); f[2 * i + 1] = bf_hi(u[i]); sum += f[2 * i] + f[2 * i + 1]; }
#pragma unroll
            for (int o = 16; o > 0; o >>= 1) sum += __shfl_xor_sync(~0u, sum, o);
            const float mean = sum * (1.f / DM);
            float sq = 0.f;
#pragma unroll
            for (int i = 0; i < 16; i++) { const float d = f[i] - mean; sq = fmaf(d, d, sq); }
#pragma unroll
            for (int o = 16; o > 0; o >>= 1) sq += __shfl_xor_sync(~0u, sq, o);
            const float mb_ = bfr(mean);
            const float vb = bfr(sq * (1.f / DM));
            const float rinv = 1.f / bfr(sqrtf(bfr(vb + 1e-5f)));
            uint32_t o[8];
            float r = 0.f;
#pragma unroll
            for (int i = 0; i < 8; i++) {
                const float d0 = bfr(f[2 * i] - mb_), d1 = bfr(f[2 * i + 1] - mb_);
                o[i] = packbf(d0 * rinv, d1 * rinv);
                r = fmaf(bf_lo(o[i]), bf_lo(w[i]), r);
                r = fmaf(bf_hi(o[i]), bf_hi(w[i]), r);
            }
            uint4* xo = reinterpret_cast<uint4*>(g_xn + (size_t)row * DM);
            xo[lane] = make_uint4(o[0], o[1], o[2], o[3]);
            xo[32 + lane] = make_uint4(o[4], o[5], o[6], o[7]);
#pragma unroll
            for (int of = 16; of > 0; of >>= 1) r += __shfl_xor_sync(~0u, r, of);
            if (lane == 0) g_r[row] = r;
        }
        __syncthreads();
        if (tid == 416) flag_release(C_LN + (idx >> 3));
        TL(1);
        {
            const int nb = idx & 7, mb = idx >> 3;
            if (warp == 15) {
                for (int c = G_ST; c < 8; c++) {
                    const int s = c - G_ST;
                    mbar_wait(bars + 8 * (B_EMPTY + s), 0);
                    if (lane == 0) {
                        mbar_expect_tx(bars + 8 * (B_FULL + s), 24576);
                        tma3d(sbase + s * G_STAGE + 16384, &maps.wqkv, bars + 8 * (B_FULL + s), c * 64, nb * 3);
                    }
                    __syncwarp();
                }
            } else if (warp == 14) {
                flag_wait(C_LN + mb, 8);
                fence_proxy_async_all();
                for (int c = 0; c < 8; c++) {
                    const int s = c & (G_ST - 1);
                    if (c >= G_ST) mbar_wait(bars + 8 * (B_EMPTY + s), 0);
                    if (lane == 0) {
                        mbar_expect_tx(bars + 8 * (B_FULL + s), 16384);
                        tma3d(sbase + s * G_STAGE, &maps.xn, bars + 8 * (B_FULL + s), mb * 128, c);
                    }
                    __syncwarp();
                }
            } else if (wg < 2) {
                float acc[96];
#pragma unroll
                for (int i = 0; i < 96; i++) acc[i] = 0.f;
#pragma unroll 1
                for (int c = 0; c < 8; c++) {
                    const int s = c & (G_ST - 1);
                    const uint32_t st = sbase + s * G_STAGE;
                    mbar_wait(bars + 8 * (B_FULL + s), c >> 2);
                    if (c == 0) TL(2);
                    const uint64_t da = mkdesc(st + wg * 8192, 16, 1024, 1);
                    const uint64_t db = mkdesc(st + 16384, 8192, 1024, 1);
                    WG_FENCE();
#pragma unroll
                    for (int k = 0; k < 4; k++) wgmma_n192(acc, da + k * 2, db + k * 128, (c | k) != 0);
                    WG_COMMIT();
                    if (c <= G_ST) {
                        WG_WAIT(1);
                        if (c >= 1 && (tid & 127) == 0) mbar_arrive(bars + 8 * (B_EMPTY + c - 1));
                    }
                }
                WG_WAIT(0);
                nbar_arrive(6, 512);
                TL(3);
                const int mt = mb * 8 + warp;
                uint32_t* dst0 = g_qkv + (mt >> 4) * 6144 + (mt & 15) * 64 + lane;
#pragma unroll
                for (int hh = 0; hh < 12; hh++) {
                    const int gh = nb * 12 + hh, ty = gh >> 5;
                    const float* a = &acc[hh * 8];
                    uint32_t* dst = dst0 + (gh & 31) * 49152 + ((ty + 2) % 3) * 2048;
                    const uint32_t ks = ty == 1 ? 0x1f801f80u : 0x3f803f80u;
                    dst[0] = hmul2bf(packbf(a[0], a[1]), ks);
                    dst[32] = hmul2bf(packbf(a[2], a[3]), ks);
                    dst[1024] = hmul2bf(packbf(a[4], a[5]), ks);
                    dst[1024 + 32] = hmul2bf(packbf(a[6], a[7]), ks);
                }
                TL(10);
                nbar_sync(8, 256);
                if (tid == 0) flag_release(C_QKV + nb);
            }
        }
        TL(4);
        uint32_t badmask = 0;
        const int head = idx >> 2, quarter = idx & 3, w4 = warp & 3;
        {
            if (warp == 15) {
                flag_wait_all(C_QKV + ((lane % 3) * 32 + head) / 12, 16);
                nbar_sync(6, 512);
                fence_proxy_async_all();
                if (lane == 0) {
                    const uint8_t* kvp = reinterpret_cast<const uint8_t*>(g_qkv + head * 49152);
#pragma unroll 1
                    for (int c = 0; c < 2; c++) {
                        mbar_expect_tx(bars + 8 * (B_KV + c), 16384);
                        bulk_g2s(sbase + SM_KV + c * KV_CH, kvp + c * 24576, 16384, bars + 8 * (B_KV + c));
                    }
                }
                __syncwarp();
            } else if (wg >= 2) {
                nbar_sync(6, 512);
#pragma unroll 1
                for (int i = tid - 256; i < 2048; i += 224)
                    *reinterpret_cast<uint4*>(smem + SM_KV + (i >> 8) * KV_CH + 16384 + (i & 255) * 16) = make_uint4(0x3f803f80u, 0x3f803f80u, 0x3f803f80u, 0x3f803f80u);
                fence_proxy_async();
            }
            __syncthreads();
            if (tid == 480) {
                const uint8_t* kvp = reinterpret_cast<const uint8_t*>(g_qkv + head * 49152);
#pragma unroll 1
                for (int c = 2; c < 8; c++) {
                    mbar_expect_tx(bars + 8 * (B_KV + c), 16384);
                    bulk_g2s(sbase + SM_KV + c * KV_CH, kvp + c * 24576, 16384, bars + 8 * (B_KV + c));
                }
            } else if (tid == 352) {
                mbar_expect_tx(bars + 8 * B_WO, 65536);
                tma3d(sbase, &maps.wo, bars + 8 * B_WO, 0, idx & 7);
                tma3d(sbase + 32768, &maps.wo, bars + 8 * B_WO, 256, idx & 7);
                map_prefetch(&maps.o);
            }
            __syncwarp();
            const uint64_t kdesc0 = mkdesc(sbase + SM_KV, 4096, 128, 0);
            const uint64_t vdesc0 = mkdesc(sbase + SM_KV + 8192, 128, 4096, 0);
#pragma unroll 1
            for (int mt = 0; mt < 2; mt++) {
                const int m64 = quarter * 8 + mt * 4 + wg;
                uint32_t q[4];
                load_q(q, head, m64 * 4 + w4, lane);
                float s[32], s2[32], o[12];
#pragma unroll
                for (int i = 0; i < 12; i++) o[i] = 0.f;
                mbar_wait(bars + 8 * B_KV, 0);
                if (mt == 0) TL(5);
                WG_FENCE();
                qk64(s, q, kdesc0);
                WG_COMMIT(); WG_WAIT(0);
                float mx0 = -INFINITY, mx1 = -INFINITY;
#pragma unroll
                for (int i = 0; i < 8; i++) { mx0 = fmaxf(mx0, fmaxf(s[4 * i], s[4 * i + 1])); mx1 = fmaxf(mx1, fmaxf(s[4 * i + 2], s[4 * i + 3])); }
                mx0 = fmaxf(mx0, __shfl_xor_sync(~0u, mx0, 1)); mx0 = fmaxf(mx0, __shfl_xor_sync(~0u, mx0, 2));
                mx1 = fmaxf(mx1, __shfl_xor_sync(~0u, mx1, 1)); mx1 = fmaxf(mx1, __shfl_xor_sync(~0u, mx1, 2));
                float cm0 = -(ceilf(mx0 * QS) + SHIFT), cm1 = -(ceilf(mx1 * QS) + SHIFT);
                float cp0 = (cm0 + 127.f) * sc, cp1 = (cm1 + 127.f) * sc;
                asm volatile("" : "+f"(cm0), "+f"(cm1), "+f"(cp0), "+f"(cp1));
                uint64_t kd = kdesc0, vd = vdesc0;
                auto step = [&](float (&sc_)[32], float (&sn)[32], uint32_t kinc, uint32_t vinc) {
                    kd += kinc;
                    WG_FENCE();
                    qk64(sn, q, kd);
                    WG_COMMIT();
#pragma unroll
                    for (int kk = 0; kk < 4; kk++) {
                        const int i0 = kk * 2, i1 = kk * 2 + 1;
                        const uint32_t p0 = packbf(ex2(fmaf(sc_[4 * i0], QS, cm0)), ex2(fmaf(sc_[4 * i0 + 1], QS, cm0)));
                        const uint32_t p1 = packbf(ex2(fmaf(sc_[4 * i0 + 2], QS, cm1)), ex2(fmaf(sc_[4 * i0 + 3], QS, cm1)));
                        const uint32_t p2 = polyexp(fmaf(sc_[4 * i1], scq, cp0), fmaf(sc_[4 * i1 + 1], scq, cp0));
                        const uint32_t p3 = polyexp(fmaf(sc_[4 * i1 + 2], scq, cp1), fmaf(sc_[4 * i1 + 3], scq, cp1));
                        WG_FENCE();
                        pv24(o, p0, p1, p2, p3, vd);
                        vd += kk == 3 ? vinc : 16u;
                    }
                    WG_COMMIT();
                    WG_WAIT(1);
                };
#pragma unroll 1
                for (int c = 0; c < 16; c++) {
                    if (mt == 0) {
                        if ((c & 1) == 0 && c < 14) mbar_wait(bars + 8 * B_KV + 4 * c + 8, 0);
                    } else if (c == 2 && !badmask) {
                        nbar_sync(wg + 1, 128);
                        if ((tid & 127) == 0) flag_release(C_O + m64 - 4);
                    }
                    const uint32_t hop = (c & 1) ? (KV_CH - 4096) / 16 : 0u;
                    step(s, s2, 64u, 16u); step(s2, s, 64u + (c == 15 ? 0u : hop), 16u + hop);
                }
                WG_WAIT(0);
                bool bad = !(o[8] > 0.f) || !(o[10] > 0.f);
#pragma unroll
                for (int i = 0; i < 12; i++) bad = bad || !(fabsf(o[i]) <= 3.0e38f);
                uint32_t anybad;
                asm volatile("{\n.reg .pred p, q;\nsetp.ne.u32 p, %1, 0;\nbarrier.cta.red.or.pred q, %2, 128, p;\nselp.u32 %0, 1, 0, q;\n}"
                             : "=r"(anybad) : "r"((uint32_t)bad), "r"(wg + 1) : "memory");
                badmask |= __shfl_sync(~0u, anybad, 0) << mt;
                attn_store(o, head, m64, w4, lane);
            }
        }
        if (badmask) {
#pragma unroll 1
            for (int mt = 0; mt < 2; mt++) {
                if (!((badmask >> mt) & 1)) continue;
                const int m64 = quarter * 8 + mt * 4 + wg;
                uint32_t q[4];
                load_q(q, head, m64 * 4 + w4, lane);
                float o[12];
                attn_safe(o, q, mkdesc(sbase + SM_KV, 4096, 128, 0), mkdesc(sbase + SM_KV + 8192, 128, 4096, 0));
                attn_store(o, head, m64, w4, lane);
            }
        }
        nbar_sync(wg + 1, 128);
        if ((tid & 127) == 32) {
            asm volatile("fence.acq_rel.gpu;" ::: "memory");
            asm volatile("red.relaxed.gpu.global.add.u32 [%0], 1;" :: "l"(g_cnt + (C_O + quarter * 8 + 4 + wg) * 32) : "memory");
            if (badmask & 1) asm volatile("red.relaxed.gpu.global.add.u32 [%0], 1;" :: "l"(g_cnt + (C_O + quarter * 8 + wg) * 32) : "memory");
        }
        TLX(14, 416);
        TLX(15, 384);
        TL(6);
        {
            const int nb = idx & 7, jb = idx >> 3;
            const int mbe = (jb >> 2) * 8 + (jb & 3);
            float* supd = reinterpret_cast<float*>(smem + SM_MISC + 512);
            if (warp == 15) nbar_sync(7, 512); else nbar_arrive(7, 512);
            TLX(11, 480);
            if (warp == 15) {
                flag_wait_all((lane & 1) ? C_FFN : C_O + mbe, (lane & 1) ? 64 : 32);
                nbar_arrive(9, 160);
                fence_proxy_async_all();
                if (lane == 0) {
                    for (int c = 0; c < 2; c++) {
                        mbar_expect_tx(bars + 8 * (B_OA + c), 32768);
                        tma3d(sbase + SM_KV + c * 32768, &maps.o, bars + 8 * (B_OA + c), mbe * 64, c * 4);
                    }
                }
                __syncwarp();
                TLX(12, 480);
                flag_wait(C_O + mbe + 4, 32);
                TLX(13, 480);
                fence_proxy_async_all();
                if (lane == 0) {
                    for (int c = 0; c < 2; c++) {
                        mbar_expect_tx(bars + 8 * (B_OA + 2 + c), 32768);
                        tma3d(sbase + SM_KV + 65536 + c * 32768, &maps.o, bars + 8 * (B_OA + 2 + c), (mbe + 4) * 64, c * 4);
                    }
                    exit_ticket();
                }
                __syncwarp();
            }
            const int late = wg >> 1, nh = wg & 1;
            const int mb = mbe + late * 4;
            const int g = lane >> 2, t = lane & 3;
            const int row0 = mb * 64 + w4 * 16 + g;
            const int col0 = nb * 64 + nh * 32 + t * 2;
            uint32_t xv[8], nv[8];
#pragma unroll
            for (int i = 0; i < 4; i++) {
                xv[2 * i] = *reinterpret_cast<const uint32_t*>(x + (size_t)row0 * DM + col0 + i * 8);
                xv[2 * i + 1] = *reinterpret_cast<const uint32_t*>(x + (size_t)(row0 + 8) * DM + col0 + i * 8);
                nv[2 * i] = __ldcg(reinterpret_cast<const uint32_t*>(g_xn + (size_t)row0 * DM + col0 + i * 8));
                nv[2 * i + 1] = __ldcg(reinterpret_cast<const uint32_t*>(g_xn + (size_t)(row0 + 8) * DM + col0 + i * 8));
            }
            if (wg == 0) {
                nbar_sync(9, 160);
                const int which = tid >> 6, col = nb * 64 + (tid & 63);
                const float y = __ldcg(&g_ypart[which * 512 + col]) + __ldcg(&g_ypart[1024 + which * 512 + col]) +
                                __ldcg(&g_ypart[2048 + which * 512 + col]) + __ldcg(&g_ypart[3072 + which * 512 + col]);
                supd[tid] = bfr(bfr(y) * __ldcg(&g_gate[which]));
                if (tid < 2) reinterpret_cast<int*>(supd + 128)[tid] = __ldcg(&g_sel[tid]);
            }
            float acc[16];
#pragma unroll
            for (int i = 0; i < 16; i++) acc[i] = 0.f;
            mbar_wait(bars + 8 * B_WO, 0);
            const uint32_t abase = sbase + SM_KV + late * 65536;
#pragma unroll 1
            for (int c = 0; c < 8; c++) {
                if ((c & 3) == 0) mbar_wait(bars + 8 * (B_OA + late * 2 + (c >> 2)), 0);
                if (c == 0) TLX(7, 256);
                const uint64_t da = mkdesc(abase + c * 8192, 16, 1024, 1);
                const uint64_t db = mkdesc(sbase + c * 8192 + nh * 64, 8192, 1024, 1);
                WG_FENCE();
#pragma unroll
                for (int k = 0; k < 4; k++) wgmma_n32(acc, da + k * 2, db + k * 128, (c | k) != 0);
                WG_COMMIT();
            }
            __syncthreads();
            const int sel0 = reinterpret_cast<const int*>(supd + 128)[0], sel1 = reinterpret_cast<const int*>(supd + 128)[1];
            WG_WAIT(0);
            TLX(8, 256);
#pragma unroll
            for (int h = 0; h < 2; h++) {
                const int row = row0 + h * 8;
                const int which = row == sel0 ? 0 : (row == sel1 ? 1 : -1);
#pragma unroll
                for (int i = 0; i < 4; i++) {
                    const int col = col0 + i * 8;
                    float b0 = bf_lo(nv[2 * i + h]), b1 = bf_hi(nv[2 * i + h]);
                    if (which >= 0) {
                        b0 = bfr(b0 + supd[which * 64 + col - nb * 64]); b1 = bfr(b1 + supd[which * 64 + col + 1 - nb * 64]);
                    }
                    const float t0 = bfr(bf_lo(xv[2 * i + h]) + bfr(acc[4 * i + 2 * h]));
                    const float t1 = bfr(bf_hi(xv[2 * i + h]) + bfr(acc[4 * i + 2 * h + 1]));
                    *reinterpret_cast<uint32_t*>(out + (size_t)row * DM + col) = packbf(t0 + b0, t1 + b1);
                }
            }
        }
        TLX(9, 256);
    }
}

typedef CUresult (*EncodeFn)(CUtensorMap*, CUtensorMapDataType, cuuint32_t, void*, const cuuint64_t*, const cuuint64_t*,
                             const cuuint32_t*, const cuuint32_t*, CUtensorMapInterleave, CUtensorMapSwizzle,
                             CUtensorMapL2promotion, CUtensorMapFloatOOBfill);

void make_map(EncodeFn fn, CUtensorMap* m, const void* ptr, uint64_t cols, uint64_t rows, uint32_t box_rows, uint32_t box_chunks) {
    cuuint64_t dims[3] = {64, rows, cols / 64};
    cuuint64_t strides[2] = {cols * 2, 128};
    cuuint32_t box[3] = {64, box_rows, box_chunks};
    cuuint32_t es[3] = {1, 1, 1};
    fn(m, CU_TENSOR_MAP_DATA_TYPE_BFLOAT16, 3, const_cast<void*>(ptr), dims, strides, box, es, CU_TENSOR_MAP_INTERLEAVE_NONE,
       CU_TENSOR_MAP_SWIZZLE_128B, CU_TENSOR_MAP_L2_PROMOTION_L2_256B, CU_TENSOR_MAP_FLOAT_OOB_FILL_NONE);
}

}

extern "C" void kernel_launch(void* const* d_in, const int* in_sizes, int n_in, void* d_out, int out_size) {
    const __nv_bfloat16* x = (const __nv_bfloat16*)d_in[0];
    const __nv_bfloat16* wqkv = (const __nv_bfloat16*)d_in[1];
    const __nv_bfloat16* wo = (const __nv_bfloat16*)d_in[2];
    const __nv_bfloat16* wr = (const __nv_bfloat16*)d_in[4];
    const __nv_bfloat16* wgate = (const __nv_bfloat16*)d_in[5];
    const __nv_bfloat16* wup = (const __nv_bfloat16*)d_in[6];
    const __nv_bfloat16* wdown = (const __nv_bfloat16*)d_in[7];
    __nv_bfloat16* out = (__nv_bfloat16*)d_out;

    static EncodeFn enc = nullptr;
    static void* p_xn = nullptr; static void* p_o = nullptr;
    if (!enc) {
        void* fn = nullptr; cudaDriverEntryPointQueryResult qr;
        cudaGetDriverEntryPoint("cuTensorMapEncodeTiled", &fn, cudaEnableDefault, &qr);
        enc = (EncodeFn)fn;
        cudaGetSymbolAddress(&p_xn, g_xn);
        cudaGetSymbolAddress(&p_o, g_o);
        cudaFuncSetAttribute(fused_kernel, cudaFuncAttributeMaxDynamicSharedMemorySize, FUSED_SMEM);
    }
    Maps maps;
    make_map(enc, &maps.g, wgate, FF, DM, 16, 7);
    make_map(enc, &maps.u, wup, FF, DM, 16, 7);
    make_map(enc, &maps.d, wdown, DM, FF, 32, 8);
    make_map(enc, &maps.xn, p_xn, DM, S_LEN, 128, 1);
    make_map(enc, &maps.wqkv, wqkv, 3 * DM, DM, 64, 3);
    make_map(enc, &maps.o, p_o, DM, S_LEN, 64, 4);
    make_map(enc, &maps.wo, wo, DM, DM, 256, 1);

    union { uint32_t u; float f; } scu; scu.u = 128u;

    cudaLaunchConfig_t cfg = {};
    cfg.gridDim = dim3(132); cfg.blockDim = dim3(512); cfg.dynamicSmemBytes = FUSED_SMEM; cfg.stream = cudaStreamPerThread;
    cudaLaunchKernelEx(&cfg, fused_kernel, maps, x, wr, out, scu.f);
}
```

```cpp
#include <cuda_runtime.h>
#include <cuda_bf16.h>
#include <cuda.h>
#include <stdint.h>
#include <type_traits>

namespace {

constexpr int S_LEN = 2048;
constexpr int DM = 512;
constexpr int NH = 32;
constexpr int FF = 1792;

__device__ __align__(1024) __nv_bfloat16 g_xn[S_LEN * DM];
__device__ __align__(16) float g_r[S_LEN];
__device__ __align__(1024) uint32_t g_qkv[NH * 8 * 6144];
__device__ __align__(1024) __nv_bfloat16 g_o[S_LEN * DM];
__device__ __align__(16) float g_ypart[4 * 2 * DM];
__device__ int g_sel[2];
__device__ float g_gate[2];
constexpr int C_LN = 0, C_QKV = 16, C_O = 24, C_FFN = 56, C_EXIT = 57, C_NUM = 58;
__device__ unsigned g_cnt[C_NUM * 32];

#define TL(slot) do {} while (0)
#define TLX(slot, th) do {} while (0)

__device__ __forceinline__ uint32_t smem_u32(const void* p) { return (uint32_t)__cvta_generic_to_shared(p); }
__device__ __forceinline__ void warp_arrive(int idx) {
    __syncwarp();
    if ((threadIdx.x & 31) == 0)
        asm volatile("red.release.gpu.global.add.u32 [%0], 1;" :: "l"(g_cnt + idx * 32) : "memory");
}
__device__ __forceinline__ void flag_release(int idx) {
    asm volatile("red.release.gpu.global.add.u32 [%0], 1;" :: "l"(g_cnt + idx * 32) : "memory");
}
__device__ __forceinline__ void exit_ticket() {
    unsigned tk;
    asm volatile("atom.relaxed.gpu.global.add.u32 %0, [%1], 1;" : "=r"(tk) : "l"(g_cnt + C_EXIT * 32) : "memory");
    if (tk == gridDim.x - 1) {
#pragma unroll 1
        for (int i = 0; i < C_NUM; i++) g_cnt[i * 32] = 0u;
    }
}
__device__ __forceinline__ void nbar_arrive(int id, int cnt) { asm volatile("bar.arrive %0, %1;" :: "r"(id), "r"(cnt) : "memory"); }
__device__ __forceinline__ void nbar_sync(int id, int cnt) { asm volatile("bar.sync %0, %1;" :: "r"(id), "r"(cnt) : "memory"); }
__device__ __forceinline__ void flag_wait(int idx, unsigned target) {
    asm volatile("{\n.reg .pred p;\n.reg .u32 n, v;\nmov.u32 n, 0;\n"
                 "FW_%=:\n"
                 "ld.acquire.gpu.global.u32 v, [%0];\n"
                 "setp.ge.u32 p, v, %1;\n"
                 "@p bra FD_%=;\n"
                 "add.u32 n, n, 1;\n"
                 "setp.lt.u32 p, n, 16000000;\n"
                 "@p bra FW_%=;\n"
                 "trap;\n"
                 "FD_%=:\n}"
                 :: "l"(g_cnt + idx * 32), "r"(target) : "memory");
}
__device__ __forceinline__ void flag_wait_all(int idx, unsigned target) {
    asm volatile("{\n.reg .pred p;\n.reg .u32 n, v;\nmov.u32 n, 0;\n"
                 "FW_%=:\n"
                 "ld.acquire.gpu.global.u32 v, [%0];\n"
                 "setp.ge.u32 p, v, %1;\n"
                 "vote.sync.all.pred p, p, 0xffffffff;\n"
                 "@p bra.uni FD_%=;\n"
                 "add.u32 n, n, 1;\n"
                 "setp.lt.u32 p, n, 16000000;\n"
                 "@p bra.uni FW_%=;\n"
                 "trap;\n"
                 "FD_%=:\n}"
                 :: "l"(g_cnt + idx * 32), "r"(target) : "memory");
}
__device__ __forceinline__ void fence_proxy_async_all() { asm volatile("fence.proxy.async.global;" ::: "memory"); }
__device__ __forceinline__ void mbar_init(uint32_t bar, uint32_t cnt) {
    asm volatile("mbarrier.init.shared::cta.b64 [%0], %1;" :: "r"(bar), "r"(cnt) : "memory");
}
__device__ __forceinline__ void mbar_expect_tx(uint32_t bar, uint32_t bytes) {
    asm volatile("mbarrier.arrive.expect_tx.shared::cta.b64 _, [%0], %1;" :: "r"(bar), "r"(bytes) : "memory");
}
__device__ __forceinline__ void mbar_arrive(uint32_t bar) {
    asm volatile("mbarrier.arrive.shared::cta.b64 _, [%0];" :: "r"(bar) : "memory");
}
__device__ __forceinline__ void mbar_wait(uint32_t bar, uint32_t parity) {
    asm volatile("{\n.reg .pred p;\n.reg .u32 n;\nmov.u32 n, 0;\n"
                 "WAIT_%=:\n"
                 "mbarrier.try_wait.parity.shared::cta.b64 p, [%0], %1;\n"
                 "@p bra DONE_%=;\n"
                 "add.u32 n, n, 1;\n"
                 "setp.lt.u32 p, n, 4000000;\n"
                 "@p bra WAIT_%=;\n"
                 "trap;\n"
                 "DONE_%=:\n}"
                 :: "r"(bar), "r"(parity) : "memory");
}
__device__ __forceinline__ void fence_barrier_init() { asm volatile("fence.mbarrier_init.release.cluster;" ::: "memory"); }
__device__ __forceinline__ void fence_proxy_async() { asm volatile("fence.proxy.async.shared::cta;" ::: "memory"); }
__device__ __forceinline__ void tma3d(uint32_t dst, const CUtensorMap* map, uint32_t bar, int row, int chunk) {
    asm volatile("cp.async.bulk.tensor.3d.shared::cluster.global.mbarrier::complete_tx::bytes [%0], [%1, {%3, %4, %5}], [%2];"
                 :: "r"(dst), "l"((uint64_t)map), "r"(bar), "r"(0), "r"(row), "r"(chunk) : "memory");
}
__device__ __forceinline__ void bulk_g2s(uint32_t dst, const void* src, uint32_t bytes, uint32_t bar) {
    asm volatile("cp.async.bulk.shared::cluster.global.mbarrier::complete_tx::bytes [%0], [%1], %2, [%3];"
                 :: "r"(dst), "l"((uint64_t)src), "r"(bytes), "r"(bar) : "memory");
}
__device__ __forceinline__ void l2_prefetch(const void* src, uint32_t bytes) {
    asm volatile("cp.async.bulk.prefetch.L2.global [%0], %1;" :: "l"((uint64_t)src), "r"(bytes) : "memory");
}
__device__ __forceinline__ void map_prefetch(const CUtensorMap* m) {
    asm volatile("prefetch.tensormap [%0];" :: "l"((uint64_t)m) : "memory");
}
__device__ __forceinline__ uint64_t mkdesc(uint32_t addr, uint32_t lbo, uint32_t sbo, uint32_t swz) {
    return (uint64_t)((addr & 0x3FFFF) >> 4) | ((uint64_t)(lbo >> 4) << 16) | ((uint64_t)(sbo >> 4) << 32) | ((uint64_t)swz << 62);
}
#define WG_FENCE() asm volatile("wgmma.fence.sync.aligned;" ::: "memory")
#define WG_COMMIT() asm volatile("wgmma.commit_group.sync.aligned;" ::: "memory")
#define WG_WAIT(n) asm volatile("wgmma.wait_group.sync.aligned %0;" :: "n"(n) : "memory")

__device__ __forceinline__ float ex2(float x) { float y; asm("ex2.approx.ftz.f32 %0, %1;" : "=f"(y) : "f"(x)); return y; }
__device__ __forceinline__ uint32_t packbf(float lo, float hi) {
    uint32_t r; asm("cvt.rn.bf16x2.f32 %0, %1, %2;" : "=r"(r) : "f"(hi), "f"(lo)); return r;
}
__device__ __forceinline__ uint32_t hmul2bf(uint32_t a, uint32_t b) { uint32_t r; asm("mul.rn.bf16x2 %0, %1, %2;" : "=r"(r) : "r"(a), "r"(b)); return r; }
__device__ __forceinline__ float bf_lo(uint32_t v) { return __uint_as_float(v << 16); }
__device__ __forceinline__ float bf_hi(uint32_t v) { return __uint_as_float(v & 0xffff0000u); }
__device__ __forceinline__ float bfr(float x) { return __bfloat162float(__float2bfloat16_rn(x)); }

__device__ __forceinline__ void wgmma_n192(float (&d)[96], uint64_t da, uint64_t db, int scale_d) {
    asm volatile("{\n.reg .pred p;\nsetp.ne.b32 p, %98, 0;\n"
        "wgmma.mma_async.sync.aligned.m64n192k16.f32.bf16.bf16 "
        "{%0,%1,%2,%3,%4,%5,%6,%7,%8,%9,%10,%11,%12,%13,%14,%15,%16,%17,%18,%19,%20,%21,%22,%23,"
        "%24,%25,%26,%27,%28,%29,%30,%31,%32,%33,%34,%35,%36,%37,%38,%39,%40,%41,%42,%43,%44,%45,%46,%47,"
        "%48,%49,%50,%51,%52,%53,%54,%55,%56,%57,%58,%59,%60,%61,%62,%63,%64,%65,%66,%67,%68,%69,%70,%71,"
        "%72,%73,%74,%75,%76,%77,%78,%79,%80,%81,%82,%83,%84,%85,%86,%87,%88,%89,%90,%91,%92,%93,%94,%95}, "
        "%96, %97, p, 1, 1, 0, 1;\n}"
        : "+f"(d[0]), "+f"(d[1]), "+f"(d[2]), "+f"(d[3]), "+f"(d[4]), "+f"(d[5]), "+f"(d[6]), "+f"(d[7]),
          "+f"(d[8]), "+f"(d[9]), "+f"(d[10]), "+f"(d[11]), "+f"(d[12]), "+f"(d[13]), "+f"(d[14]), "+f"(d[15]),
          "+f"(d[16]), "+f"(d[17]), "+f"(d[18]), "+f"(d[19]), "+f"(d[20]), "+f"(d[21]), "+f"(d[22]), "+f"(d[23]),
          "+f"(d[24]), "+f"(d[25]), "+f"(d[26]), "+f"(d[27]), "+f"(d[28]), "+f"(d[29]), "+f"(d[30]), "+f"(d[31]),
          "+f"(d[32]), "+f"(d[33]), "+f"(d[34]), "+f"(d[35]), "+f"(d[36]), "+f"(d[37]), "+f"(d[38]), "+f"(d[39]),
          "+f"(d[40]), "+f"(d[41]), "+f"(d[42]), "+f"(d[43]), "+f"(d[44]), "+f"(d[45]), "+f"(d[46]), "+f"(d[47]),
          "+f"(d[48]), "+f"(d[49]), "+f"(d[50]), "+f"(d[51]), "+f"(d[52]), "+f"(d[53]), "+f"(d[54]), "+f"(d[55]),
          "+f"(d[56]), "+f"(d[57]), "+f"(d[58]), "+f"(d[59]), "+f"(d[60]), "+f"(d[61]), "+f"(d[62]), "+f"(d[63]),
          "+f"(d[64]), "+f"(d[65]), "+f"(d[66]), "+f"(d[67]), "+f"(d[68]), "+f"(d[69]), "+f"(d[70]), "+f"(d[71]),
          "+f"(d[72]), "+f"(d[73]), "+f"(d[74]), "+f"(d[75]), "+f"(d[76]), "+f"(d[77]), "+f"(d[78]), "+f"(d[79]),
          "+f"(d[80]), "+f"(d[81]), "+f"(d[82]), "+f"(d[83]), "+f"(d[84]), "+f"(d[85]), "+f"(d[86]), "+f"(d[87]),
          "+f"(d[88]), "+f"(d[89]), "+f"(d[90]), "+f"(d[91]), "+f"(d[92]), "+f"(d[93]), "+f"(d[94]), "+f"(d[95])
        : "l"(da), "l"(db), "r"(scale_d));
}

constexpr float SHIFT = 90.0f;
constexpr float QS = 0.25f * 1.4426950408889634f * 18446744073709551616.0f;
constexpr float scq = 0.25f * 1.4426950408889634f * 3.3087224502121107e-24f;

__device__ __forceinline__ uint32_t polyexp(float lo, float hi) {
    uint32_t w, g, q, h;
    asm("cvt.pack.sat.s16.s32 %0, %1, %2;" : "=r"(w) : "r"(__float_as_uint(hi)), "r"(__float_as_uint(lo)));
    g = w & 0x007F007Fu;
    asm("fma.rn.f16x2 %0, %1, %2, %3;" : "=r"(q) : "r"(g), "r"(0xf940f940u), "r"(0x35513551u));
    asm("mul.rn.f16x2 %0, %1, %2;" : "=r"(h) : "r"(q), "r"(g));
    return w - h;
}
__device__ __forceinline__ void qk64(float (&s)[32], const uint32_t (&q)[4], uint64_t db) {
    asm volatile("wgmma.mma_async.sync.aligned.m64n64k16.f32.bf16.bf16 "
        "{%0,%1,%2,%3,%4,%5,%6,%7,%8,%9,%10,%11,%12,%13,%14,%15,%16,%17,%18,%19,%20,%21,%22,%23,%24,%25,%26,%27,%28,%29,%30,%31}, "
        "{%32,%33,%34,%35}, %36, 0, 1, 1, 0;"
        : "=f"(s[0]), "=f"(s[1]), "=f"(s[2]), "=f"(s[3]), "=f"(s[4]), "=f"(s[5]), "=f"(s[6]), "=f"(s[7]),
          "=f"(s[8]), "=f"(s[9]), "=f"(s[10]), "=f"(s[11]), "=f"(s[12]), "=f"(s[13]), "=f"(s[14]), "=f"(s[15]),
          "=f"(s[16]), "=f"(s[17]), "=f"(s[18]), "=f"(s[19]), "=f"(s[20]), "=f"(s[21]), "=f"(s[22]), "=f"(s[23]),
          "=f"(s[24]), "=f"(s[25]), "=f"(s[26]), "=f"(s[27]), "=f"(s[28]), "=f"(s[29]), "=f"(s[30]), "=f"(s[31])
        : "r"(q[0]), "r"(q[1]), "r"(q[2]), "r"(q[3]), "l"(db));
}
__device__ __forceinline__ void pv24(float (&o)[12], uint32_t a0, uint32_t a1, uint32_t a2, uint32_t a3, uint64_t db) {
    asm volatile("wgmma.mma_async.sync.aligned.m64n24k16.f32.bf16.bf16 "
        "{%0,%1,%2,%3,%4,%5,%6,%7,%8,%9,%10,%11}, {%12,%13,%14,%15}, %16, 1, 1, 1, 1;"
        : "+f"(o[0]), "+f"(o[1]), "+f"(o[2]), "+f"(o[3]), "+f"(o[4]), "+f"(o[5]), "+f"(o[6]), "+f"(o[7]),
          "+f"(o[8]), "+f"(o[9]), "+f"(o[10]), "+f"(o[11])
        : "r"(a0), "r"(a1), "r"(a2), "r"(a3), "l"(db));
}

__device__ __forceinline__ void attn_safe(float (&o)[12], const uint32_t (&q)[4], uint64_t kdesc0, uint64_t vdesc0) {
    float s[32];
    float m0 = -INFINITY, m1 = -INFINITY;
#pragma unroll
    for (int i = 0; i < 12; i++) o[i] = 0.f;
#pragma unroll 1
    for (int j = 0; j < 32; j++) {
        WG_FENCE();
        qk64(s, q, kdesc0 + (uint64_t)((j >> 2) * (20480 / 16) + (j & 3) * 64));
        WG_COMMIT(); WG_WAIT(0);
        float n0 = m0, n1 = m1;
#pragma unroll
        for (int i = 0; i < 8; i++) { n0 = fmaxf(n0, fmaxf(s[4 * i], s[4 * i + 1])); n1 = fmaxf(n1, fmaxf(s[4 * i + 2], s[4 * i + 3])); }
        n0 = fmaxf(n0, __shfl_xor_sync(~0u, n0, 1)); n0 = fmaxf(n0, __shfl_xor_sync(~0u, n0, 2));
        n1 = fmaxf(n1, __shfl_xor_sync(~0u, n1, 1)); n1 = fmaxf(n1, __shfl_xor_sync(~0u, n1, 2));
        const float c0 = ex2((m0 - n0) * QS), c1 = ex2((m1 - n1) * QS);
        m0 = n0; m1 = n1;
#pragma unroll
        for (int i = 0; i < 3; i++) { o[4 * i] *= c0; o[4 * i + 1] *= c0; o[4 * i + 2] *= c1; o[4 * i + 3] *= c1; }
        uint32_t p[16];
#pragma unroll
        for (int i = 0; i < 8; i++) {
            p[2 * i] = packbf(ex2((s[4 * i] - m0) * QS), ex2((s[4 * i + 1] - m0) * QS));
            p[2 * i + 1] = packbf(ex2((s[4 * i + 2] - m1) * QS), ex2((s[4 * i + 3] - m1) * QS));
        }
        WG_FENCE();
#pragma unroll
        for (int kk = 0; kk < 4; kk++) pv24(o, p[4 * kk], p[4 * kk + 1], p[4 * kk + 2], p[4 * kk + 3], vdesc0 + (uint64_t)((j >> 2) * (20480 / 16) + (j & 3) * 64 + kk * 16));
        WG_COMMIT(); WG_WAIT(0);
    }
}

__device__ __forceinline__ void load_q(uint32_t (&q)[4], int head, int mt, int lane) {
    const uint32_t* src = g_qkv + head * 49152 + (mt >> 4) * 6144 + 4096 + (mt & 15) * 64 + lane;
    q[0] = __ldcg(src); q[1] = __ldcg(src + 32); q[2] = __ldcg(src + 1024); q[3] = __ldcg(src + 1024 + 32);
}
__device__ __forceinline__ void attn_store(const float (&o)[12], int head, int m64, int warp, int lane) {
    const int g = lane >> 2, t = lane & 3;
    const int row = m64 * 64 + warp * 16 + g;
    const float i0 = 1.f / o[8], i1 = 1.f / o[10];
    uint32_t* p0 = reinterpret_cast<uint32_t*>(g_o + (size_t)row * DM + head * 16 + t * 2);
    uint32_t* p1 = reinterpret_cast<uint32_t*>(g_o + (size_t)(row + 8) * DM + head * 16 + t * 2);
    p0[0] = packbf(o[0] * i0, o[1] * i0); p0[4] = packbf(o[4] * i0, o[5] * i0);
    p1[0] = packbf(o[2] * i1, o[3] * i1); p1[4] = packbf(o[6] * i1, o[7] * i1);
}

constexpr int FS_N = 4;
constexpr int FS_BYTES = 32768;
__device__ __forceinline__ void ldsm4t(uint32_t& r0, uint32_t& r1, uint32_t& r2, uint32_t& r3, uint32_t addr) {
    asm volatile("ldmatrix.sync.aligned.m8n8.x4.trans.shared.b16 {%0,%1,%2,%3}, [%4];" : "=r"(r0), "=r"(r1), "=r"(r2), "=r"(r3) : "r"(addr) : "memory");
}
__device__ __forceinline__ void mma16816(float (&d)[4], uint32_t a0, uint32_t a2, uint32_t b0, uint32_t b1) {
    asm volatile("mma.sync.aligned.m16n8k16.row.col.f32.bf16.bf16.f32 {%0,%1,%2,%3}, {%4,%5,%6,%5}, {%7,%8}, {%0,%1,%2,%3};"
                 : "+f"(d[0]), "+f"(d[1]), "+f"(d[2]), "+f"(d[3]) : "r"(a0), "r"(0u), "r"(a2), "r"(b0), "r"(b1));
}
__device__ void ffn_block(int c, uint8_t* smem, uint32_t sbase, const CUtensorMap* mapG, const CUtensorMap* mapU, const CUtensorMap* mapD) {
    const int tid = threadIdx.x, warp = tid >> 5, lane = tid & 31;
    uint32_t* sx = reinterpret_cast<uint32_t*>(smem + FS_N * FS_BYTES);
    __nv_bfloat16* sh = reinterpret_cast<__nv_bfloat16*>(sx + 512);
    const uint32_t bars = sbase + FS_N * FS_BYTES + 8192;
    float* tv = reinterpret_cast<float*>(smem + FS_N * FS_BYTES + 4096);
    int* ti = reinterpret_cast<int*>(tv + 32);
    int* ssel = ti + 32;
    auto issue = [&](int item) {
        const int slot = item % FS_N;
        const uint32_t dst = sbase + slot * FS_BYTES, bar = bars + 8 * slot;
        mbar_expect_tx(bar, item < 32 ? 28672 : 32768);
        if (item < 32) {
            tma3d(dst, mapG, bar, item * 16, c * 7);
            tma3d(dst + 14336, mapU, bar, item * 16, c * 7);
        } else {
            tma3d(dst, mapD, bar, c * 448 + (item - 32) * 32, 0);
        }
    };
    if (tid == 0) {
        for (int i = 0; i < FS_N; i++) mbar_init(bars + 8 * i, 1);
        fence_barrier_init();
        for (int i = 0; i < FS_N; i++) issue(i);
    }
    flag_wait(C_LN + warp, 8);
    __syncthreads();
    float b1 = -INFINITY, b2 = -INFINITY; int i1 = 0x7fffffff, i2 = 0x7fffffff;
    auto push = [&](float v, int i) {
        if (v > b1 || (v == b1 && i < i1)) { b2 = b1; i2 = i1; b1 = v; i1 = i; }
        else if (v > b2 || (v == b2 && i < i2)) { b2 = v; i2 = i; }
    };
    {
        const float4 rv = __ldcg(reinterpret_cast<const float4*>(g_r) + tid);
        push(rv.x, 4 * tid); push(rv.y, 4 * tid + 1); push(rv.z, 4 * tid + 2); push(rv.w, 4 * tid + 3);
    }
#pragma unroll
    for (int o = 16; o > 0; o >>= 1) {
        float v1 = __shfl_xor_sync(~0u, b1, o), v2 = __shfl_xor_sync(~0u, b2, o);
        int j1 = __shfl_xor_sync(~0u, i1, o), j2 = __shfl_xor_sync(~0u, i2, o);
        push(v1, j1); push(v2, j2);
    }
    if (lane == 0) { tv[2 * warp] = b1; ti[2 * warp] = i1; tv[2 * warp + 1] = b2; ti[2 * warp + 1] = i2; }
    __syncthreads();
    if (warp == 1) {
        b1 = tv[lane]; i1 = ti[lane]; b2 = -INFINITY; i2 = 0x7fffffff;
#pragma unroll
        for (int o = 16; o > 0; o >>= 1) {
            float v1 = __shfl_xor_sync(~0u, b1, o), v2 = __shfl_xor_sync(~0u, b2, o);
            int j1 = __shfl_xor_sync(~0u, i1, o), j2 = __shfl_xor_sync(~0u, i2, o);
            push(v1, j1); push(v2, j2);
        }
        if (lane == 0) {
            i1 = min(max(i1, 0), S_LEN - 1); i2 = min(max(i2, 0), S_LEN - 1);
            ssel[0] = i1; ssel[1] = i2;
            if (c == 0) {
                g_sel[0] = i1; g_sel[1] = i2;
                g_gate[0] = bfr(1.f / (1.f + __expf(-bfr(b1))));
                g_gate[1] = bfr(1.f / (1.f + __expf(-bfr(b2))));
            }
        }
    }
    __syncthreads();
    sx[tid] = __ldcg(reinterpret_cast<const uint32_t*>(g_xn + (size_t)ssel[tid >> 8] * DM + (tid & 255) * 2));
    __syncthreads();
    TL(1);
    const int g = lane >> 2, t = lane & 3;
    const int lrow = lane & 15, lsel = lane >> 4;
    {
        float ag[4][4], au[4][4];
#pragma unroll
        for (int j = 0; j < 4; j++) { ag[j][0] = ag[j][1] = ag[j][2] = ag[j][3] = 0.f; au[j][0] = au[j][1] = au[j][2] = au[j][3] = 0.f; }
#pragma unroll 1
        for (int it = 0; it < 32; it++) {
            const int slot = it % FS_N;
            const uint32_t a0 = g < 2 ? sx[g * 256 + it * 8 + t] : 0u, a2 = g < 2 ? sx[g * 256 + it * 8 + 4 + t] : 0u;
            mbar_wait(bars + 8 * slot, (it / FS_N) & 1);
            const uint32_t base = sbase + slot * FS_BYTES + lsel * 14336 + lrow * 128;
#pragma unroll
            for (int j = 0; j < 4; j++) {
                const int nt = warp + j * 16;
                if (nt < 56) {
                    uint32_t b0, b1, b2, b3;
                    ldsm4t(b0, b1, b2, b3, base + (nt >> 3) * 2048 + (((nt & 7) ^ (lrow & 7)) << 4));
                    mma16816(ag[j], a0, a2, b0, b1);
                    mma16816(au[j], a0, a2, b2, b3);
                }
            }
            __syncthreads();
            if (tid == 480) issue(it + FS_N);
        }
        if (g < 2) {
#pragma unroll
            for (int j = 0; j < 4; j++) {
                const int nt = warp + j * 16;
                if (nt < 56) {
#pragma unroll
                    for (int e = 0; e < 2; e++) {
                        const float gs = bfr(ag[j][e]), us = bfr(au[j][e]);
                        const float sg = bfr(gs / (1.f + __expf(-gs)));
                        sh[g * 448 + nt * 8 + t * 2 + e] = __float2bfloat16_rn(sg * us);
                    }
                }
            }
        }
        __syncthreads();
    }
    TL(2);
    {
        const uint32_t* shw = reinterpret_cast<const uint32_t*>(sh);
        float a[4][4];
#pragma unroll
        for (int j = 0; j < 4; j++) a[j][0] = a[j][1] = a[j][2] = a[j][3] = 0.f;
#pragma unroll 1
        for (int it = 32; it < 46; it++) {
            const int slot = it % FS_N;
            uint32_t af[4];
#pragma unroll
            for (int q = 0; q < 4; q++) af[q] = g < 2 ? shw[g * 224 + (it - 32) * 16 + q * 4 + t] : 0u;
            mbar_wait(bars + 8 * slot, (it / FS_N) & 1);
            const uint32_t base = sbase + slot * FS_BYTES + (warp >> 1) * 4096 + lane * 128;
#pragma unroll
            for (int j = 0; j < 4; j++) {
                const int u = (warp & 1) * 4 + j;
                uint32_t b0, b1, b2, b3;
                ldsm4t(b0, b1, b2, b3, base + ((u ^ (lane & 7)) << 4));
                mma16816(a[j], af[0], af[1], b0, b1);
                mma16816(a[j], af[2], af[3], b2, b3);
            }
            __syncthreads();
            if (tid == 480 && it + FS_N < 46) issue(it + FS_N);
        }
        if (g < 2) {
#pragma unroll
            for (int j = 0; j < 4; j++)
                *reinterpret_cast<float2*>(&g_ypart[c * 1024 + g * 512 + (warp * 4 + j) * 8 + t * 2]) = make_float2(a[j][0], a[j][1]);
        }
    }
    warp_arrive(C_FFN);
}

__device__ __forceinline__ void wgmma_n32(float (&d)[16], uint64_t da, uint64_t db, int scale_d) {
    asm volatile("{\n.reg .pred p;\nsetp.ne.b32 p, %18, 0;\n"
        "wgmma.mma_async.sync.aligned.m64n32k16.f32.bf16.bf16 "
        "{%0,%1,%2,%3,%4,%5,%6,%7,%8,%9,%10,%11,%12,%13,%14,%15}, "
        "%16, %17, p, 1, 1, 0, 1;\n}"
        : "+f"(d[0]), "+f"(d[1]), "+f"(d[2]), "+f"(d[3]), "+f"(d[4]), "+f"(d[5]), "+f"(d[6]), "+f"(d[7]),
          "+f"(d[8]), "+f"(d[9]), "+f"(d[10]), "+f"(d[11]), "+f"(d[12]), "+f"(d[13]), "+f"(d[14]), "+f"(d[15])
        : "l"(da), "l"(db), "r"(scale_d));
}

constexpr int G_ST = 4;
constexpr int G_STAGE = 16384 + 24576;
constexpr int SM_KV = 0, KV_CH = 20480, SM_WO = 163840, SM_MISC = 229376;
constexpr int FUSED_SMEM = SM_MISC + 2048;
constexpr int B_FULL = 0, B_EMPTY = 4, B_KV = 8, B_WO = 16, B_OA = 18, B_NUM = 22;

struct Maps { CUtensorMap xn, wqkv, o, wo, g, u, d; };

__global__ void __launch_bounds__(512, 1) fused_kernel(const __grid_constant__ Maps maps, const __nv_bfloat16* __restrict__ x,
                                                       const __nv_bfloat16* __restrict__ wr, __nv_bfloat16* __restrict__ out, float sc) {
    extern __shared__ __align__(1024) uint8_t smem[];
    const uint32_t sbase = smem_u32(smem);
    const int tid = threadIdx.x, warp = __shfl_sync(~0u, tid >> 5, 0), lane = tid & 31;
    const uint32_t bars = sbase + SM_MISC;
    TL(0);
    if (sbase & 1023u) __trap();
    if (blockIdx.x < 4) {
        ffn_block(blockIdx.x, smem, sbase, &maps.g, &maps.u, &maps.d);
        __syncthreads();
        if (tid == 0) exit_ticket();
        TL(3);
    } else {
        const int idx = blockIdx.x - 4;
        const int wg = warp >> 2;
        {
            const int row = idx * 16 + warp;
            const uint4* xr = reinterpret_cast<const uint4*>(x + (size_t)row * DM);
            const uint4 a = xr[lane], b = xr[32 + lane];
            const uint4* wp = reinterpret_cast<const uint4*>(wr);
            const uint4 wa = wp[lane], wb = wp[32 + lane];
            if (tid == 480) {
                for (int s = 0; s < G_ST; s++) { mbar_init(bars + 8 * (B_FULL + s), 2); mbar_init(bars + 8 * (B_EMPTY + s), 2); }
                for (int c = B_KV; c < B_NUM; c++) mbar_init(bars + 8 * c, 1);
                fence_barrier_init();
                for (int c = 0; c < G_ST; c++) {
                    mbar_expect_tx(bars + 8 * (B_FULL + c), 24576);
                    tma3d(sbase + c * G_STAGE + 16384, &maps.wqkv, bars + 8 * (B_FULL + c), c * 64, (idx & 7) * 3);
                }
                map_prefetch(&maps.xn);
            }
            __syncwarp();
            const uint32_t u[8] = {a.x, a.y, a.z, a.w, b.x, b.y, b.z, b.w};
            const uint32_t w[8] = {wa.x, wa.y, wa.z, wa.w, wb.x, wb.y, wb.z, wb.w};
            float f[16];
            float sum = 0.f;
#pragma unroll
            for (int i = 0; i < 8; i++) { f[2 * i] = bf_lo(u[i]); f[2 * i + 1] = bf_hi(u[i]); sum += f[2 * i] + f[2 * i + 1]; }
#pragma unroll
            for (int o = 16; o > 0; o >>= 1) sum += __shfl_xor_sync(~0u, sum, o);
            const float mean = sum * (1.f / DM);
            float sq = 0.f;
#pragma unroll
            for (int i = 0; i < 16; i++) { const float d = f[i] - mean; sq = fmaf(d, d, sq); }
#pragma unroll
            for (int o = 16; o > 0; o >>= 1) sq += __shfl_xor_sync(~0u, sq, o);
            const float mb_ = bfr(mean);
            const float vb = bfr(sq * (1.f / DM));
            const float rinv = 1.f / bfr(sqrtf(bfr(vb + 1e-5f)));
            uint32_t o[8];
            float r = 0.f;
#pragma unroll
            for (int i = 0; i < 8; i++) {
                const float d0 = bfr(f[2 * i] - mb_), d1 = bfr(f[2 * i + 1] - mb_);
                o[i] = packbf(d0 * rinv, d1 * rinv);
                r = fmaf(bf_lo(o[i]), bf_lo(w[i]), r);
                r = fmaf(bf_hi(o[i]), bf_hi(w[i]), r);
            }
            uint4* xo = reinterpret_cast<uint4*>(g_xn + (size_t)row * DM);
            xo[lane] = make_uint4(o[0], o[1], o[2], o[3]);
            xo[32 + lane] = make_uint4(o[4], o[5], o[6], o[7]);
#pragma unroll
            for (int of = 16; of > 0; of >>= 1) r += __shfl_xor_sync(~0u, r, of);
            if (lane == 0) g_r[row] = r;
        }
        __syncthreads();
        if (tid == 416) flag_release(C_LN + (idx >> 3));
        if (tid == 352) {
            mbar_expect_tx(bars + 8 * B_WO, 65536);
            tma3d(sbase + SM_WO, &maps.wo, bars + 8 * B_WO, 0, idx & 7);
            tma3d(sbase + SM_WO + 32768, &maps.wo, bars + 8 * B_WO, 256, idx & 7);
            map_prefetch(&maps.o);
        }
        TL(1);
        {
            const int nb = idx & 7, mb = idx >> 3;
            if (warp == 15) {
                for (int c = G_ST; c < 8; c++) {
                    const int s = c - G_ST;
                    mbar_wait(bars + 8 * (B_EMPTY + s), 0);
                    if (lane == 0) {
                        mbar_expect_tx(bars + 8 * (B_FULL + s), 24576);
                        tma3d(sbase + s * G_STAGE + 16384, &maps.wqkv, bars + 8 * (B_FULL + s), c * 64, nb * 3);
                    }
                    __syncwarp();
                }
            } else if (warp == 14) {
                flag_wait(C_LN + mb, 8);
                fence_proxy_async_all();
                for (int c = 0; c < 8; c++) {
                    const int s = c & (G_ST - 1);
                    if (c >= G_ST) mbar_wait(bars + 8 * (B_EMPTY + s), 0);
                    if (lane == 0) {
                        mbar_expect_tx(bars + 8 * (B_FULL + s), 16384);
                        tma3d(sbase + s * G_STAGE, &maps.xn, bars + 8 * (B_FULL + s), mb * 128, c);
                    }
                    __syncwarp();
                }
            } else if (wg < 2) {
                float acc[96];
#pragma unroll
                for (int i = 0; i < 96; i++) acc[i] = 0.f;
#pragma unroll 1
                for (int c = 0; c < 8; c++) {
                    const int s = c & (G_ST - 1);
                    const uint32_t st = sbase + s * G_STAGE;
                    mbar_wait(bars + 8 * (B_FULL + s), c >> 2);
                    if (c == 0) TL(2);
                    const uint64_t da = mkdesc(st + wg * 8192, 16, 1024, 1);
                    const uint64_t db = mkdesc(st + 16384, 8192, 1024, 1);
                    WG_FENCE();
#pragma unroll
                    for (int k = 0; k < 4; k++) wgmma_n192(acc, da + k * 2, db + k * 128, (c | k) != 0);
                    WG_COMMIT();
                    if (c <= G_ST) {
                        WG_WAIT(1);
                        if (c >= 1 && (tid & 127) == 0) mbar_arrive(bars + 8 * (B_EMPTY + c - 1));
                    }
                }
                WG_WAIT(0);
                nbar_arrive(6, 512);
                TL(3);
                const int mt = mb * 8 + warp;
                uint32_t* dst0 = g_qkv + (mt >> 4) * 6144 + (mt & 15) * 64 + lane;
#pragma unroll
                for (int hh = 0; hh < 12; hh++) {
                    const int gh = nb * 12 + hh, ty = gh >> 5;
                    const float* a = &acc[hh * 8];
                    uint32_t* dst = dst0 + (gh & 31) * 49152 + ((ty + 2) % 3) * 2048;
                    const uint32_t ks = ty == 1 ? 0x1f801f80u : 0x3f803f80u;
                    dst[0] = hmul2bf(packbf(a[0], a[1]), ks);
                    dst[32] = hmul2bf(packbf(a[2], a[3]), ks);
                    dst[1024] = hmul2bf(packbf(a[4], a[5]), ks);
                    dst[1024 + 32] = hmul2bf(packbf(a[6], a[7]), ks);
                }
                TL(10);
                nbar_sync(8, 256);
                if (tid == 0) flag_release(C_QKV + nb);
            }
        }
        TL(4);
        uint32_t badmask = 0;
        const int head = idx >> 2, quarter = idx & 3, w4 = warp & 3;
        {
            if (warp == 15) {
                flag_wait_all(C_QKV + ((lane % 3) * 32 + head) / 12, 16);
                nbar_sync(6, 512);
                fence_proxy_async_all();
                if (lane == 0) {
                    const uint8_t* kvp = reinterpret_cast<const uint8_t*>(g_qkv + head * 49152);
#pragma unroll 1
                    for (int c = 0; c < 2; c++) {
                        mbar_expect_tx(bars + 8 * (B_KV + c), 16384);
                        bulk_g2s(sbase + SM_KV + c * KV_CH, kvp + c * 24576, 16384, bars + 8 * (B_KV + c));
                    }
                }
                __syncwarp();
            } else if (wg >= 2) {
                nbar_sync(6, 512);
#pragma unroll 1
                for (int i = tid - 256; i < 2048; i += 224)
                    *reinterpret_cast<uint4*>(smem + SM_KV + (i >> 8) * KV_CH + 16384 + (i & 255) * 16) = make_uint4(0x3f803f80u, 0x3f803f80u, 0x3f803f80u, 0x3f803f80u);
                fence_proxy_async();
            }
            __syncthreads();
            if (tid == 480) {
                const uint8_t* kvp = reinterpret_cast<const uint8_t*>(g_qkv + head * 49152);
#pragma unroll 1
                for (int c = 2; c < 8; c++) {
                    mbar_expect_tx(bars + 8 * (B_KV + c), 16384);
                    bulk_g2s(sbase + SM_KV + c * KV_CH, kvp + c * 24576, 16384, bars + 8 * (B_KV + c));
                }
            }
            __syncwarp();
            const uint64_t kdesc0 = mkdesc(sbase + SM_KV, 4096, 128, 0);
            const uint64_t vdesc0 = mkdesc(sbase + SM_KV + 8192, 128, 4096, 0);
#pragma unroll 1
            for (int mt = 0; mt < 2; mt++) {
                const int m64 = quarter * 8 + mt * 4 + wg;
                uint32_t q[4];
                load_q(q, head, m64 * 4 + w4, lane);
                float s[32], s2[32], o[12];
#pragma unroll
                for (int i = 0; i < 12; i++) o[i] = 0.f;
                mbar_wait(bars + 8 * B_KV, 0);
                if (mt == 0) TL(5);
                WG_FENCE();
                qk64(s, q, kdesc0);
                WG_COMMIT(); WG_WAIT(0);
                float mx0 = -INFINITY, mx1 = -INFINITY;
#pragma unroll
                for (int i = 0; i < 8; i++) { mx0 = fmaxf(mx0, fmaxf(s[4 * i], s[4 * i + 1])); mx1 = fmaxf(mx1, fmaxf(s[4 * i + 2], s[4 * i + 3])); }
                mx0 = fmaxf(mx0, __shfl_xor_sync(~0u, mx0, 1)); mx0 = fmaxf(mx0, __shfl_xor_sync(~0u, mx0, 2));
                mx1 = fmaxf(mx1, __shfl_xor_sync(~0u, mx1, 1)); mx1 = fmaxf(mx1, __shfl_xor_sync(~0u, mx1, 2));
                float cm0 = -(ceilf(mx0 * QS) + SHIFT), cm1 = -(ceilf(mx1 * QS) + SHIFT);
                float cp0 = (cm0 + 127.f) * sc, cp1 = (cm1 + 127.f) * sc;
                asm volatile("" : "+f"(cm0), "+f"(cm1), "+f"(cp0), "+f"(cp1));
                uint64_t kd = kdesc0, vd = vdesc0;
                auto step = [&](float (&sc_)[32], float (&sn)[32], uint64_t kinc, uint64_t vinc) {
                    kd += kinc;
                    WG_FENCE();
                    qk64(sn, q, kd);
                    WG_COMMIT();
#pragma unroll
                    for (int kk = 0; kk < 4; kk++) {
                        const int i0 = kk * 2, i1 = kk * 2 + 1;
                        const uint32_t p0 = packbf(ex2(fmaf(sc_[4 * i0], QS, cm0)), ex2(fmaf(sc_[4 * i0 + 1], QS, cm0)));
                        const uint32_t p1 = packbf(ex2(fmaf(sc_[4 * i0 + 2], QS, cm1)), ex2(fmaf(sc_[4 * i0 + 3], QS, cm1)));
                        const uint32_t p2 = polyexp(fmaf(sc_[4 * i1], scq, cp0), fmaf(sc_[4 * i1 + 1], scq, cp0));
                        const uint32_t p3 = polyexp(fmaf(sc_[4 * i1 + 2], scq, cp1), fmaf(sc_[4 * i1 + 3], scq, cp1));
                        WG_FENCE();
                        pv24(o, p0, p1, p2, p3, vd + kk * 16);
                    }
                    vd += vinc;
                    WG_COMMIT();
                    WG_WAIT(1);
                };
                uint64_t hop = 64u;
#pragma unroll 1
                for (int c = 0; c < 16; c++) {
                    if (mt == 0) {
                        if ((c & 1) == 0 && c < 14) mbar_wait(bars + 8 * B_KV + 4 * c + 8, 0);
                    } else if (c == 2 && !badmask) {
                        nbar_sync(wg + 1, 128);
                        if ((tid & 127) == 0) flag_release(C_O + m64 - 4);
                    }
                    step(s, s2, 64u, 64u);
                    step(s2, s, hop, hop);
                    hop ^= (KV_CH - 4096) / 16;
                }
                WG_WAIT(0);
                bool bad = !(o[8] > 0.f) || !(o[10] > 0.f);
#pragma unroll
                for (int i = 0; i < 12; i++) bad = bad || !(fabsf(o[i]) <= 3.0e38f);
                uint32_t anybad;
                asm volatile("{\n.reg .pred p, q;\nsetp.ne.u32 p, %1, 0;\nbarrier.cta.red.or.pred q, %2, 128, p;\nselp.u32 %0, 1, 0, q;\n}"
                             : "=r"(anybad) : "r"((uint32_t)bad), "r"(wg + 1) : "memory");
                badmask |= __shfl_sync(~0u, anybad, 0) << mt;
                attn_store(o, head, m64, w4, lane);
            }
        }
        if (badmask) {
#pragma unroll 1
            for (int mt = 0; mt < 2; mt++) {
                if (!((badmask >> mt) & 1)) continue;
                const int m64 = quarter * 8 + mt * 4 + wg;
                uint32_t q[4];
                load_q(q, head, m64 * 4 + w4, lane);
                float o[12];
                attn_safe(o, q, mkdesc(sbase + SM_KV, 4096, 128, 0), mkdesc(sbase + SM_KV + 8192, 128, 4096, 0));
                attn_store(o, head, m64, w4, lane);
            }
        }
        nbar_sync(wg + 1, 128);
        if ((tid & 127) == 32) {
            asm volatile("fence.acq_rel.gpu;" ::: "memory");
            asm volatile("red.relaxed.gpu.global.add.u32 [%0], 1;" :: "l"(g_cnt + (C_O + quarter * 8 + 4 + wg) * 32) : "memory");
            if (badmask & 1) asm volatile("red.relaxed.gpu.global.add.u32 [%0], 1;" :: "l"(g_cnt + (C_O + quarter * 8 + wg) * 32) : "memory");
        }
        TLX(14, 416);
        TLX(15, 384);
        TL(6);
        {
            const int nb = idx & 7, jb = idx >> 3;
            const int mbe = (jb >> 2) * 8 + (jb & 3);
            float* supd = reinterpret_cast<float*>(smem + SM_MISC + 512);
            if (warp == 15) nbar_sync(7, 512); else nbar_arrive(7, 512);
            TLX(11, 480);
            if (warp == 15) {
                flag_wait_all((lane & 1) ? C_FFN : C_O + mbe, (lane & 1) ? 64 : 32);
                nbar_arrive(9, 160);
                fence_proxy_async_all();
                if (lane == 0) {
                    for (int c = 0; c < 2; c++) {
                        mbar_expect_tx(bars + 8 * (B_OA + c), 32768);
                        tma3d(sbase + SM_KV + c * 32768, &maps.o, bars + 8 * (B_OA + c), mbe * 64, c * 4);
                    }
                }
                __syncwarp();
                TLX(12, 480);
                flag_wait(C_O + mbe + 4, 32);
                TLX(13, 480);
                fence_proxy_async_all();
                if (lane == 0) {
                    for (int c = 0; c < 2; c++) {
                        mbar_expect_tx(bars + 8 * (B_OA + 2 + c), 32768);
                        tma3d(sbase + SM_KV + 65536 + c * 32768, &maps.o, bars + 8 * (B_OA + 2 + c), (mbe + 4) * 64, c * 4);
                    }
                    exit_ticket();
                }
                __syncwarp();
            }
            const int late = wg >> 1, nh = wg & 1;
            const int mb = mbe + late * 4;
            const int g = lane >> 2, t = lane & 3;
            const int row0 = mb * 64 + w4 * 16 + g;
            const int col0 = nb * 64 + nh * 32 + t * 2;
            uint32_t xv[8], nv[8];
#pragma unroll
            for (int i = 0; i < 4; i++) {
                xv[2 * i] = *reinterpret_cast<const uint32_t*>(x + (size_t)row0 * DM + col0 + i * 8);
                xv[2 * i + 1] = *reinterpret_cast<const uint32_t*>(x + (size_t)(row0 + 8) * DM + col0 + i * 8);
                nv[2 * i] = __ldcg(reinterpret_cast<const uint32_t*>(g_xn + (size_t)row0 * DM + col0 + i * 8));
                nv[2 * i + 1] = __ldcg(reinterpret_cast<const uint32_t*>(g_xn + (size_t)(row0 + 8) * DM + col0 + i * 8));
            }
            if (wg == 0) {
                nbar_sync(9, 160);
                const int which = tid >> 6, col = nb * 64 + (tid & 63);
                const float y = __ldcg(&g_ypart[which * 512 + col]) + __ldcg(&g_ypart[1024 + which * 512 + col]) +
                                __ldcg(&g_ypart[2048 + which * 512 + col]) + __ldcg(&g_ypart[3072 + which * 512 + col]);
                supd[tid] = bfr(bfr(y) * __ldcg(&g_gate[which]));
                if (tid < 2) reinterpret_cast<int*>(supd + 128)[tid] = __ldcg(&g_sel[tid]);
            }
            float acc[16];
#pragma unroll
            for (int i = 0; i < 16; i++) acc[i] = 0.f;
            mbar_wait(bars + 8 * B_WO, 0);
            const uint32_t abase = sbase + SM_KV + late * 65536;
#pragma unroll 1
            for (int c = 0; c < 8; c++) {
                if ((c & 3) == 0) mbar_wait(bars + 8 * (B_OA + late * 2 + (c >> 2)), 0);
                if (c == 0) TLX(7, 256);
                const uint64_t da = mkdesc(abase + c * 8192, 16, 1024, 1);
                const uint64_t db = mkdesc(sbase + SM_WO + c * 8192 + nh * 64, 8192, 1024, 1);
                WG_FENCE();
#pragma unroll
                for (int k = 0; k < 4; k++) wgmma_n32(acc, da + k * 2, db + k * 128, (c | k) != 0);
                WG_COMMIT();
            }
            __syncthreads();
            const int sel0 = reinterpret_cast<const int*>(supd + 128)[0], sel1 = reinterpret_cast<const int*>(supd + 128)[1];
            WG_WAIT(0);
            TLX(8, 256);
#pragma unroll
            for (int h = 0; h < 2; h++) {
                const int row = row0 + h * 8;
                const int which = row == sel0 ? 0 : (row == sel1 ? 1 : -1);
#pragma unroll
                for (int i = 0; i < 4; i++) {
                    const int col = col0 + i * 8;
                    float b0 = bf_lo(nv[2 * i + h]), b1 = bf_hi(nv[2 * i + h]);
                    if (which >= 0) {
                        b0 = bfr(b0 + supd[which * 64 + col - nb * 64]); b1 = bfr(b1 + supd[which * 64 + col + 1 - nb * 64]);
                    }
                    const float t0 = bfr(bf_lo(xv[2 * i + h]) + bfr(acc[4 * i + 2 * h]));
                    const float t1 = bfr(bf_hi(xv[2 * i + h]) + bfr(acc[4 * i + 2 * h + 1]));
                    *reinterpret_cast<uint32_t*>(out + (size_t)row * DM + col) = packbf(t0 + b0, t1 + b1);
                }
            }
        }
        TLX(9, 256);
    }
}

typedef CUresult (*EncodeFn)(CUtensorMap*, CUtensorMapDataType, cuuint32_t, void*, const cuuint64_t*, const cuuint64_t*,
                             const cuuint32_t*, const cuuint32_t*, CUtensorMapInterleave, CUtensorMapSwizzle,
                             CUtensorMapL2promotion, CUtensorMapFloatOOBfill);

void make_map(EncodeFn fn, CUtensorMap* m, const void* ptr, uint64_t cols, uint64_t rows, uint32_t box_rows, uint32_t box_chunks) {
    cuuint64_t dims[3] = {64, rows, cols / 64};
    cuuint64_t strides[2] = {cols * 2, 128};
    cuuint32_t box[3] = {64, box_rows, box_chunks};
    cuuint32_t es[3] = {1, 1, 1};
    fn(m, CU_TENSOR_MAP_DATA_TYPE_BFLOAT16, 3, const_cast<void*>(ptr), dims, strides, box, es, CU_TENSOR_MAP_INTERLEAVE_NONE,
       CU_TENSOR_MAP_SWIZZLE_128B, CU_TENSOR_MAP_L2_PROMOTION_L2_256B, CU_TENSOR_MAP_FLOAT_OOB_FILL_NONE);
}

}

extern "C" void kernel_launch(void* const* d_in, const int* in_sizes, int n_in, void* d_out, int out_size) {
    const __nv_bfloat16* x = (const __nv_bfloat16*)d_in[0];
    const __nv_bfloat16* wqkv = (const __nv_bfloat16*)d_in[1];
    const __nv_bfloat16* wo = (const __nv_bfloat16*)d_in[2];
    const __nv_bfloat16* wr = (const __nv_bfloat16*)d_in[4];
    const __nv_bfloat16* wgate = (const __nv_bfloat16*)d_in[5];
    const __nv_bfloat16* wup = (const __nv_bfloat16*)d_in[6];
    const __nv_bfloat16* wdown = (const __nv_bfloat16*)d_in[7];
    __nv_bfloat16* out = (__nv_bfloat16*)d_out;

    static EncodeFn enc = nullptr;
    static void* p_xn = nullptr; static void* p_o = nullptr;
    if (!enc) {
        void* fn = nullptr; cudaDriverEntryPointQueryResult qr;
        cudaGetDriverEntryPoint("cuTensorMapEncodeTiled", &fn, cudaEnableDefault, &qr);
        enc = (EncodeFn)fn;
        cudaGetSymbolAddress(&p_xn, g_xn);
        cudaGetSymbolAddress(&p_o, g_o);
        cudaFuncSetAttribute(fused_kernel, cudaFuncAttributeMaxDynamicSharedMemorySize, FUSED_SMEM);
    }
    Maps maps;
    make_map(enc, &maps.g, wgate, FF, DM, 16, 7);
    make_map(enc, &maps.u, wup, FF, DM, 16, 7);
    make_map(enc, &maps.d, wdown, DM, FF, 32, 8);
    make_map(enc, &maps.xn, p_xn, DM, S_LEN, 128, 1);
    make_map(enc, &maps.wqkv, wqkv, 3 * DM, DM, 64, 3);
    make_map(enc, &maps.o, p_o, DM, S_LEN, 64, 4);
    make_map(enc, &maps.wo, wo, DM, DM, 256, 1);

    union { uint32_t u; float f; } scu; scu.u = 128u;

    cudaLaunchConfig_t cfg = {};
    cfg.gridDim = dim3(132); cfg.blockDim = dim3(512); cfg.dynamicSmemBytes = FUSED_SMEM; cfg.stream = cudaStreamPerThread;
    cudaLaunchKernelEx(&cfg, fused_kernel, maps, x, wr, out, scu.f);
}
```

```cpp
#include <cuda_runtime.h>
#include <cuda_bf16.h>
#include <cuda.h>
#include <stdint.h>
#include <type_traits>

namespace {

constexpr int S_LEN = 2048;
constexpr int DM = 512;
constexpr int NH = 32;
constexpr int FF = 1792;

__device__ __align__(1024) __nv_bfloat16 g_xn[S_LEN * DM];
__device__ __align__(16) float g_r[S_LEN];
__device__ __align__(1024) uint32_t g_qkv[NH * 8 * 6144];
__device__ __align__(1024) __nv_bfloat16 g_o[S_LEN * DM];
__device__ __align__(16) float g_ypart[4 * 2 * DM];
__device__ int g_sel[2];
__device__ float g_gate[2];
constexpr int C_LN = 0, C_QKV = 16, C_O = 24, C_FFN = 56, C_EXIT = 57, C_NUM = 58;
__device__ unsigned g_cnt[C_NUM * 32];

#define TLC(slot) do {} while (0)
#define TL(slot) do {} while (0)
#define TLX(slot, th) do {} while (0)

__device__ __forceinline__ uint32_t smem_u32(const void* p) { return (uint32_t)__cvta_generic_to_shared(p); }
__device__ __forceinline__ void warp_arrive(int idx) {
    __syncwarp();
    if ((threadIdx.x & 31) == 0)
        asm volatile("red.release.gpu.global.add.u32 [%0], 1;" :: "l"(g_cnt + idx * 32) : "memory");
}
__device__ __forceinline__ void flag_release(int idx) {
    asm volatile("red.release.gpu.global.add.u32 [%0], 1;" :: "l"(g_cnt + idx * 32) : "memory");
}
__device__ __forceinline__ void exit_ticket() {
    unsigned tk;
    asm volatile("atom.relaxed.gpu.global.add.u32 %0, [%1], 1;" : "=r"(tk) : "l"(g_cnt + C_EXIT * 32) : "memory");
    if (tk == gridDim.x - 1) {
#pragma unroll 1
        for (int i = 0; i < C_NUM; i++) g_cnt[i * 32] = 0u;
    }
}
__device__ __forceinline__ void nbar_arrive(int id, int cnt) { asm volatile("bar.arrive %0, %1;" :: "r"(id), "r"(cnt) : "memory"); }
__device__ __forceinline__ void nbar_sync(int id, int cnt) { asm volatile("bar.sync %0, %1;" :: "r"(id), "r"(cnt) : "memory"); }
__device__ __forceinline__ void flag_wait(int idx, unsigned target) {
    asm volatile("{\n.reg .pred p;\n.reg .u32 n, v;\nmov.u32 n, 0;\n"
                 "FW_%=:\n"
                 "ld.acquire.gpu.global.u32 v, [%0];\n"
                 "setp.ge.u32 p, v, %1;\n"
                 "@p bra FD_%=;\n"
                 "add.u32 n, n, 1;\n"
                 "setp.lt.u32 p, n, 16000000;\n"
                 "@p bra FW_%=;\n"
                 "trap;\n"
                 "FD_%=:\n}"
                 :: "l"(g_cnt + idx * 32), "r"(target) : "memory");
}
__device__ __forceinline__ void flag_wait_all(int idx, unsigned target) {
    asm volatile("{\n.reg .pred p;\n.reg .u32 n, v;\nmov.u32 n, 0;\n"
                 "FW_%=:\n"
                 "ld.acquire.gpu.global.u32 v, [%0];\n"
                 "setp.ge.u32 p, v, %1;\n"
                 "vote.sync.all.pred p, p, 0xffffffff;\n"
                 "@p bra.uni FD_%=;\n"
                 "add.u32 n, n, 1;\n"
                 "setp.lt.u32 p, n, 16000000;\n"
                 "@p bra.uni FW_%=;\n"
                 "trap;\n"
                 "FD_%=:\n}"
                 :: "l"(g_cnt + idx * 32), "r"(target) : "memory");
}
__device__ __forceinline__ void fence_proxy_async_all() { asm volatile("fence.proxy.async.global;" ::: "memory"); }
__device__ __forceinline__ void mbar_init(uint32_t bar, uint32_t cnt) {
    asm volatile("mbarrier.init.shared::cta.b64 [%0], %1;" :: "r"(bar), "r"(cnt) : "memory");
}
__device__ __forceinline__ void mbar_expect_tx(uint32_t bar, uint32_t bytes) {
    asm volatile("mbarrier.arrive.expect_tx.shared::cta.b64 _, [%0], %1;" :: "r"(bar), "r"(bytes) : "memory");
}
__device__ __forceinline__ void mbar_arrive(uint32_t bar) {
    asm volatile("mbarrier.arrive.shared::cta.b64 _, [%0];" :: "r"(bar) : "memory");
}
__device__ __forceinline__ void mbar_wait(uint32_t bar, uint32_t parity) {
    asm volatile("{\n.reg .pred p;\n.reg .u32 n;\nmov.u32 n, 0;\n"
                 "WAIT_%=:\n"
                 "mbarrier.try_wait.parity.shared::cta.b64 p, [%0], %1;\n"
                 "@p bra DONE_%=;\n"
                 "add.u32 n, n, 1;\n"
                 "setp.lt.u32 p, n, 4000000;\n"
                 "@p bra WAIT_%=;\n"
                 "trap;\n"
                 "DONE_%=:\n}"
                 :: "r"(bar), "r"(parity) : "memory");
}
__device__ __forceinline__ void fence_barrier_init() { asm volatile("fence.mbarrier_init.release.cluster;" ::: "memory"); }
__device__ __forceinline__ void fence_proxy_async() { asm volatile("fence.proxy.async.shared::cta;" ::: "memory"); }
__device__ __forceinline__ void tma3d(uint32_t dst, const CUtensorMap* map, uint32_t bar, int row, int chunk) {
    asm volatile("cp.async.bulk.tensor.3d.shared::cluster.global.mbarrier::complete_tx::bytes [%0], [%1, {%3, %4, %5}], [%2];"
                 :: "r"(dst), "l"((uint64_t)map), "r"(bar), "r"(0), "r"(row), "r"(chunk) : "memory");
}
__device__ __forceinline__ void bulk_g2s(uint32_t dst, const void* src, uint32_t bytes, uint32_t bar) {
    asm volatile("cp.async.bulk.shared::cluster.global.mbarrier::complete_tx::bytes [%0], [%1], %2, [%3];"
                 :: "r"(dst), "l"((uint64_t)src), "r"(bytes), "r"(bar) : "memory");
}
__device__ __forceinline__ void l2_prefetch(const void* src, uint32_t bytes) {
    asm volatile("cp.async.bulk.prefetch.L2.global [%0], %1;" :: "l"((uint64_t)src), "r"(bytes) : "memory");
}
__device__ __forceinline__ void map_prefetch(const CUtensorMap* m) {
    asm volatile("prefetch.tensormap [%0];" :: "l"((uint64_t)m) : "memory");
}
__device__ __forceinline__ uint64_t mkdesc(uint32_t addr, uint32_t lbo, uint32_t sbo, uint32_t swz) {
    return (uint64_t)((addr & 0x3FFFF) >> 4) | ((uint64_t)(lbo >> 4) << 16) | ((uint64_t)(sbo >> 4) << 32) | ((uint64_t)swz << 62);
}
#define WG_FENCE() asm volatile("wgmma.fence.sync.aligned;" ::: "memory")
#define WG_COMMIT() asm volatile("wgmma.commit_group.sync.aligned;" ::: "memory")
#define WG_WAIT(n) asm volatile("wgmma.wait_group.sync.aligned %0;" :: "n"(n) : "memory")

__device__ __forceinline__ float ex2(float x) { float y; asm("ex2.approx.ftz.f32 %0, %1;" : "=f"(y) : "f"(x)); return y; }
__device__ __forceinline__ uint32_t packbf(float lo, float hi) {
    uint32_t r; asm("cvt.rn.bf16x2.f32 %0, %1, %2;" : "=r"(r) : "f"(hi), "f"(lo)); return r;
}
__device__ __forceinline__ uint32_t hmul2bf(uint32_t a, uint32_t b) { uint32_t r; asm("mul.rn.bf16x2 %0, %1, %2;" : "=r"(r) : "r"(a), "r"(b)); return r; }
__device__ __forceinline__ float bf_lo(uint32_t v) { return __uint_as_float(v << 16); }
__device__ __forceinline__ float bf_hi(uint32_t v) { return __uint_as_float(v & 0xffff0000u); }
__device__ __forceinline__ float bfr(float x) { return __bfloat162float(__float2bfloat16_rn(x)); }

__device__ __forceinline__ void wgmma_n192(float (&d)[96], uint64_t da, uint64_t db, int scale_d) {
    asm volatile("{\n.reg .pred p;\nsetp.ne.b32 p, %98, 0;\n"
        "wgmma.mma_async.sync.aligned.m64n192k16.f32.bf16.bf16 "
        "{%0,%1,%2,%3,%4,%5,%6,%7,%8,%9,%10,%11,%12,%13,%14,%15,%16,%17,%18,%19,%20,%21,%22,%23,"
        "%24,%25,%26,%27,%28,%29,%30,%31,%32,%33,%34,%35,%36,%37,%38,%39,%40,%41,%42,%43,%44,%45,%46,%47,"
        "%48,%49,%50,%51,%52,%53,%54,%55,%56,%57,%58,%59,%60,%61,%62,%63,%64,%65,%66,%67,%68,%69,%70,%71,"
        "%72,%73,%74,%75,%76,%77,%78,%79,%80,%81,%82,%83,%84,%85,%86,%87,%88,%89,%90,%91,%92,%93,%94,%95}, "
        "%96, %97, p, 1, 1, 0, 1;\n}"
        : "+f"(d[0]), "+f"(d[1]), "+f"(d[2]), "+f"(d[3]), "+f"(d[4]), "+f"(d[5]), "+f"(d[6]), "+f"(d[7]),
          "+f"(d[8]), "+f"(d[9]), "+f"(d[10]), "+f"(d[11]), "+f"(d[12]), "+f"(d[13]), "+f"(d[14]), "+f"(d[15]),
          "+f"(d[16]), "+f"(d[17]), "+f"(d[18]), "+f"(d[19]), "+f"(d[20]), "+f"(d[21]), "+f"(d[22]), "+f"(d[23]),
          "+f"(d[24]), "+f"(d[25]), "+f"(d[26]), "+f"(d[27]), "+f"(d[28]), "+f"(d[29]), "+f"(d[30]), "+f"(d[31]),
          "+f"(d[32]), "+f"(d[33]), "+f"(d[34]), "+f"(d[35]), "+f"(d[36]), "+f"(d[37]), "+f"(d[38]), "+f"(d[39]),
          "+f"(d[40]), "+f"(d[41]), "+f"(d[42]), "+f"(d[43]), "+f"(d[44]), "+f"(d[45]), "+f"(d[46]), "+f"(d[47]),
          "+f"(d[48]), "+f"(d[49]), "+f"(d[50]), "+f"(d[51]), "+f"(d[52]), "+f"(d[53]), "+f"(d[54]), "+f"(d[55]),
          "+f"(d[56]), "+f"(d[57]), "+f"(d[58]), "+f"(d[59]), "+f"(d[60]), "+f"(d[61]), "+f"(d[62]), "+f"(d[63]),
          "+f"(d[64]), "+f"(d[65]), "+f"(d[66]), "+f"(d[67]), "+f"(d[68]), "+f"(d[69]), "+f"(d[70]), "+f"(d[71]),
          "+f"(d[72]), "+f"(d[73]), "+f"(d[74]), "+f"(d[75]), "+f"(d[76]), "+f"(d[77]), "+f"(d[78]), "+f"(d[79]),
          "+f"(d[80]), "+f"(d[81]), "+f"(d[82]), "+f"(d[83]), "+f"(d[84]), "+f"(d[85]), "+f"(d[86]), "+f"(d[87]),
          "+f"(d[88]), "+f"(d[89]), "+f"(d[90]), "+f"(d[91]), "+f"(d[92]), "+f"(d[93]), "+f"(d[94]), "+f"(d[95])
        : "l"(da), "l"(db), "r"(scale_d));
}

constexpr float SHIFT = 90.0f;
constexpr float QS = 0.25f * 1.4426950408889634f * 18446744073709551616.0f;
constexpr float scq = 0.25f * 1.4426950408889634f * 3.3087224502121107e-24f;

__device__ __forceinline__ uint32_t polyexp(float lo, float hi) {
    uint32_t w, g, q, h;
    asm("cvt.pack.sat.s16.s32 %0, %1, %2;" : "=r"(w) : "r"(__float_as_uint(hi)), "r"(__float_as_uint(lo)));
    g = w & 0x007F007Fu;
    asm("fma.rn.f16x2 %0, %1, %2, %3;" : "=r"(q) : "r"(g), "r"(0xf940f940u), "r"(0x35513551u));
    asm("mul.rn.f16x2 %0, %1, %2;" : "=r"(h) : "r"(q), "r"(g));
    return w - h;
}
__device__ __forceinline__ void qk64(float (&s)[32], const uint32_t (&q)[4], uint64_t db) {
    asm volatile("wgmma.mma_async.sync.aligned.m64n64k16.f32.bf16.bf16 "
        "{%0,%1,%2,%3,%4,%5,%6,%7,%8,%9,%10,%11,%12,%13,%14,%15,%16,%17,%18,%19,%20,%21,%22,%23,%24,%25,%26,%27,%28,%29,%30,%31}, "
        "{%32,%33,%34,%35}, %36, 0, 1, 1, 0;"
        : "=f"(s[0]), "=f"(s[1]), "=f"(s[2]), "=f"(s[3]), "=f"(s[4]), "=f"(s[5]), "=f"(s[6]), "=f"(s[7]),
          "=f"(s[8]), "=f"(s[9]), "=f"(s[10]), "=f"(s[11]), "=f"(s[12]), "=f"(s[13]), "=f"(s[14]), "=f"(s[15]),
          "=f"(s[16]), "=f"(s[17]), "=f"(s[18]), "=f"(s[19]), "=f"(s[20]), "=f"(s[21]), "=f"(s[22]), "=f"(s[23]),
          "=f"(s[24]), "=f"(s[25]), "=f"(s[26]), "=f"(s[27]), "=f"(s[28]), "=f"(s[29]), "=f"(s[30]), "=f"(s[31])
        : "r"(q[0]), "r"(q[1]), "r"(q[2]), "r"(q[3]), "l"(db));
}
__device__ __forceinline__ void pv24(float (&o)[12], uint32_t a0, uint32_t a1, uint32_t a2, uint32_t a3, uint64_t db) {
    asm volatile("wgmma.mma_async.sync.aligned.m64n24k16.f32.bf16.bf16 "
        "{%0,%1,%2,%3,%4,%5,%6,%7,%8,%9,%10,%11}, {%12,%13,%14,%15}, %16, 1, 1, 1, 1;"
        : "+f"(o[0]), "+f"(o[1]), "+f"(o[2]), "+f"(o[3]), "+f"(o[4]), "+f"(o[5]), "+f"(o[6]), "+f"(o[7]),
          "+f"(o[8]), "+f"(o[9]), "+f"(o[10]), "+f"(o[11])
        : "r"(a0), "r"(a1), "r"(a2), "r"(a3), "l"(db));
}

__device__ __forceinline__ void mma_full(float (&d)[4], uint32_t a0, uint32_t a1, uint32_t a2, uint32_t a3, uint32_t b0, uint32_t b1) {
    asm volatile("mma.sync.aligned.m16n8k16.row.col.f32.bf16.bf16.f32 {%0,%1,%2,%3}, {%4,%5,%6,%7}, {%8,%9}, {%0,%1,%2,%3};"
                 : "+f"(d[0]), "+f"(d[1]), "+f"(d[2]), "+f"(d[3]) : "r"(a0), "r"(a1), "r"(a2), "r"(a3), "r"(b0), "r"(b1));
}
__device__ __forceinline__ uint32_t movt(uint32_t a) {
    uint32_t r; asm volatile("movmatrix.sync.aligned.m8n8.trans.b16 %0, %1;" : "=r"(r) : "r"(a)); return r;
}
__device__ __noinline__ void attn_safe(float* o_out, const uint32_t* qf, int head, int lane) {
    float o0[4] = {0.f, 0.f, 0.f, 0.f}, o1[4] = {0.f, 0.f, 0.f, 0.f};
    float m0 = -INFINITY, m1 = -INFINITY, l0 = 0.f, l1 = 0.f;
    const uint32_t q0 = qf[0], q1 = qf[1], q2 = qf[2], q3 = qf[3];
#pragma unroll 1
    for (int kb = 0; kb < 128; kb++) {
        const uint32_t* src = g_qkv + head * 49152 + (kb >> 4) * 6144 + (kb & 15) * 64 + lane;
        float sa[4] = {0.f, 0.f, 0.f, 0.f}, sb[4] = {0.f, 0.f, 0.f, 0.f};
        mma_full(sa, q0, q1, q2, q3, __ldcg(src), __ldcg(src + 1024));
        mma_full(sb, q0, q1, q2, q3, __ldcg(src + 32), __ldcg(src + 1024 + 32));
        float n0 = fmaxf(fmaxf(m0, fmaxf(sa[0], sa[1])), fmaxf(sb[0], sb[1]));
        float n1 = fmaxf(fmaxf(m1, fmaxf(sa[2], sa[3])), fmaxf(sb[2], sb[3]));
        n0 = fmaxf(n0, __shfl_xor_sync(~0u, n0, 1)); n0 = fmaxf(n0, __shfl_xor_sync(~0u, n0, 2));
        n1 = fmaxf(n1, __shfl_xor_sync(~0u, n1, 1)); n1 = fmaxf(n1, __shfl_xor_sync(~0u, n1, 2));
        const float c0 = ex2((m0 - n0) * QS), c1 = ex2((m1 - n1) * QS);
        m0 = n0; m1 = n1;
        const uint32_t p0 = packbf(ex2((sa[0] - m0) * QS), ex2((sa[1] - m0) * QS));
        const uint32_t p1 = packbf(ex2((sa[2] - m1) * QS), ex2((sa[3] - m1) * QS));
        const uint32_t p2 = packbf(ex2((sb[0] - m0) * QS), ex2((sb[1] - m0) * QS));
        const uint32_t p3 = packbf(ex2((sb[2] - m1) * QS), ex2((sb[3] - m1) * QS));
        l0 = l0 * c0 + (bf_lo(p0) + bf_hi(p0)) + (bf_lo(p2) + bf_hi(p2));
        l1 = l1 * c1 + (bf_lo(p1) + bf_hi(p1)) + (bf_lo(p3) + bf_hi(p3));
        o0[0] *= c0; o0[1] *= c0; o0[2] *= c1; o0[3] *= c1;
        o1[0] *= c0; o1[1] *= c0; o1[2] *= c1; o1[3] *= c1;
        mma_full(o0, p0, p1, p2, p3, movt(__ldcg(src + 2048)), movt(__ldcg(src + 2048 + 32)));
        mma_full(o1, p0, p1, p2, p3, movt(__ldcg(src + 3072)), movt(__ldcg(src + 3072 + 32)));
    }
    l0 += __shfl_xor_sync(~0u, l0, 1); l0 += __shfl_xor_sync(~0u, l0, 2);
    l1 += __shfl_xor_sync(~0u, l1, 1); l1 += __shfl_xor_sync(~0u, l1, 2);
#pragma unroll
    for (int i = 0; i < 4; i++) { o_out[i] = o0[i]; o_out[4 + i] = o1[i]; }
    o_out[8] = o_out[9] = l0; o_out[10] = o_out[11] = l1;
}

__device__ __forceinline__ void load_q(uint32_t (&q)[4], int head, int mt, int lane) {
    const uint32_t* src = g_qkv + head * 49152 + (mt >> 4) * 6144 + 4096 + (mt & 15) * 64 + lane;
    q[0] = __ldcg(src); q[1] = __ldcg(src + 32); q[2] = __ldcg(src + 1024); q[3] = __ldcg(src + 1024 + 32);
}
__device__ __forceinline__ void attn_store(const float (&o)[12], int head, int m64, int warp, int lane) {
    const int g = lane >> 2, t = lane & 3;
    const int row = m64 * 64 + warp * 16 + g;
    const float i0 = 1.f / o[8], i1 = 1.f / o[10];
    uint32_t* p0 = reinterpret_cast<uint32_t*>(g_o + (size_t)row * DM + head * 16 + t * 2);
    uint32_t* p1 = reinterpret_cast<uint32_t*>(g_o + (size_t)(row + 8) * DM + head * 16 + t * 2);
    p0[0] = packbf(o[0] * i0, o[1] * i0); p0[4] = packbf(o[4] * i0, o[5] * i0);
    p1[0] = packbf(o[2] * i1, o[3] * i1); p1[4] = packbf(o[6] * i1, o[7] * i1);
}

constexpr int FS_N = 4;
constexpr int FS_BYTES = 32768;
__device__ __forceinline__ void ldsm4t(uint32_t& r0, uint32_t& r1, uint32_t& r2, uint32_t& r3, uint32_t addr) {
    asm volatile("ldmatrix.sync.aligned.m8n8.x4.trans.shared.b16 {%0,%1,%2,%3}, [%4];" : "=r"(r0), "=r"(r1), "=r"(r2), "=r"(r3) : "r"(addr) : "memory");
}
__device__ __forceinline__ void mma16816(float (&d)[4], uint32_t a0, uint32_t a2, uint32_t b0, uint32_t b1) {
    asm volatile("mma.sync.aligned.m16n8k16.row.col.f32.bf16.bf16.f32 {%0,%1,%2,%3}, {%4,%5,%6,%5}, {%7,%8}, {%0,%1,%2,%3};"
                 : "+f"(d[0]), "+f"(d[1]), "+f"(d[2]), "+f"(d[3]) : "r"(a0), "r"(0u), "r"(a2), "r"(b0), "r"(b1));
}
__device__ void ffn_block(int c, uint8_t* smem, uint32_t sbase, const CUtensorMap* mapG, const CUtensorMap* mapU, const CUtensorMap* mapD) {
    const int tid = threadIdx.x, warp = tid >> 5, lane = tid & 31;
    uint32_t* sx = reinterpret_cast<uint32_t*>(smem + FS_N * FS_BYTES);
    __nv_bfloat16* sh = reinterpret_cast<__nv_bfloat16*>(sx + 512);
    const uint32_t bars = sbase + FS_N * FS_BYTES + 8192;
    float* tv = reinterpret_cast<float*>(smem + FS_N * FS_BYTES + 4096);
    int* ti = reinterpret_cast<int*>(tv + 32);
    int* ssel = ti + 32;
    auto issue = [&](int item) {
        const int slot = item % FS_N;
        const uint32_t dst = sbase + slot * FS_BYTES, bar = bars + 8 * slot;
        mbar_expect_tx(bar, item < 32 ? 28672 : 32768);
        if (item < 32) {
            tma3d(dst, mapG, bar, item * 16, c * 7);
            tma3d(dst + 14336, mapU, bar, item * 16, c * 7);
        } else {
            tma3d(dst, mapD, bar, c * 448 + (item - 32) * 32, 0);
        }
    };
    if (tid == 0) {
        for (int i = 0; i < FS_N; i++) mbar_init(bars + 8 * i, 1);
        fence_barrier_init();
        for (int i = 0; i < FS_N; i++) issue(i);
    }
    flag_wait(C_LN + warp, 8);
    __syncthreads();
    float b1 = -INFINITY, b2 = -INFINITY; int i1 = 0x7fffffff, i2 = 0x7fffffff;
    auto push = [&](float v, int i) {
        if (v > b1 || (v == b1 && i < i1)) { b2 = b1; i2 = i1; b1 = v; i1 = i; }
        else if (v > b2 || (v == b2 && i < i2)) { b2 = v; i2 = i; }
    };
    {
        const float4 rv = __ldcg(reinterpret_cast<const float4*>(g_r) + tid);
        push(rv.x, 4 * tid); push(rv.y, 4 * tid + 1); push(rv.z, 4 * tid + 2); push(rv.w, 4 * tid + 3);
    }
#pragma unroll
    for (int o = 16; o > 0; o >>= 1) {
        float v1 = __shfl_xor_sync(~0u, b1, o), v2 = __shfl_xor_sync(~0u, b2, o);
        int j1 = __shfl_xor_sync(~0u, i1, o), j2 = __shfl_xor_sync(~0u, i2, o);
        push(v1, j1); push(v2, j2);
    }
    if (lane == 0) { tv[2 * warp] = b1; ti[2 * warp] = i1; tv[2 * warp + 1] = b2; ti[2 * warp + 1] = i2; }
    __syncthreads();
    if (warp == 1) {
        b1 = tv[lane]; i1 = ti[lane]; b2 = -INFINITY; i2 = 0x7fffffff;
#pragma unroll
        for (int o = 16; o > 0; o >>= 1) {
            float v1 = __shfl_xor_sync(~0u, b1, o), v2 = __shfl_xor_sync(~0u, b2, o);
            int j1 = __shfl_xor_sync(~0u, i1, o), j2 = __shfl_xor_sync(~0u, i2, o);
            push(v1, j1); push(v2, j2);
        }
        if (lane == 0) {
            i1 = min(max(i1, 0), S_LEN - 1); i2 = min(max(i2, 0), S_LEN - 1);
            ssel[0] = i1; ssel[1] = i2;
            if (c == 0) {
                g_sel[0] = i1; g_sel[1] = i2;
                g_gate[0] = bfr(1.f / (1.f + __expf(-bfr(b1))));
                g_gate[1] = bfr(1.f / (1.f + __expf(-bfr(b2))));
            }
        }
    }
    __syncthreads();
    sx[tid] = __ldcg(reinterpret_cast<const uint32_t*>(g_xn + (size_t)ssel[tid >> 8] * DM + (tid & 255) * 2));
    __syncthreads();
    TL(1);
    const int g = lane >> 2, t = lane & 3;
    const int lrow = lane & 15, lsel = lane >> 4;
    {
        float ag[4][4], au[4][4];
#pragma unroll
        for (int j = 0; j < 4; j++) { ag[j][0] = ag[j][1] = ag[j][2] = ag[j][3] = 0.f; au[j][0] = au[j][1] = au[j][2] = au[j][3] = 0.f; }
#pragma unroll 1
        for (int it = 0; it < 32; it++) {
            const int slot = it % FS_N;
            const uint32_t a0 = g < 2 ? sx[g * 256 + it * 8 + t] : 0u, a2 = g < 2 ? sx[g * 256 + it * 8 + 4 + t] : 0u;
            mbar_wait(bars + 8 * slot, (it / FS_N) & 1);
            const uint32_t base = sbase + slot * FS_BYTES + lsel * 14336 + lrow * 128;
#pragma unroll
            for (int j = 0; j < 4; j++) {
                const int nt = warp + j * 16;
                if (nt < 56) {
                    uint32_t b0, b1, b2, b3;
                    ldsm4t(b0, b1, b2, b3, base + (nt >> 3) * 2048 + (((nt & 7) ^ (lrow & 7)) << 4));
                    mma16816(ag[j], a0, a2, b0, b1);
                    mma16816(au[j], a0, a2, b2, b3);
                }
            }
            __syncthreads();
            if (tid == 480) issue(it + FS_N);
        }
        if (g < 2) {
#pragma unroll
            for (int j = 0; j < 4; j++) {
                const int nt = warp + j * 16;
                if (nt < 56) {
#pragma unroll
                    for (int e = 0; e < 2; e++) {
                        const float gs = bfr(ag[j][e]), us = bfr(au[j][e]);
                        const float sg = bfr(gs / (1.f + __expf(-gs)));
                        sh[g * 448 + nt * 8 + t * 2 + e] = __float2bfloat16_rn(sg * us);
                    }
                }
            }
        }
        __syncthreads();
    }
    TL(2);
    {
        const uint32_t* shw = reinterpret_cast<const uint32_t*>(sh);
        float a[4][4];
#pragma unroll
        for (int j = 0; j < 4; j++) a[j][0] = a[j][1] = a[j][2] = a[j][3] = 0.f;
#pragma unroll 1
        for (int it = 32; it < 46; it++) {
            const int slot = it % FS_N;
            uint32_t af[4];
#pragma unroll
            for (int q = 0; q < 4; q++) af[q] = g < 2 ? shw[g * 224 + (it - 32) * 16 + q * 4 + t] : 0u;
            mbar_wait(bars + 8 * slot, (it / FS_N) & 1);
            const uint32_t base = sbase + slot * FS_BYTES + (warp >> 1) * 4096 + lane * 128;
#pragma unroll
            for (int j = 0; j < 4; j++) {
                const int u = (warp & 1) * 4 + j;
                uint32_t b0, b1, b2, b3;
                ldsm4t(b0, b1, b2, b3, base + ((u ^ (lane & 7)) << 4));
                mma16816(a[j], af[0], af[1], b0, b1);
                mma16816(a[j], af[2], af[3], b2, b3);
            }
            __syncthreads();
            if (tid == 480 && it + FS_N < 46) issue(it + FS_N);
        }
        if (g < 2) {
#pragma unroll
            for (int j = 0; j < 4; j++)
                *reinterpret_cast<float2*>(&g_ypart[c * 1024 + g * 512 + (warp * 4 + j) * 8 + t * 2]) = make_float2(a[j][0], a[j][1]);
        }
    }
    warp_arrive(C_FFN);
}

__device__ __forceinline__ void wgmma_n32(float (&d)[16], uint64_t da, uint64_t db, int scale_d) {
    asm volatile("{\n.reg .pred p;\nsetp.ne.b32 p, %18, 0;\n"
        "wgmma.mma_async.sync.aligned.m64n32k16.f32.bf16.bf16 "
        "{%0,%1,%2,%3,%4,%5,%6,%7,%8,%9,%10,%11,%12,%13,%14,%15}, "
        "%16, %17, p, 1, 1, 0, 1;\n}"
        : "+f"(d[0]), "+f"(d[1]), "+f"(d[2]), "+f"(d[3]), "+f"(d[4]), "+f"(d[5]), "+f"(d[6]), "+f"(d[7]),
          "+f"(d[8]), "+f"(d[9]), "+f"(d[10]), "+f"(d[11]), "+f"(d[12]), "+f"(d[13]), "+f"(d[14]), "+f"(d[15])
        : "l"(da), "l"(db), "r"(scale_d));
}

constexpr int G_ST = 4;
constexpr int G_STAGE = 16384 + 24576;
constexpr int SM_KV = 0, KV_CH = 20480, SM_WO = 163840, SM_MISC = 229376;
constexpr int FUSED_SMEM = SM_MISC + 2048;
constexpr int B_FULL = 0, B_EMPTY = 4, B_KV = 8, B_WO = 16, B_OA = 18, B_NUM = 22, B_HALF = 22;

struct Maps { CUtensorMap xn, wqkv, o, wo, g, u, d; };

__global__ void __launch_bounds__(512, 1) fused_kernel(const __grid_constant__ Maps maps, const __nv_bfloat16* __restrict__ x,
                                                       const __nv_bfloat16* __restrict__ wr, __nv_bfloat16* __restrict__ out, float sc) {
    extern __shared__ __align__(1024) uint8_t smem[];
    const uint32_t sbase = smem_u32(smem);
    const int tid = threadIdx.x, warp = __shfl_sync(~0u, tid >> 5, 0), lane = tid & 31;
    const uint32_t bars = sbase + SM_MISC;
    TL(0);
    if (sbase & 1023u) __trap();
    if (blockIdx.x < 4) {
        ffn_block(blockIdx.x, smem, sbase, &maps.g, &maps.u, &maps.d);
        __syncthreads();
        if (tid == 0) exit_ticket();
        TL(3);
    } else {
        const int idx = blockIdx.x - 4;
        const int wg = warp >> 2;
        {
            const int row = idx * 16 + warp;
            const uint4* xr = reinterpret_cast<const uint4*>(x + (size_t)row * DM);
            const uint4 a = xr[lane], b = xr[32 + lane];
            const uint4* wp = reinterpret_cast<const uint4*>(wr);
            const uint4 wa = wp[lane], wb = wp[32 + lane];
            if (tid == 480) {
                for (int s = 0; s < G_ST; s++) { mbar_init(bars + 8 * (B_FULL + s), 2); mbar_init(bars + 8 * (B_EMPTY + s), 2); }
                for (int c = B_KV; c < B_NUM; c++) mbar_init(bars + 8 * c, 1);
                mbar_init(bars + 8 * B_HALF, 4);
                fence_barrier_init();
                for (int c = 0; c < G_ST; c++) {
                    mbar_expect_tx(bars + 8 * (B_FULL + c), 24576);
                    tma3d(sbase + c * G_STAGE + 16384, &maps.wqkv, bars + 8 * (B_FULL + c), c * 64, (idx & 7) * 3);
                }
                map_prefetch(&maps.xn);
            }
            __syncwarp();
            const uint32_t u[8] = {a.x, a.y, a.z, a.w, b.x, b.y, b.z, b.w};
            const uint32_t w[8] = {wa.x, wa.y, wa.z, wa.w, wb.x, wb.y, wb.z, wb.w};
            float f[16];
            float sum = 0.f;
#pragma unroll
            for (int i = 0; i < 8; i++) { f[2 * i] = bf_lo(u[i]); f[2 * i + 1] = bf_hi(u[i]); sum += f[2 * i] + f[2 * i + 1]; }
#pragma unroll
            for (int o = 16; o > 0; o >>= 1) sum += __shfl_xor_sync(~0u, sum, o);
            const float mean = sum * (1.f / DM);
            float sq = 0.f;
#pragma unroll
            for (int i = 0; i < 16; i++) { const float d = f[i] - mean; sq = fmaf(d, d, sq); }
#pragma unroll
            for (int o = 16; o > 0; o >>= 1) sq += __shfl_xor_sync(~0u, sq, o);
            const float mb_ = bfr(mean);
            const float vb = bfr(sq * (1.f / DM));
            const float rinv = 1.f / bfr(sqrtf(bfr(vb + 1e-5f)));
            uint32_t o[8];
            float r = 0.f;
#pragma unroll
            for (int i = 0; i < 8; i++) {
                const float d0 = bfr(f[2 * i] - mb_), d1 = bfr(f[2 * i + 1] - mb_);
                o[i] = packbf(d0 * rinv, d1 * rinv);
                r = fmaf(bf_lo(o[i]), bf_lo(w[i]), r);
                r = fmaf(bf_hi(o[i]), bf_hi(w[i]), r);
            }
            uint4* xo = reinterpret_cast<uint4*>(g_xn + (size_t)row * DM);
            xo[lane] = make_uint4(o[0], o[1], o[2], o[3]);
            xo[32 + lane] = make_uint4(o[4], o[5], o[6], o[7]);
#pragma unroll
            for (int of = 16; of > 0; of >>= 1) r += __shfl_xor_sync(~0u, r, of);
            if (lane == 0) g_r[row] = r;
        }
        __syncthreads();
        if (tid == 416) flag_release(C_LN + (idx >> 3));
        TL(1);
        {
            const int nb = idx & 7, mb = idx >> 3;
            if (warp == 15) {
                for (int c = G_ST; c < 8; c++) {
                    const int s = c - G_ST;
                    mbar_wait(bars + 8 * (B_EMPTY + s), 0);
                    if (lane == 0) {
                        mbar_expect_tx(bars + 8 * (B_FULL + s), 24576);
                        tma3d(sbase + s * G_STAGE + 16384, &maps.wqkv, bars + 8 * (B_FULL + s), c * 64, nb * 3);
                    }
                    __syncwarp();
                }
            } else if (warp == 14) {
                flag_wait(C_LN + mb, 8);
                fence_proxy_async_all();
                for (int c = 0; c < 8; c++) {
                    const int s = c & (G_ST - 1);
                    if (c >= G_ST) mbar_wait(bars + 8 * (B_EMPTY + s), 0);
                    if (lane == 0) {
                        mbar_expect_tx(bars + 8 * (B_FULL + s), 16384);
                        tma3d(sbase + s * G_STAGE, &maps.xn, bars + 8 * (B_FULL + s), mb * 128, c);
                    }
                    __syncwarp();
                }
            } else if (wg < 2) {
                float acc[96];
#pragma unroll
                for (int i = 0; i < 96; i++) acc[i] = 0.f;
#pragma unroll 1
                for (int c = 0; c < 8; c++) {
                    const int s = c & (G_ST - 1);
                    const uint32_t st = sbase + s * G_STAGE;
                    mbar_wait(bars + 8 * (B_FULL + s), c >> 2);
                    if (c == 0) TL(2);
                    const uint64_t da = mkdesc(st + wg * 8192, 16, 1024, 1);
                    const uint64_t db = mkdesc(st + 16384, 8192, 1024, 1);
                    WG_FENCE();
#pragma unroll
                    for (int k = 0; k < 4; k++) wgmma_n192(acc, da + k * 2, db + k * 128, (c | k) != 0);
                    WG_COMMIT();
                    if (c <= G_ST) {
                        WG_WAIT(1);
                        if (c >= 1 && (tid & 127) == 0) mbar_arrive(bars + 8 * (B_EMPTY + c - 1));
                    }
                }
                WG_WAIT(0);
                nbar_arrive(6, 512);
                TL(3);
                const int mt = mb * 8 + warp;
                uint32_t* dst0 = g_qkv + (mt >> 4) * 6144 + (mt & 15) * 64 + lane;
#pragma unroll
                for (int hh = 0; hh < 12; hh++) {
                    const int gh = nb * 12 + hh, ty = gh >> 5;
                    const float* a = &acc[hh * 8];
                    uint32_t* dst = dst0 + (gh & 31) * 49152 + ((ty + 2) % 3) * 2048;
                    const uint32_t ks = ty == 1 ? 0x1f801f80u : 0x3f803f80u;
                    dst[0] = hmul2bf(packbf(a[0], a[1]), ks);
                    dst[32] = hmul2bf(packbf(a[2], a[3]), ks);
                    dst[1024] = hmul2bf(packbf(a[4], a[5]), ks);
                    dst[1024 + 32] = hmul2bf(packbf(a[6], a[7]), ks);
                }
                TL(10);
                nbar_sync(8, 256);
                if (tid == 0) flag_release(C_QKV + nb);
            }
        }
        TL(4);
        const int head = idx >> 2, quarter = idx & 3, w4 = warp & 3;
        {
            if (warp == 15) {
                flag_wait_all(C_QKV + ((lane % 3) * 32 + head) / 12, 16);
                nbar_sync(6, 512);
                fence_proxy_async_all();
                if (lane == 0) {
                    const uint8_t* kvp = reinterpret_cast<const uint8_t*>(g_qkv + head * 49152);
#pragma unroll 1
                    for (int c = 0; c < 2; c++) {
                        mbar_expect_tx(bars + 8 * (B_KV + c), 16384);
                        bulk_g2s(sbase + SM_KV + c * KV_CH, kvp + c * 24576, 16384, bars + 8 * (B_KV + c));
                    }
                }
                __syncwarp();
            } else if (wg >= 2) {
                nbar_sync(6, 512);
#pragma unroll 1
                for (int i = tid - 256; i < 2048; i += 224)
                    *reinterpret_cast<uint4*>(smem + SM_KV + (i >> 8) * KV_CH + 16384 + (i & 255) * 16) = make_uint4(0x3f803f80u, 0x3f803f80u, 0x3f803f80u, 0x3f803f80u);
                fence_proxy_async();
            }
            __syncthreads();
            if (tid == 480) {
                const uint8_t* kvp = reinterpret_cast<const uint8_t*>(g_qkv + head * 49152);
#pragma unroll 1
                for (int c = 2; c < 8; c++) {
                    mbar_expect_tx(bars + 8 * (B_KV + c), 16384);
                    bulk_g2s(sbase + SM_KV + c * KV_CH, kvp + c * 24576, 16384, bars + 8 * (B_KV + c));
                }
            } else if (tid == 352) {
                mbar_expect_tx(bars + 8 * B_WO, 65536);
                tma3d(sbase + SM_WO, &maps.wo, bars + 8 * B_WO, 0, idx & 7);
                tma3d(sbase + SM_WO + 32768, &maps.wo, bars + 8 * B_WO, 256, idx & 7);
                map_prefetch(&maps.o);
            }
            __syncwarp();
            const uint64_t kdesc0 = mkdesc(sbase + SM_KV, 4096, 128, 0);
            const uint64_t vdesc0 = mkdesc(sbase + SM_KV + 8192, 128, 4096, 0);
#pragma unroll 1
            for (int mt = 0; mt < 2; mt++) {
                const int m64 = quarter * 8 + mt * 4 + wg;
                uint32_t q[4];
                load_q(q, head, m64 * 4 + w4, lane);
                float s[32], s2[32], o[12];
#pragma unroll
                for (int i = 0; i < 12; i++) o[i] = 0.f;
                mbar_wait(bars + 8 * B_KV, 0);
                if (mt == 0) { TL(5); TLC(12); }
                WG_FENCE();
                qk64(s, q, kdesc0);
                WG_COMMIT(); WG_WAIT(0);
                float mx0 = -INFINITY, mx1 = -INFINITY;
#pragma unroll
                for (int i = 0; i < 8; i++) { mx0 = fmaxf(mx0, fmaxf(s[4 * i], s[4 * i + 1])); mx1 = fmaxf(mx1, fmaxf(s[4 * i + 2], s[4 * i + 3])); }
                mx0 = fmaxf(mx0, __shfl_xor_sync(~0u, mx0, 1)); mx0 = fmaxf(mx0, __shfl_xor_sync(~0u, mx0, 2));
                mx1 = fmaxf(mx1, __shfl_xor_sync(~0u, mx1, 1)); mx1 = fmaxf(mx1, __shfl_xor_sync(~0u, mx1, 2));
                float cm0 = -(ceilf(mx0 * QS) + SHIFT), cm1 = -(ceilf(mx1 * QS) + SHIFT);
                float cp0 = (cm0 + 127.f) * sc, cp1 = (cm1 + 127.f) * sc;
                asm volatile("" : "+f"(cm0), "+f"(cm1), "+f"(cp0), "+f"(cp1));
                uint64_t kd = kdesc0, vd = vdesc0;
                auto step = [&](float (&sc_)[32], float (&sn)[32], uint64_t kinc, uint64_t vinc) {
                    kd += kinc;
                    WG_FENCE();
                    qk64(sn, q, kd);
                    WG_COMMIT();
#pragma unroll
                    for (int kk = 0; kk < 4; kk++) {
                        const int i0 = kk * 2, i1 = kk * 2 + 1;
                        const uint32_t p0 = packbf(ex2(fmaf(sc_[4 * i0], QS, cm0)), ex2(fmaf(sc_[4 * i0 + 1], QS, cm0)));
                        const uint32_t p1 = packbf(ex2(fmaf(sc_[4 * i0 + 2], QS, cm1)), ex2(fmaf(sc_[4 * i0 + 3], QS, cm1)));
                        const uint32_t p2 = polyexp(fmaf(sc_[4 * i1], scq, cp0), fmaf(sc_[4 * i1 + 1], scq, cp0));
                        const uint32_t p3 = polyexp(fmaf(sc_[4 * i1 + 2], scq, cp1), fmaf(sc_[4 * i1 + 3], scq, cp1));
                        WG_FENCE();
                        pv24(o, p0, p1, p2, p3, vd + kk * 16);
                    }
                    vd += vinc;
                    WG_COMMIT();
                    WG_WAIT(1);
                };
                uint64_t hop = 64u;
#pragma unroll 1
                for (int c = 0; c < 16; c++) {
                    if (mt == 0) {
                        if ((c & 1) == 0 && c < 14) mbar_wait(bars + 8 * B_KV + 4 * c + 8, 0);
                    } else if (c == 2) {
                        nbar_sync(wg + 1, 128);
                        if ((tid & 127) == 0) flag_release(C_O + m64 - 4);
                    } else if (c == 9) {
                        if ((tid & 127) == 32) mbar_arrive(bars + 8 * B_HALF);
                    } else if (c == 12 && wg == 3) {
                        const int jb = idx >> 3, mbe = (jb >> 2) * 8 + (jb & 3);
                        mbar_wait(bars + 8 * B_HALF, 0);
                        flag_wait_all((lane & 1) ? C_FFN : C_O + mbe, (lane & 1) ? 64 : 32);
                        fence_proxy_async_all();
                        if (tid == 416) {
                            mbar_expect_tx(bars + 8 * B_OA, 32768);
                            tma3d(sbase + SM_KV, &maps.o, bars + 8 * B_OA, mbe * 64, 0);
                            mbar_expect_tx(bars + 8 * (B_OA + 1), 32768);
                            tma3d(sbase + SM_KV + 32768, &maps.o, bars + 8 * (B_OA + 1), mbe * 64, 4);
                        }
                    }
                    step(s, s2, 64u, 64u);
                    step(s2, s, hop, hop);
                    hop ^= (KV_CH - 4096) / 16;
                }
                WG_WAIT(0);
                bool bad = !(o[8] > 0.f) || !(o[10] > 0.f);
#pragma unroll
                for (int i = 0; i < 12; i++) bad = bad || !(fabsf(o[i]) <= 3.0e38f);
                if (__any_sync(~0u, bad)) attn_safe(o, q, head, lane);
                attn_store(o, head, m64, w4, lane);
            }
        }
        nbar_sync(wg + 1, 128);
        if ((tid & 127) == 32) {
            flag_release(C_O + quarter * 8 + 4 + wg);
        }

        TL(6); TLC(13);
        {
            const int nb = idx & 7, jb = idx >> 3;
            const int mbe = (jb >> 2) * 8 + (jb & 3);
            float* supd = reinterpret_cast<float*>(smem + SM_MISC + 512);
            if (warp == 15) nbar_sync(7, 512); else nbar_arrive(7, 512);
            TLX(11, 480);
            if (warp == 15) {
                nbar_arrive(9, 160);
                flag_wait(C_O + mbe + 4, 32);
                fence_proxy_async_all();
                if (lane == 0) {
                    for (int c = 0; c < 2; c++) {
                        mbar_expect_tx(bars + 8 * (B_OA + 2 + c), 32768);
                        tma3d(sbase + SM_KV + 65536 + c * 32768, &maps.o, bars + 8 * (B_OA + 2 + c), (mbe + 4) * 64, c * 4);
                    }
                    exit_ticket();
                }
                __syncwarp();
            }
            const int late = wg >> 1, nh = wg & 1;
            const int mb = mbe + late * 4;
            const int g = lane >> 2, t = lane & 3;
            const int row0 = mb * 64 + w4 * 16 + g;
            const int col0 = nb * 64 + nh * 32 + t * 2;
            uint32_t xv[8], nv[8];
#pragma unroll
            for (int i = 0; i < 4; i++) {
                xv[2 * i] = *reinterpret_cast<const uint32_t*>(x + (size_t)row0 * DM + col0 + i * 8);
                xv[2 * i + 1] = *reinterpret_cast<const uint32_t*>(x + (size_t)(row0 + 8) * DM + col0 + i * 8);
                nv[2 * i] = __ldcg(reinterpret_cast<const uint32_t*>(g_xn + (size_t)row0 * DM + col0 + i * 8));
                nv[2 * i + 1] = __ldcg(reinterpret_cast<const uint32_t*>(g_xn + (size_t)(row0 + 8) * DM + col0 + i * 8));
            }
            if (wg == 0) {
                nbar_sync(9, 160);
                const int which = tid >> 6, col = nb * 64 + (tid & 63);
                const float y = __ldcg(&g_ypart[which * 512 + col]) + __ldcg(&g_ypart[1024 + which * 512 + col]) +
                                __ldcg(&g_ypart[2048 + which * 512 + col]) + __ldcg(&g_ypart[3072 + which * 512 + col]);
                supd[tid] = bfr(bfr(y) * __ldcg(&g_gate[which]));
                if (tid < 2) reinterpret_cast<int*>(supd + 128)[tid] = __ldcg(&g_sel[tid]);
            }
            float acc[16];
#pragma unroll
            for (int i = 0; i < 16; i++) acc[i] = 0.f;
            mbar_wait(bars + 8 * B_WO, 0);
            const uint32_t abase = sbase + SM_KV + late * 65536;
#pragma unroll 1
            for (int c = 0; c < 8; c++) {
                if ((c & 3) == 0) mbar_wait(bars + 8 * (B_OA + late * 2 + (c >> 2)), 0);
                if (c == 0) TLX(7, 256);
                const uint64_t da = mkdesc(abase + c * 8192, 16, 1024, 1);
                const uint64_t db = mkdesc(sbase + SM_WO + c * 8192 + nh * 64, 8192, 1024, 1);
                WG_FENCE();
#pragma unroll
                for (int k = 0; k < 4; k++) wgmma_n32(acc, da + k * 2, db + k * 128, (c | k) != 0);
                WG_COMMIT();
            }
            TLX(14, 256);
            __syncthreads();
            TLX(15, 256);
            const int sel0 = reinterpret_cast<const int*>(supd + 128)[0], sel1 = reinterpret_cast<const int*>(supd + 128)[1];
            WG_WAIT(0);
            TLX(8, 256);
#pragma unroll
            for (int h = 0; h < 2; h++) {
                const int row = row0 + h * 8;
                const int which = row == sel0 ? 0 : (row == sel1 ? 1 : -1);
#pragma unroll
                for (int i = 0; i < 4; i++) {
                    const int col = col0 + i * 8;
                    float b0 = bf_lo(nv[2 * i + h]), b1 = bf_hi(nv[2 * i + h]);
                    if (which >= 0) {
                        b0 = bfr(b0 + supd[which * 64 + col - nb * 64]); b1 = bfr(b1 + supd[which * 64 + col + 1 - nb * 64]);
                    }
                    const float t0 = bfr(bf_lo(xv[2 * i + h]) + bfr(acc[4 * i + 2 * h]));
                    const float t1 = bfr(bf_hi(xv[2 * i + h]) + bfr(acc[4 * i + 2 * h + 1]));
                    *reinterpret_cast<uint32_t*>(out + (size_t)row * DM + col) = packbf(t0 + b0, t1 + b1);
                }
            }
        }
        TLX(9, 256);
    }
}

typedef CUresult (*EncodeFn)(CUtensorMap*, CUtensorMapDataType, cuuint32_t, void*, const cuuint64_t*, const cuuint64_t*,
                             const cuuint32_t*, const cuuint32_t*, CUtensorMapInterleave, CUtensorMapSwizzle,
                             CUtensorMapL2promotion, CUtensorMapFloatOOBfill);

void make_map(EncodeFn fn, CUtensorMap* m, const void* ptr, uint64_t cols, uint64_t rows, uint32_t box_rows, uint32_t box_chunks) {
    cuuint64_t dims[3] = {64, rows, cols / 64};
    cuuint64_t strides[2] = {cols * 2, 128};
    cuuint32_t box[3] = {64, box_rows, box_chunks};
    cuuint32_t es[3] = {1, 1, 1};
    fn(m, CU_TENSOR_MAP_DATA_TYPE_BFLOAT16, 3, const_cast<void*>(ptr), dims, strides, box, es, CU_TENSOR_MAP_INTERLEAVE_NONE,
       CU_TENSOR_MAP_SWIZZLE_128B, CU_TENSOR_MAP_L2_PROMOTION_L2_256B, CU_TENSOR_MAP_FLOAT_OOB_FILL_NONE);
}

}

extern "C" void kernel_launch(void* const* d_in, const int* in_sizes, int n_in, void* d_out, int out_size) {
    const __nv_bfloat16* x = (const __nv_bfloat16*)d_in[0];
    const __nv_bfloat16* wqkv = (const __nv_bfloat16*)d_in[1];
    const __nv_bfloat16* wo = (const __nv_bfloat16*)d_in[2];
    const __nv_bfloat16* wr = (const __nv_bfloat16*)d_in[4];
    const __nv_bfloat16* wgate = (const __nv_bfloat16*)d_in[5];
    const __nv_bfloat16* wup = (const __nv_bfloat16*)d_in[6];
    const __nv_bfloat16* wdown = (const __nv_bfloat16*)d_in[7];
    __nv_bfloat16* out = (__nv_bfloat16*)d_out;

    static EncodeFn enc = nullptr;
    static void* p_xn = nullptr; static void* p_o = nullptr;
    if (!enc) {
        void* fn = nullptr; cudaDriverEntryPointQueryResult qr;
        cudaGetDriverEntryPoint("cuTensorMapEncodeTiled", &fn, cudaEnableDefault, &qr);
        enc = (EncodeFn)fn;
        cudaGetSymbolAddress(&p_xn, g_xn);
        cudaGetSymbolAddress(&p_o, g_o);
        cudaFuncSetAttribute(fused_kernel, cudaFuncAttributeMaxDynamicSharedMemorySize, FUSED_SMEM);
    }
    Maps maps;
    make_map(enc, &maps.g, wgate, FF, DM, 16, 7);
    make_map(enc, &maps.u, wup, FF, DM, 16, 7);
    make_map(enc, &maps.d, wdown, DM, FF, 32, 8);
    make_map(enc, &maps.xn, p_xn, DM, S_LEN, 128, 1);
    make_map(enc, &maps.wqkv, wqkv, 3 * DM, DM, 64, 3);
    make_map(enc, &maps.o, p_o, DM, S_LEN, 64, 4);
    make_map(enc, &maps.wo, wo, DM, DM, 256, 1);

    union { uint32_t u; float f; } scu; scu.u = 128u;

    cudaLaunchConfig_t cfg = {};
    cfg.gridDim = dim3(132); cfg.blockDim = dim3(512); cfg.dynamicSmemBytes = FUSED_SMEM; cfg.stream = cudaStreamPerThread;
    cudaLaunchKernelEx(&cfg, fused_kernel, maps, x, wr, out, scu.f);
}
```

```cpp
#include <cuda_runtime.h>
#include <cuda_bf16.h>
#include <cuda.h>
#include <stdint.h>
#include <type_traits>

namespace {

constexpr int S_LEN = 2048;
constexpr int DM = 512;
constexpr int NH = 32;
constexpr int FF = 1792;

__device__ __align__(1024) __nv_bfloat16 g_xn[S_LEN * DM];
__device__ __align__(16) float g_r[S_LEN];
__device__ __align__(1024) uint32_t g_qkv[NH * 8 * 6144];
__device__ __align__(1024) __nv_bfloat16 g_o[S_LEN * DM];
__device__ __align__(16) float g_ypart[4 * 2 * DM];
__device__ int g_sel[2];
__device__ float g_gate[2];
constexpr int C_LN = 0, C_QKV = 16, C_O = 24, C_FFN = 56, C_EXIT = 57, C_NUM = 58;
__device__ unsigned g_cnt[C_NUM * 32];

#define TLC(slot) do {} while (0)
#define TL(slot) do {} while (0)
#define TLX(slot, th) do {} while (0)

__device__ __forceinline__ uint32_t smem_u32(const void* p) { return (uint32_t)__cvta_generic_to_shared(p); }
__device__ __forceinline__ void warp_arrive(int idx) {
    __syncwarp();
    if ((threadIdx.x & 31) == 0)
        asm volatile("red.release.gpu.global.add.u32 [%0], 1;" :: "l"(g_cnt + idx * 32) : "memory");
}
__device__ __forceinline__ void flag_release(int idx) {
    asm volatile("red.release.gpu.global.add.u32 [%0], 1;" :: "l"(g_cnt + idx * 32) : "memory");
}
__device__ __forceinline__ void exit_ticket() {
    unsigned tk;
    asm volatile("atom.relaxed.gpu.global.add.u32 %0, [%1], 1;" : "=r"(tk) : "l"(g_cnt + C_EXIT * 32) : "memory");
    if (tk == gridDim.x - 1) {
#pragma unroll 1
        for (int i = 0; i < C_NUM; i++) g_cnt[i * 32] = 0u;
    }
}
__device__ __forceinline__ void nbar_arrive(int id, int cnt) { asm volatile("bar.arrive %0, %1;" :: "r"(id), "r"(cnt) : "memory"); }
__device__ __forceinline__ void nbar_sync(int id, int cnt) { asm volatile("bar.sync %0, %1;" :: "r"(id), "r"(cnt) : "memory"); }
__device__ __forceinline__ void flag_wait(int idx, unsigned target) {
    asm volatile("{\n.reg .pred p;\n.reg .u32 n, v;\nmov.u32 n, 0;\n"
                 "FW_%=:\n"
                 "ld.acquire.gpu.global.u32 v, [%0];\n"
                 "setp.ge.u32 p, v, %1;\n"
                 "@p bra FD_%=;\n"
                 "add.u32 n, n, 1;\n"
                 "setp.lt.u32 p, n, 16000000;\n"
                 "@p bra FW_%=;\n"
                 "trap;\n"
                 "FD_%=:\n}"
                 :: "l"(g_cnt + idx * 32), "r"(target) : "memory");
}
__device__ __forceinline__ void flag_wait_all(int idx, unsigned target) {
    asm volatile("{\n.reg .pred p;\n.reg .u32 n, v;\nmov.u32 n, 0;\n"
                 "FW_%=:\n"
                 "ld.acquire.gpu.global.u32 v, [%0];\n"
                 "setp.ge.u32 p, v, %1;\n"
                 "vote.sync.all.pred p, p, 0xffffffff;\n"
                 "@p bra.uni FD_%=;\n"
                 "add.u32 n, n, 1;\n"
                 "setp.lt.u32 p, n, 16000000;\n"
                 "@p bra.uni FW_%=;\n"
                 "trap;\n"
                 "FD_%=:\n}"
                 :: "l"(g_cnt + idx * 32), "r"(target) : "memory");
}
__device__ __forceinline__ void fence_proxy_async_all() { asm volatile("fence.proxy.async.global;" ::: "memory"); }
__device__ __forceinline__ void mbar_init(uint32_t bar, uint32_t cnt) {
    asm volatile("mbarrier.init.shared::cta.b64 [%0], %1;" :: "r"(bar), "r"(cnt) : "memory");
}
__device__ __forceinline__ void mbar_expect_tx(uint32_t bar, uint32_t bytes) {
    asm volatile("mbarrier.arrive.expect_tx.shared::cta.b64 _, [%0], %1;" :: "r"(bar), "r"(bytes) : "memory");
}
__device__ __forceinline__ void mbar_arrive(uint32_t bar) {
    asm volatile("mbarrier.arrive.shared::cta.b64 _, [%0];" :: "r"(bar) : "memory");
}
__device__ __forceinline__ void mbar_wait(uint32_t bar, uint32_t parity) {
    asm volatile("{\n.reg .pred p;\n.reg .u32 n;\nmov.u32 n, 0;\n"
                 "WAIT_%=:\n"
                 "mbarrier.try_wait.parity.shared::cta.b64 p, [%0], %1;\n"
                 "@p bra DONE_%=;\n"
                 "add.u32 n, n, 1;\n"
                 "setp.lt.u32 p, n, 4000000;\n"
                 "@p bra WAIT_%=;\n"
                 "trap;\n"
                 "DONE_%=:\n}"
                 :: "r"(bar), "r"(parity) : "memory");
}
__device__ __forceinline__ void fence_barrier_init() { asm volatile("fence.mbarrier_init.release.cluster;" ::: "memory"); }
__device__ __forceinline__ void fence_proxy_async() { asm volatile("fence.proxy.async.shared::cta;" ::: "memory"); }
__device__ __forceinline__ void tma3d(uint32_t dst, const CUtensorMap* map, uint32_t bar, int row, int chunk) {
    asm volatile("cp.async.bulk.tensor.3d.shared::cluster.global.mbarrier::complete_tx::bytes [%0], [%1, {%3, %4, %5}], [%2];"
                 :: "r"(dst), "l"((uint64_t)map), "r"(bar), "r"(0), "r"(row), "r"(chunk) : "memory");
}
__device__ __forceinline__ void bulk_g2s(uint32_t dst, const void* src, uint32_t bytes, uint32_t bar) {
    asm volatile("cp.async.bulk.shared::cluster.global.mbarrier::complete_tx::bytes [%0], [%1], %2, [%3];"
                 :: "r"(dst), "l"((uint64_t)src), "r"(bytes), "r"(bar) : "memory");
}
__device__ __forceinline__ void l2_prefetch(const void* src, uint32_t bytes) {
    asm volatile("cp.async.bulk.prefetch.L2.global [%0], %1;" :: "l"((uint64_t)src), "r"(bytes) : "memory");
}
__device__ __forceinline__ void map_prefetch(const CUtensorMap* m) {
    asm volatile("prefetch.tensormap [%0];" :: "l"((uint64_t)m) : "memory");
}
__device__ __forceinline__ uint64_t mkdesc(uint32_t addr, uint32_t lbo, uint32_t sbo, uint32_t swz) {
    return (uint64_t)((addr & 0x3FFFF) >> 4) | ((uint64_t)(lbo >> 4) << 16) | ((uint64_t)(sbo >> 4) << 32) | ((uint64_t)swz << 62);
}
#define WG_FENCE() asm volatile("wgmma.fence.sync.aligned;" ::: "memory")
#define WG_COMMIT() asm volatile("wgmma.commit_group.sync.aligned;" ::: "memory")
#define WG_WAIT(n) asm volatile("wgmma.wait_group.sync.aligned %0;" :: "n"(n) : "memory")

__device__ __forceinline__ float ex2(float x) { float y; asm("ex2.approx.ftz.f32 %0, %1;" : "=f"(y) : "f"(x)); return y; }
__device__ __forceinline__ uint32_t packbf(float lo, float hi) {
    uint32_t r; asm("cvt.rn.bf16x2.f32 %0, %1, %2;" : "=r"(r) : "f"(hi), "f"(lo)); return r;
}
__device__ __forceinline__ uint32_t hmul2bf(uint32_t a, uint32_t b) { uint32_t r; asm("mul.rn.bf16x2 %0, %1, %2;" : "=r"(r) : "r"(a), "r"(b)); return r; }
__device__ __forceinline__ float bf_lo(uint32_t v) { return __uint_as_float(v << 16); }
__device__ __forceinline__ float bf_hi(uint32_t v) { return __uint_as_float(v & 0xffff0000u); }
__device__ __forceinline__ float bfr(float x) { return __bfloat162float(__float2bfloat16_rn(x)); }

__device__ __forceinline__ void wgmma_n192(float (&d)[96], uint64_t da, uint64_t db, int scale_d) {
    asm volatile("{\n.reg .pred p;\nsetp.ne.b32 p, %98, 0;\n"
        "wgmma.mma_async.sync.aligned.m64n192k16.f32.bf16.bf16 "
        "{%0,%1,%2,%3,%4,%5,%6,%7,%8,%9,%10,%11,%12,%13,%14,%15,%16,%17,%18,%19,%20,%21,%22,%23,"
        "%24,%25,%26,%27,%28,%29,%30,%31,%32,%33,%34,%35,%36,%37,%38,%39,%40,%41,%42,%43,%44,%45,%46,%47,"
        "%48,%49,%50,%51,%52,%53,%54,%55,%56,%57,%58,%59,%60,%61,%62,%63,%64,%65,%66,%67,%68,%69,%70,%71,"
        "%72,%73,%74,%75,%76,%77,%78,%79,%80,%81,%82,%83,%84,%85,%86,%87,%88,%89,%90,%91,%92,%93,%94,%95}, "
        "%96, %97, p, 1, 1, 0, 1;\n}"
        : "+f"(d[0]), "+f"(d[1]), "+f"(d[2]), "+f"(d[3]), "+f"(d[4]), "+f"(d[5]), "+f"(d[6]), "+f"(d[7]),
          "+f"(d[8]), "+f"(d[9]), "+f"(d[10]), "+f"(d[11]), "+f"(d[12]), "+f"(d[13]), "+f"(d[14]), "+f"(d[15]),
          "+f"(d[16]), "+f"(d[17]), "+f"(d[18]), "+f"(d[19]), "+f"(d[20]), "+f"(d[21]), "+f"(d[22]), "+f"(d[23]),
          "+f"(d[24]), "+f"(d[25]), "+f"(d[26]), "+f"(d[27]), "+f"(d[28]), "+f"(d[29]), "+f"(d[30]), "+f"(d[31]),
          "+f"(d[32]), "+f"(d[33]), "+f"(d[34]), "+f"(d[35]), "+f"(d[36]), "+f"(d[37]), "+f"(d[38]), "+f"(d[39]),
          "+f"(d[40]), "+f"(d[41]), "+f"(d[42]), "+f"(d[43]), "+f"(d[44]), "+f"(d[45]), "+f"(d[46]), "+f"(d[47]),
          "+f"(d[48]), "+f"(d[49]), "+f"(d[50]), "+f"(d[51]), "+f"(d[52]), "+f"(d[53]), "+f"(d[54]), "+f"(d[55]),
          "+f"(d[56]), "+f"(d[57]), "+f"(d[58]), "+f"(d[59]), "+f"(d[60]), "+f"(d[61]), "+f"(d[62]), "+f"(d[63]),
          "+f"(d[64]), "+f"(d[65]), "+f"(d[66]), "+f"(d[67]), "+f"(d[68]), "+f"(d[69]), "+f"(d[70]), "+f"(d[71]),
          "+f"(d[72]), "+f"(d[73]), "+f"(d[74]), "+f"(d[75]), "+f"(d[76]), "+f"(d[77]), "+f"(d[78]), "+f"(d[79]),
          "+f"(d[80]), "+f"(d[81]), "+f"(d[82]), "+f"(d[83]), "+f"(d[84]), "+f"(d[85]), "+f"(d[86]), "+f"(d[87]),
          "+f"(d[88]), "+f"(d[89]), "+f"(d[90]), "+f"(d[91]), "+f"(d[92]), "+f"(d[93]), "+f"(d[94]), "+f"(d[95])
        : "l"(da), "l"(db), "r"(scale_d));
}

constexpr float SHIFT = 90.0f;
constexpr float QS = 0.25f * 1.4426950408889634f * 18446744073709551616.0f;
constexpr float scq = 0.25f * 1.4426950408889634f * 3.3087224502121107e-24f;

__device__ __forceinline__ uint32_t polyexp(float lo, float hi) {
    uint32_t w, g, q, h;
    asm("cvt.pack.sat.s16.s32 %0, %1, %2;" : "=r"(w) : "r"(__float_as_uint(hi)), "r"(__float_as_uint(lo)));
    g = w & 0x007F007Fu;
    asm("fma.rn.f16x2 %0, %1, %2, %3;" : "=r"(q) : "r"(g), "r"(0xf940f940u), "r"(0x35513551u));
    asm("mul.rn.f16x2 %0, %1, %2;" : "=r"(h) : "r"(q), "r"(g));
    return w - h;
}
__device__ __forceinline__ void qk64(float (&s)[32], const uint32_t (&q)[4], uint64_t db) {
    asm volatile("wgmma.mma_async.sync.aligned.m64n64k16.f32.bf16.bf16 "
        "{%0,%1,%2,%3,%4,%5,%6,%7,%8,%9,%10,%11,%12,%13,%14,%15,%16,%17,%18,%19,%20,%21,%22,%23,%24,%25,%26,%27,%28,%29,%30,%31}, "
        "{%32,%33,%34,%35}, %36, 0, 1, 1, 0;"
        : "=f"(s[0]), "=f"(s[1]), "=f"(s[2]), "=f"(s[3]), "=f"(s[4]), "=f"(s[5]), "=f"(s[6]), "=f"(s[7]),
          "=f"(s[8]), "=f"(s[9]), "=f"(s[10]), "=f"(s[11]), "=f"(s[12]), "=f"(s[13]), "=f"(s[14]), "=f"(s[15]),
          "=f"(s[16]), "=f"(s[17]), "=f"(s[18]), "=f"(s[19]), "=f"(s[20]), "=f"(s[21]), "=f"(s[22]), "=f"(s[23]),
          "=f"(s[24]), "=f"(s[25]), "=f"(s[26]), "=f"(s[27]), "=f"(s[28]), "=f"(s[29]), "=f"(s[30]), "=f"(s[31])
        : "r"(q[0]), "r"(q[1]), "r"(q[2]), "r"(q[3]), "l"(db));
}
__device__ __forceinline__ void pv24(float (&o)[12], uint32_t a0, uint32_t a1, uint32_t a2, uint32_t a3, uint64_t db) {
    asm volatile("wgmma.mma_async.sync.aligned.m64n24k16.f32.bf16.bf16 "
        "{%0,%1,%2,%3,%4,%5,%6,%7,%8,%9,%10,%11}, {%12,%13,%14,%15}, %16, 1, 1, 1, 1;"
        : "+f"(o[0]), "+f"(o[1]), "+f"(o[2]), "+f"(o[3]), "+f"(o[4]), "+f"(o[5]), "+f"(o[6]), "+f"(o[7]),
          "+f"(o[8]), "+f"(o[9]), "+f"(o[10]), "+f"(o[11])
        : "r"(a0), "r"(a1), "r"(a2), "r"(a3), "l"(db));
}

__device__ __forceinline__ void mma_full(float (&d)[4], uint32_t a0, uint32_t a1, uint32_t a2, uint32_t a3, uint32_t b0, uint32_t b1) {
    asm volatile("mma.sync.aligned.m16n8k16.row.col.f32.bf16.bf16.f32 {%0,%1,%2,%3}, {%4,%5,%6,%7}, {%8,%9}, {%0,%1,%2,%3};"
                 : "+f"(d[0]), "+f"(d[1]), "+f"(d[2]), "+f"(d[3]) : "r"(a0), "r"(a1), "r"(a2), "r"(a3), "r"(b0), "r"(b1));
}
__device__ __forceinline__ uint32_t movt(uint32_t a) {
    uint32_t r; asm volatile("movmatrix.sync.aligned.m8n8.trans.b16 %0, %1;" : "=r"(r) : "r"(a)); return r;
}
__device__ __noinline__ void attn_safe(float* o_out, const uint32_t* qf, int head, int lane) {
    float o0[4] = {0.f, 0.f, 0.f, 0.f}, o1[4] = {0.f, 0.f, 0.f, 0.f};
    float m0 = -INFINITY, m1 = -INFINITY, l0 = 0.f, l1 = 0.f;
    const uint32_t q0 = qf[0], q1 = qf[1], q2 = qf[2], q3 = qf[3];
#pragma unroll 1
    for (int kb = 0; kb < 128; kb++) {
        const uint32_t* src = g_qkv + head * 49152 + (kb >> 4) * 6144 + (kb & 15) * 64 + lane;
        float sa[4] = {0.f, 0.f, 0.f, 0.f}, sb[4] = {0.f, 0.f, 0.f, 0.f};
        mma_full(sa, q0, q1, q2, q3, __ldcg(src), __ldcg(src + 1024));
        mma_full(sb, q0, q1, q2, q3, __ldcg(src + 32), __ldcg(src + 1024 + 32));
        float n0 = fmaxf(fmaxf(m0, fmaxf(sa[0], sa[1])), fmaxf(sb[0], sb[1]));
        float n1 = fmaxf(fmaxf(m1, fmaxf(sa[2], sa[3])), fmaxf(sb[2], sb[3]));
        n0 = fmaxf(n0, __shfl_xor_sync(~0u, n0, 1)); n0 = fmaxf(n0, __shfl_xor_sync(~0u, n0, 2));
        n1 = fmaxf(n1, __shfl_xor_sync(~0u, n1, 1)); n1 = fmaxf(n1, __shfl_xor_sync(~0u, n1, 2));
        const float c0 = ex2((m0 - n0) * QS), c1 = ex2((m1 - n1) * QS);
        m0 = n0; m1 = n1;
        const uint32_t p0 = packbf(ex2((sa[0] - m0) * QS), ex2((sa[1] - m0) * QS));
        const uint32_t p1 = packbf(ex2((sa[2] - m1) * QS), ex2((sa[3] - m1) * QS));
        const uint32_t p2 = packbf(ex2((sb[0] - m0) * QS), ex2((sb[1] - m0) * QS));
        const uint32_t p3 = packbf(ex2((sb[2] - m1) * QS), ex2((sb[3] - m1) * QS));
        l0 = l0 * c0 + (bf_lo(p0) + bf_hi(p0)) + (bf_lo(p2) + bf_hi(p2));
        l1 = l1 * c1 + (bf_lo(p1) + bf_hi(p1)) + (bf_lo(p3) + bf_hi(p3));
        o0[0] *= c0; o0[1] *= c0; o0[2] *= c1; o0[3] *= c1;
        o1[0] *= c0; o1[1] *= c0; o1[2] *= c1; o1[3] *= c1;
        mma_full(o0, p0, p1, p2, p3, movt(__ldcg(src + 2048)), movt(__ldcg(src + 2048 + 32)));
        mma_full(o1, p0, p1, p2, p3, movt(__ldcg(src + 3072)), movt(__ldcg(src + 3072 + 32)));
    }
    l0 += __shfl_xor_sync(~0u, l0, 1); l0 += __shfl_xor_sync(~0u, l0, 2);
    l1 += __shfl_xor_sync(~0u, l1, 1); l1 += __shfl_xor_sync(~0u, l1, 2);
#pragma unroll
    for (int i = 0; i < 4; i++) { o_out[i] = o0[i]; o_out[4 + i] = o1[i]; }
    o_out[8] = o_out[9] = l0; o_out[10] = o_out[11] = l1;
}

__device__ __forceinline__ void load_q(uint32_t (&q)[4], int head, int mt, int lane) {
    const uint32_t* src = g_qkv + head * 49152 + (mt >> 4) * 6144 + 4096 + (mt & 15) * 64 + lane;
    q[0] = __ldcg(src); q[1] = __ldcg(src + 32); q[2] = __ldcg(src + 1024); q[3] = __ldcg(src + 1024 + 32);
}
__device__ __forceinline__ void attn_store(const float (&o)[12], int head, int m64, int warp, int lane) {
    const int g = lane >> 2, t = lane & 3;
    const int row = m64 * 64 + warp * 16 + g;
    const float i0 = 1.f / o[8], i1 = 1.f / o[10];
    uint32_t* p0 = reinterpret_cast<uint32_t*>(g_o + (size_t)row * DM + head * 16 + t * 2);
    uint32_t* p1 = reinterpret_cast<uint32_t*>(g_o + (size_t)(row + 8) * DM + head * 16 + t * 2);
    p0[0] = packbf(o[0] * i0, o[1] * i0); p0[4] = packbf(o[4] * i0, o[5] * i0);
    p1[0] = packbf(o[2] * i1, o[3] * i1); p1[4] = packbf(o[6] * i1, o[7] * i1);
}

constexpr int FS_N = 4;
constexpr int FS_BYTES = 32768;
__device__ __forceinline__ void ldsm4t(uint32_t& r0, uint32_t& r1, uint32_t& r2, uint32_t& r3, uint32_t addr) {
    asm volatile("ldmatrix.sync.aligned.m8n8.x4.trans.shared.b16 {%0,%1,%2,%3}, [%4];" : "=r"(r0), "=r"(r1), "=r"(r2), "=r"(r3) : "r"(addr) : "memory");
}
__device__ __forceinline__ void mma16816(float (&d)[4], uint32_t a0, uint32_t a2, uint32_t b0, uint32_t b1) {
    asm volatile("mma.sync.aligned.m16n8k16.row.col.f32.bf16.bf16.f32 {%0,%1,%2,%3}, {%4,%5,%6,%5}, {%7,%8}, {%0,%1,%2,%3};"
                 : "+f"(d[0]), "+f"(d[1]), "+f"(d[2]), "+f"(d[3]) : "r"(a0), "r"(0u), "r"(a2), "r"(b0), "r"(b1));
}
__device__ void ffn_block(int c, uint8_t* smem, uint32_t sbase, const CUtensorMap* mapG, const CUtensorMap* mapU, const CUtensorMap* mapD) {
    const int tid = threadIdx.x, warp = tid >> 5, lane = tid & 31;
    uint32_t* sx = reinterpret_cast<uint32_t*>(smem + FS_N * FS_BYTES);
    __nv_bfloat16* sh = reinterpret_cast<__nv_bfloat16*>(sx + 512);
    const uint32_t bars = sbase + FS_N * FS_BYTES + 8192;
    float* tv = reinterpret_cast<float*>(smem + FS_N * FS_BYTES + 4096);
    int* ti = reinterpret_cast<int*>(tv + 32);
    int* ssel = ti + 32;
    auto issue = [&](int item) {
        const int slot = item % FS_N;
        const uint32_t dst = sbase + slot * FS_BYTES, bar = bars + 8 * slot;
        mbar_expect_tx(bar, item < 32 ? 28672 : 32768);
        if (item < 32) {
            tma3d(dst, mapG, bar, item * 16, c * 7);
            tma3d(dst + 14336, mapU, bar, item * 16, c * 7);
        } else {
            tma3d(dst, mapD, bar, c * 448 + (item - 32) * 32, 0);
        }
    };
    if (tid == 0) {
        for (int i = 0; i < FS_N; i++) mbar_init(bars + 8 * i, 1);
        fence_barrier_init();
        for (int i = 0; i < FS_N; i++) issue(i);
    }
    flag_wait(C_LN + warp, 8);
    __syncthreads();
    float b1 = -INFINITY, b2 = -INFINITY; int i1 = 0x7fffffff, i2 = 0x7fffffff;
    auto push = [&](float v, int i) {
        if (v > b1 || (v == b1 && i < i1)) { b2 = b1; i2 = i1; b1 = v; i1 = i; }
        else if (v > b2 || (v == b2 && i < i2)) { b2 = v; i2 = i; }
    };
    {
        const float4 rv = __ldcg(reinterpret_cast<const float4*>(g_r) + tid);
        push(rv.x, 4 * tid); push(rv.y, 4 * tid + 1); push(rv.z, 4 * tid + 2); push(rv.w, 4 * tid + 3);
    }
#pragma unroll
    for (int o = 16; o > 0; o >>= 1) {
        float v1 = __shfl_xor_sync(~0u, b1, o), v2 = __shfl_xor_sync(~0u, b2, o);
        int j1 = __shfl_xor_sync(~0u, i1, o), j2 = __shfl_xor_sync(~0u, i2, o);
        push(v1, j1); push(v2, j2);
    }
    if (lane == 0) { tv[2 * warp] = b1; ti[2 * warp] = i1; tv[2 * warp + 1] = b2; ti[2 * warp + 1] = i2; }
    __syncthreads();
    if (warp == 1) {
        b1 = tv[lane]; i1 = ti[lane]; b2 = -INFINITY; i2 = 0x7fffffff;
#pragma unroll
        for (int o = 16; o > 0; o >>= 1) {
            float v1 = __shfl_xor_sync(~0u, b1, o), v2 = __shfl_xor_sync(~0u, b2, o);
            int j1 = __shfl_xor_sync(~0u, i1, o), j2 = __shfl_xor_sync(~0u, i2, o);
            push(v1, j1); push(v2, j2);
        }
        if (lane == 0) {
            i1 = min(max(i1, 0), S_LEN - 1); i2 = min(max(i2, 0), S_LEN - 1);
            ssel[0] = i1; ssel[1] = i2;
            if (c == 0) {
                g_sel[0] = i1; g_sel[1] = i2;
                g_gate[0] = bfr(1.f / (1.f + __expf(-bfr(b1))));
                g_gate[1] = bfr(1.f / (1.f + __expf(-bfr(b2))));
            }
        }
    }
    __syncthreads();
    sx[tid] = __ldcg(reinterpret_cast<const uint32_t*>(g_xn + (size_t)ssel[tid >> 8] * DM + (tid & 255) * 2));
    __syncthreads();
    TL(1);
    const int g = lane >> 2, t = lane & 3;
    const int lrow = lane & 15, lsel = lane >> 4;
    {
        float ag[4][4], au[4][4];
#pragma unroll
        for (int j = 0; j < 4; j++) { ag[j][0] = ag[j][1] = ag[j][2] = ag[j][3] = 0.f; au[j][0] = au[j][1] = au[j][2] = au[j][3] = 0.f; }
#pragma unroll 1
        for (int it = 0; it < 32; it++) {
            const int slot = it % FS_N;
            const uint32_t a0 = g < 2 ? sx[g * 256 + it * 8 + t] : 0u, a2 = g < 2 ? sx[g * 256 + it * 8 + 4 + t] : 0u;
            mbar_wait(bars + 8 * slot, (it / FS_N) & 1);
            const uint32_t base = sbase + slot * FS_BYTES + lsel * 14336 + lrow * 128;
#pragma unroll
            for (int j = 0; j < 4; j++) {
                const int nt = warp + j * 16;
                if (nt < 56) {
                    uint32_t b0, b1, b2, b3;
                    ldsm4t(b0, b1, b2, b3, base + (nt >> 3) * 2048 + (((nt & 7) ^ (lrow & 7)) << 4));
                    mma16816(ag[j], a0, a2, b0, b1);
                    mma16816(au[j], a0, a2, b2, b3);
                }
            }
            __syncthreads();
            if (tid == 480) issue(it + FS_N);
        }
        if (g < 2) {
#pragma unroll
            for (int j = 0; j < 4; j++) {
                const int nt = warp + j * 16;
                if (nt < 56) {
#pragma unroll
                    for (int e = 0; e < 2; e++) {
                        const float gs = bfr(ag[j][e]), us = bfr(au[j][e]);
                        const float sg = bfr(gs / (1.f + __expf(-gs)));
                        sh[g * 448 + nt * 8 + t * 2 + e] = __float2bfloat16_rn(sg * us);
                    }
                }
            }
        }
        __syncthreads();
    }
    TL(2);
    {
        const uint32_t* shw = reinterpret_cast<const uint32_t*>(sh);
        float a[4][4];
#pragma unroll
        for (int j = 0; j < 4; j++) a[j][0] = a[j][1] = a[j][2] = a[j][3] = 0.f;
#pragma unroll 1
        for (int it = 32; it < 46; it++) {
            const int slot = it % FS_N;
            uint32_t af[4];
#pragma unroll
            for (int q = 0; q < 4; q++) af[q] = g < 2 ? shw[g * 224 + (it - 32) * 16 + q * 4 + t] : 0u;
            mbar_wait(bars + 8 * slot, (it / FS_N) & 1);
            const uint32_t base = sbase + slot * FS_BYTES + (warp >> 1) * 4096 + lane * 128;
#pragma unroll
            for (int j = 0; j < 4; j++) {
                const int u = (warp & 1) * 4 + j;
                uint32_t b0, b1, b2, b3;
                ldsm4t(b0, b1, b2, b3, base + ((u ^ (lane & 7)) << 4));
                mma16816(a[j], af[0], af[1], b0, b1);
                mma16816(a[j], af[2], af[3], b2, b3);
            }
            __syncthreads();
            if (tid == 480 && it + FS_N < 46) issue(it + FS_N);
        }
        if (g < 2) {
#pragma unroll
            for (int j = 0; j < 4; j++)
                *reinterpret_cast<float2*>(&g_ypart[c * 1024 + g * 512 + (warp * 4 + j) * 8 + t * 2]) = make_float2(a[j][0], a[j][1]);
        }
    }
    warp_arrive(C_FFN);
}

__device__ __forceinline__ void wgmma_n32(float (&d)[16], uint64_t da, uint64_t db, int scale_d) {
    asm volatile("{\n.reg .pred p;\nsetp.ne.b32 p, %18, 0;\n"
        "wgmma.mma_async.sync.aligned.m64n32k16.f32.bf16.bf16 "
        "{%0,%1,%2,%3,%4,%5,%6,%7,%8,%9,%10,%11,%12,%13,%14,%15}, "
        "%16, %17, p, 1, 1, 0, 1;\n}"
        : "+f"(d[0]), "+f"(d[1]), "+f"(d[2]), "+f"(d[3]), "+f"(d[4]), "+f"(d[5]), "+f"(d[6]), "+f"(d[7]),
          "+f"(d[8]), "+f"(d[9]), "+f"(d[10]), "+f"(d[11]), "+f"(d[12]), "+f"(d[13]), "+f"(d[14]), "+f"(d[15])
        : "l"(da), "l"(db), "r"(scale_d));
}

constexpr int G_ST = 4;
constexpr int G_STAGE = 16384 + 24576;
constexpr int SM_KV = 0, KV_CH = 20480, SM_WO = 163840, SM_MISC = 229376;
constexpr int FUSED_SMEM = SM_MISC + 2048;
constexpr int B_FULL = 0, B_EMPTY = 4, B_KV = 8, B_WO = 16, B_OA = 18, B_NUM = 22;

struct Maps { CUtensorMap xn, wqkv, o, wo, g, u, d; };

__global__ void __launch_bounds__(512, 1) fused_kernel(const __grid_constant__ Maps maps, const __nv_bfloat16* __restrict__ x,
                                                       const __nv_bfloat16* __restrict__ wr, __nv_bfloat16* __restrict__ out, float sc) {
    extern __shared__ __align__(1024) uint8_t smem[];
    const uint32_t sbase = smem_u32(smem);
    const int tid = threadIdx.x, warp = __shfl_sync(~0u, tid >> 5, 0), lane = tid & 31;
    const uint32_t bars = sbase + SM_MISC;
    TL(0);
    if (sbase & 1023u) __trap();
    if (blockIdx.x < 4) {
        ffn_block(blockIdx.x, smem, sbase, &maps.g, &maps.u, &maps.d);
        __syncthreads();
        if (tid == 0) exit_ticket();
        TL(3);
    } else {
        const int idx = blockIdx.x - 4;
        const int wg = warp >> 2;
        {
            const int row = idx * 16 + warp;
            const uint4* xr = reinterpret_cast<const uint4*>(x + (size_t)row * DM);
            const uint4 a = xr[lane], b = xr[32 + lane];
            const uint4* wp = reinterpret_cast<const uint4*>(wr);
            const uint4 wa = wp[lane], wb = wp[32 + lane];
            if (tid == 480) {
                for (int s = 0; s < G_ST; s++) { mbar_init(bars + 8 * (B_FULL + s), 2); mbar_init(bars + 8 * (B_EMPTY + s), 2); }
                for (int c = B_KV; c < B_NUM; c++) mbar_init(bars + 8 * c, 1);
                fence_barrier_init();
                for (int c = 0; c < G_ST; c++) {
                    mbar_expect_tx(bars + 8 * (B_FULL + c), 24576);
                    tma3d(sbase + c * G_STAGE + 16384, &maps.wqkv, bars + 8 * (B_FULL + c), c * 64, (idx & 7) * 3);
                }
                map_prefetch(&maps.xn);
            }
            __syncwarp();
            const uint32_t u[8] = {a.x, a.y, a.z, a.w, b.x, b.y, b.z, b.w};
            const uint32_t w[8] = {wa.x, wa.y, wa.z, wa.w, wb.x, wb.y, wb.z, wb.w};
            float f[16];
            float sum = 0.f;
#pragma unroll
            for (int i = 0; i < 8; i++) { f[2 * i] = bf_lo(u[i]); f[2 * i + 1] = bf_hi(u[i]); sum += f[2 * i] + f[2 * i + 1]; }
#pragma unroll
            for (int o = 16; o > 0; o >>= 1) sum += __shfl_xor_sync(~0u, sum, o);
            const float mean = sum * (1.f / DM);
            float sq = 0.f;
#pragma unroll
            for (int i = 0; i < 16; i++) { const float d = f[i] - mean; sq = fmaf(d, d, sq); }
#pragma unroll
            for (int o = 16; o > 0; o >>= 1) sq += __shfl_xor_sync(~0u, sq, o);
            const float mb_ = bfr(mean);
            const float vb = bfr(sq * (1.f / DM));
            const float rinv = 1.f / bfr(sqrtf(bfr(vb + 1e-5f)));
            uint32_t o[8];
            float r = 0.f;
#pragma unroll
            for (int i = 0; i < 8; i++) {
                const float d0 = bfr(f[2 * i] - mb_), d1 = bfr(f[2 * i + 1] - mb_);
                o[i] = packbf(d0 * rinv, d1 * rinv);
                r = fmaf(bf_lo(o[i]), bf_lo(w[i]), r);
                r = fmaf(bf_hi(o[i]), bf_hi(w[i]), r);
            }
            uint4* xo = reinterpret_cast<uint4*>(g_xn + (size_t)row * DM);
            xo[lane] = make_uint4(o[0], o[1], o[2], o[3]);
            xo[32 + lane] = make_uint4(o[4], o[5], o[6], o[7]);
#pragma unroll
            for (int of = 16; of > 0; of >>= 1) r += __shfl_xor_sync(~0u, r, of);
            if (lane == 0) g_r[row] = r;
        }
        __syncthreads();
        if (tid == 416) flag_release(C_LN + (idx >> 3));
        TL(1);
        {
            const int nb = idx & 7, mb = idx >> 3;
            if (warp == 15) {
                for (int c = G_ST; c < 8; c++) {
                    const int s = c - G_ST;
                    mbar_wait(bars + 8 * (B_EMPTY + s), 0);
                    if (lane == 0) {
                        mbar_expect_tx(bars + 8 * (B_FULL + s), 24576);
                        tma3d(sbase + s * G_STAGE + 16384, &maps.wqkv, bars + 8 * (B_FULL + s), c * 64, nb * 3);
                    }
                    __syncwarp();
                }
            } else if (warp == 14) {
                flag_wait(C_LN + mb, 8);
                fence_proxy_async_all();
                for (int c = 0; c < 8; c++) {
                    const int s = c & (G_ST - 1);
                    if (c >= G_ST) mbar_wait(bars + 8 * (B_EMPTY + s), 0);
                    if (lane == 0) {
                        mbar_expect_tx(bars + 8 * (B_FULL + s), 16384);
                        tma3d(sbase + s * G_STAGE, &maps.xn, bars + 8 * (B_FULL + s), mb * 128, c);
                    }
                    __syncwarp();
                }
            } else if (wg < 2) {
                float acc[96];
#pragma unroll
                for (int i = 0; i < 96; i++) acc[i] = 0.f;
#pragma unroll 1
                for (int c = 0; c < 8; c++) {
                    const int s = c & (G_ST - 1);
                    const uint32_t st = sbase + s * G_STAGE;
                    mbar_wait(bars + 8 * (B_FULL + s), c >> 2);
                    if (c == 0) TL(2);
                    const uint64_t da = mkdesc(st + wg * 8192, 16, 1024, 1);
                    const uint64_t db = mkdesc(st + 16384, 8192, 1024, 1);
                    WG_FENCE();
#pragma unroll
                    for (int k = 0; k < 4; k++) wgmma_n192(acc, da + k * 2, db + k * 128, (c | k) != 0);
                    WG_COMMIT();
                    if (c <= G_ST) {
                        WG_WAIT(1);
                        if (c >= 1 && (tid & 127) == 0) mbar_arrive(bars + 8 * (B_EMPTY + c - 1));
                    }
                }
                WG_WAIT(0);
                nbar_arrive(6, 512);
                TL(3);
                const int mt = mb * 8 + warp;
                uint32_t* dst0 = g_qkv + (mt >> 4) * 6144 + (mt & 15) * 64 + lane;
#pragma unroll
                for (int hh = 0; hh < 12; hh++) {
                    const int gh = nb * 12 + hh, ty = gh >> 5;
                    const float* a = &acc[hh * 8];
                    uint32_t* dst = dst0 + (gh & 31) * 49152 + ((ty + 2) % 3) * 2048;
                    const uint32_t ks = ty == 1 ? 0x1f801f80u : 0x3f803f80u;
                    dst[0] = hmul2bf(packbf(a[0], a[1]), ks);
                    dst[32] = hmul2bf(packbf(a[2], a[3]), ks);
                    dst[1024] = hmul2bf(packbf(a[4], a[5]), ks);
                    dst[1024 + 32] = hmul2bf(packbf(a[6], a[7]), ks);
                }
                TL(10);
                nbar_sync(8, 256);
                if (tid == 0) flag_release(C_QKV + nb);
            }
        }
        TL(4);
        const int head = idx >> 2, quarter = idx & 3, w4 = warp & 3;
        {
            if (warp == 15) {
                flag_wait_all(C_QKV + ((lane % 3) * 32 + head) / 12, 16);
                nbar_sync(6, 512);
                fence_proxy_async_all();
                if (lane == 0) {
                    const uint8_t* kvp = reinterpret_cast<const uint8_t*>(g_qkv + head * 49152);
#pragma unroll 1
                    for (int c = 0; c < 2; c++) {
                        mbar_expect_tx(bars + 8 * (B_KV + c), 16384);
                        bulk_g2s(sbase + SM_KV + c * KV_CH, kvp + c * 24576, 16384, bars + 8 * (B_KV + c));
                    }
                }
                __syncwarp();
            } else if (wg >= 2) {
                nbar_sync(6, 512);
#pragma unroll 1
                for (int i = tid - 256; i < 2048; i += 224)
                    *reinterpret_cast<uint4*>(smem + SM_KV + (i >> 8) * KV_CH + 16384 + (i & 255) * 16) = make_uint4(0x3f803f80u, 0x3f803f80u, 0x3f803f80u, 0x3f803f80u);
                fence_proxy_async();
            }
            __syncthreads();
            if (tid == 480) {
                const uint8_t* kvp = reinterpret_cast<const uint8_t*>(g_qkv + head * 49152);
#pragma unroll 1
                for (int c = 2; c < 8; c++) {
                    mbar_expect_tx(bars + 8 * (B_KV + c), 16384);
                    bulk_g2s(sbase + SM_KV + c * KV_CH, kvp + c * 24576, 16384, bars + 8 * (B_KV + c));
                }
            } else if (tid == 352) {
                mbar_expect_tx(bars + 8 * B_WO, 65536);
                tma3d(sbase + SM_WO, &maps.wo, bars + 8 * B_WO, 0, idx & 7);
                tma3d(sbase + SM_WO + 32768, &maps.wo, bars + 8 * B_WO, 256, idx & 7);
                map_prefetch(&maps.o);
            }
            __syncwarp();
            const uint64_t kdesc0 = mkdesc(sbase + SM_KV, 4096, 128, 0);
            const uint64_t vdesc0 = mkdesc(sbase + SM_KV + 8192, 128, 4096, 0);
#pragma unroll 1
            for (int mt = 0; mt < 2; mt++) {
                const int m64 = quarter * 8 + mt * 4 + wg;
                uint32_t q[4];
                load_q(q, head, m64 * 4 + w4, lane);
                float s[32], s2[32], o[12];
#pragma unroll
                for (int i = 0; i < 12; i++) o[i] = 0.f;
                mbar_wait(bars + 8 * B_KV, 0);
                if (mt == 0) { TL(5); TLC(12); }
                WG_FENCE();
                qk64(s, q, kdesc0);
                WG_COMMIT(); WG_WAIT(0);
                float mx0 = -INFINITY, mx1 = -INFINITY;
#pragma unroll
                for (int i = 0; i < 8; i++) { mx0 = fmaxf(mx0, fmaxf(s[4 * i], s[4 * i + 1])); mx1 = fmaxf(mx1, fmaxf(s[4 * i + 2], s[4 * i + 3])); }
                mx0 = fmaxf(mx0, __shfl_xor_sync(~0u, mx0, 1)); mx0 = fmaxf(mx0, __shfl_xor_sync(~0u, mx0, 2));
                mx1 = fmaxf(mx1, __shfl_xor_sync(~0u, mx1, 1)); mx1 = fmaxf(mx1, __shfl_xor_sync(~0u, mx1, 2));
                float cm0 = -(ceilf(mx0 * QS) + SHIFT), cm1 = -(ceilf(mx1 * QS) + SHIFT);
                float cp0 = (cm0 + 127.f) * sc, cp1 = (cm1 + 127.f) * sc;
                asm volatile("" : "+f"(cm0), "+f"(cm1), "+f"(cp0), "+f"(cp1));
                uint64_t kd = kdesc0, vd = vdesc0;
                auto step = [&](float (&sc_)[32], float (&sn)[32], uint64_t kinc, uint64_t vinc) {
                    kd += kinc;
                    WG_FENCE();
                    qk64(sn, q, kd);
                    WG_COMMIT();
#pragma unroll
                    for (int kk = 0; kk < 4; kk++) {
                        const int i0 = kk * 2, i1 = kk * 2 + 1;
                        const uint32_t p0 = packbf(ex2(fmaf(sc_[4 * i0], QS, cm0)), ex2(fmaf(sc_[4 * i0 + 1], QS, cm0)));
                        const uint32_t p1 = packbf(ex2(fmaf(sc_[4 * i0 + 2], QS, cm1)), ex2(fmaf(sc_[4 * i0 + 3], QS, cm1)));
                        const uint32_t p2 = polyexp(fmaf(sc_[4 * i1], scq, cp0), fmaf(sc_[4 * i1 + 1], scq, cp0));
                        const uint32_t p3 = polyexp(fmaf(sc_[4 * i1 + 2], scq, cp1), fmaf(sc_[4 * i1 + 3], scq, cp1));
                        WG_FENCE();
                        pv24(o, p0, p1, p2, p3, vd + kk * 16);
                    }
                    vd += vinc;
                    WG_COMMIT();
                    WG_WAIT(1);
                };
                uint64_t hop = 64u;
#pragma unroll 1
                for (int c = 0; c < 16; c++) {
                    if (mt == 0) {
                        if ((c & 1) == 0 && c < 14) mbar_wait(bars + 8 * B_KV + 4 * c + 8, 0);
                    } else if (c == 2) {
                        nbar_sync(wg + 1, 128);
                        if ((tid & 127) == 0) flag_release(C_O + m64 - 4);
                    }
                    step(s, s2, 64u, 64u);
                    step(s2, s, hop, hop);
                    hop ^= (KV_CH - 4096) / 16;
                }
                WG_WAIT(0);
                bool bad = !(o[8] > 0.f) || !(o[10] > 0.f);
#pragma unroll
                for (int i = 0; i < 12; i++) bad = bad || !(fabsf(o[i]) <= 3.0e38f);
                if (__any_sync(~0u, bad)) attn_safe(o, q, head, lane);
                attn_store(o, head, m64, w4, lane);
            }
        }
        nbar_sync(wg + 1, 128);
        if ((tid & 127) == 32) {
            flag_release(C_O + quarter * 8 + 4 + wg);
        }

        TL(6); TLC(13);
        {
            const int nb = idx & 7, jb = idx >> 3;
            const int mbe = (jb >> 2) * 8 + (jb & 3);
            float* supd = reinterpret_cast<float*>(smem + SM_MISC + 512);
            if (warp == 15) nbar_sync(7, 512); else nbar_arrive(7, 512);
            TLX(11, 480);
            if (warp == 15) {
                flag_wait_all((lane & 1) ? C_FFN : C_O + mbe, (lane & 1) ? 64 : 32);
                nbar_arrive(9, 160);
                fence_proxy_async_all();
                if (lane == 0) {
                    for (int c = 0; c < 2; c++) {
                        mbar_expect_tx(bars + 8 * (B_OA + c), 32768);
                        tma3d(sbase + SM_KV + c * 32768, &maps.o, bars + 8 * (B_OA + c), mbe * 64, c * 4);
                    }
                }
                __syncwarp();
                flag_wait(C_O + mbe + 4, 32);
                fence_proxy_async_all();
                if (lane == 0) {
                    for (int c = 0; c < 2; c++) {
                        mbar_expect_tx(bars + 8 * (B_OA + 2 + c), 32768);
                        tma3d(sbase + SM_KV + 65536 + c * 32768, &maps.o, bars + 8 * (B_OA + 2 + c), (mbe + 4) * 64, c * 4);
                    }
                    exit_ticket();
                }
                __syncwarp();
            }
            const int late = wg >> 1, nh = wg & 1;
            const int mb = mbe + late * 4;
            const int g = lane >> 2, t = lane & 3;
            const int row0 = mb * 64 + w4 * 16 + g;
            const int col0 = nb * 64 + nh * 32 + t * 2;
            uint32_t xv[8], nv[8];
#pragma unroll
            for (int i = 0; i < 4; i++) {
                xv[2 * i] = *reinterpret_cast<const uint32_t*>(x + (size_t)row0 * DM + col0 + i * 8);
                xv[2 * i + 1] = *reinterpret_cast<const uint32_t*>(x + (size_t)(row0 + 8) * DM + col0 + i * 8);
                nv[2 * i] = __ldcg(reinterpret_cast<const uint32_t*>(g_xn + (size_t)row0 * DM + col0 + i * 8));
                nv[2 * i + 1] = __ldcg(reinterpret_cast<const uint32_t*>(g_xn + (size_t)(row0 + 8) * DM + col0 + i * 8));
            }
            if (wg == 0) {
                nbar_sync(9, 160);
                const int which = tid >> 6, col = nb * 64 + (tid & 63);
                const float y = __ldcg(&g_ypart[which * 512 + col]) + __ldcg(&g_ypart[1024 + which * 512 + col]) +
                                __ldcg(&g_ypart[2048 + which * 512 + col]) + __ldcg(&g_ypart[3072 + which * 512 + col]);
                supd[tid] = bfr(bfr(y) * __ldcg(&g_gate[which]));
                if (tid < 2) reinterpret_cast<int*>(supd + 128)[tid] = __ldcg(&g_sel[tid]);
            }
            float acc[16];
#pragma unroll
            for (int i = 0; i < 16; i++) acc[i] = 0.f;
            mbar_wait(bars + 8 * B_WO, 0);
            const uint32_t abase = sbase + SM_KV + late * 65536;
#pragma unroll 1
            for (int c = 0; c < 8; c++) {
                if ((c & 3) == 0) mbar_wait(bars + 8 * (B_OA + late * 2 + (c >> 2)), 0);
                if (c == 0) TLX(7, 256);
                const uint64_t da = mkdesc(abase + c * 8192, 16, 1024, 1);
                const uint64_t db = mkdesc(sbase + SM_WO + c * 8192 + nh * 64, 8192, 1024, 1);
                WG_FENCE();
#pragma unroll
                for (int k = 0; k < 4; k++) wgmma_n32(acc, da + k * 2, db + k * 128, (c | k) != 0);
                WG_COMMIT();
            }
            TLX(14, 256);
            __syncthreads();
            TLX(15, 256);
            const int sel0 = reinterpret_cast<const int*>(supd + 128)[0], sel1 = reinterpret_cast<const int*>(supd + 128)[1];
            WG_WAIT(0);
            TLX(8, 256);
#pragma unroll
            for (int h = 0; h < 2; h++) {
                const int row = row0 + h * 8;
                const int which = row == sel0 ? 0 : (row == sel1 ? 1 : -1);
#pragma unroll
                for (int i = 0; i < 4; i++) {
                    const int col = col0 + i * 8;
                    float b0 = bf_lo(nv[2 * i + h]), b1 = bf_hi(nv[2 * i + h]);
                    if (which >= 0) {
                        b0 = bfr(b0 + supd[which * 64 + col - nb * 64]); b1 = bfr(b1 + supd[which * 64 + col + 1 - nb * 64]);
                    }
                    const float t0 = bfr(bf_lo(xv[2 * i + h]) + bfr(acc[4 * i + 2 * h]));
                    const float t1 = bfr(bf_hi(xv[2 * i + h]) + bfr(acc[4 * i + 2 * h + 1]));
                    *reinterpret_cast<uint32_t*>(out + (size_t)row * DM + col) = packbf(t0 + b0, t1 + b1);
                }
            }
        }
        TLX(9, 256);
    }
}

typedef CUresult (*EncodeFn)(CUtensorMap*, CUtensorMapDataType, cuuint32_t, void*, const cuuint64_t*, const cuuint64_t*,
                             const cuuint32_t*, const cuuint32_t*, CUtensorMapInterleave, CUtensorMapSwizzle,
                             CUtensorMapL2promotion, CUtensorMapFloatOOBfill);

void make_map(EncodeFn fn, CUtensorMap* m, const void* ptr, uint64_t cols, uint64_t rows, uint32_t box_rows, uint32_t box_chunks) {
    cuuint64_t dims[3] = {64, rows, cols / 64};
    cuuint64_t strides[2] = {cols * 2, 128};
    cuuint32_t box[3] = {64, box_rows, box_chunks};
    cuuint32_t es[3] = {1, 1, 1};
    fn(m, CU_TENSOR_MAP_DATA_TYPE_BFLOAT16, 3, const_cast<void*>(ptr), dims, strides, box, es, CU_TENSOR_MAP_INTERLEAVE_NONE,
       CU_TENSOR_MAP_SWIZZLE_128B, CU_TENSOR_MAP_L2_PROMOTION_L2_256B, CU_TENSOR_MAP_FLOAT_OOB_FILL_NONE);
}

}

extern "C" void kernel_launch(void* const* d_in, const int* in_sizes, int n_in, void* d_out, int out_size) {
    const __nv_bfloat16* x = (const __nv_bfloat16*)d_in[0];
    const __nv_bfloat16* wqkv = (const __nv_bfloat16*)d_in[1];
    const __nv_bfloat16* wo = (const __nv_bfloat16*)d_in[2];
    const __nv_bfloat16* wr = (const __nv_bfloat16*)d_in[4];
    const __nv_bfloat16* wgate = (const __nv_bfloat16*)d_in[5];
    const __nv_bfloat16* wup = (const __nv_bfloat16*)d_in[6];
    const __nv_bfloat16* wdown = (const __nv_bfloat16*)d_in[7];
    __nv_bfloat16* out = (__nv_bfloat16*)d_out;

    static EncodeFn enc = nullptr;
    static void* p_xn = nullptr; static void* p_o = nullptr;
    if (!enc) {
        void* fn = nullptr; cudaDriverEntryPointQueryResult qr;
        cudaGetDriverEntryPoint("cuTensorMapEncodeTiled", &fn, cudaEnableDefault, &qr);
        enc = (EncodeFn)fn;
        cudaGetSymbolAddress(&p_xn, g_xn);
        cudaGetSymbolAddress(&p_o, g_o);
        cudaFuncSetAttribute(fused_kernel, cudaFuncAttributeMaxDynamicSharedMemorySize, FUSED_SMEM);
    }
    Maps maps;
    make_map(enc, &maps.g, wgate, FF, DM, 16, 7);
    make_map(enc, &maps.u, wup, FF, DM, 16, 7);
    make_map(enc, &maps.d, wdown, DM, FF, 32, 8);
    make_map(enc, &maps.xn, p_xn, DM, S_LEN, 128, 1);
    make_map(enc, &maps.wqkv, wqkv, 3 * DM, DM, 64, 3);
    make_map(enc, &maps.o, p_o, DM, S_LEN, 64, 4);
    make_map(enc, &maps.wo, wo, DM, DM, 256, 1);

    union { uint32_t u; float f; } scu; scu.u = 128u;

    cudaLaunchConfig_t cfg = {};
    cfg.gridDim = dim3(132); cfg.blockDim = dim3(512); cfg.dynamicSmemBytes = FUSED_SMEM; cfg.stream = cudaStreamPerThread;
    cudaLaunchKernelEx(&cfg, fused_kernel, maps, x, wr, out, scu.f);
}
```

```cpp
#include <cuda_runtime.h>
#include <cuda_bf16.h>
#include <cuda.h>
#include <stdint.h>
#include <type_traits>

namespace {

constexpr int S_LEN = 2048;
constexpr int DM = 512;
constexpr int NH = 32;
constexpr int FF = 1792;

__device__ __align__(1024) __nv_bfloat16 g_xn[S_LEN * DM];
__device__ __align__(16) float g_r[S_LEN];
__device__ __align__(1024) uint32_t g_qkv[NH * 8 * 6144];
__device__ __align__(1024) __nv_bfloat16 g_o[S_LEN * DM];
__device__ __align__(16) float g_ypart[4 * 2 * DM];
__device__ int g_sel[2];
__device__ float g_gate[2];
constexpr int C_LN = 0, C_QKV = 16, C_O = 24, C_FFN = 56, C_EXIT = 57, C_NUM = 58;
__device__ unsigned g_cnt[C_NUM * 32];

#define TLC(slot) do {} while (0)
#define TL(slot) do {} while (0)
#define TLX(slot, th) do {} while (0)

__device__ __forceinline__ uint32_t smem_u32(const void* p) { return (uint32_t)__cvta_generic_to_shared(p); }
__device__ __forceinline__ void warp_arrive(int idx) {
    __syncwarp();
    if ((threadIdx.x & 31) == 0)
        asm volatile("red.release.gpu.global.add.u32 [%0], 1;" :: "l"(g_cnt + idx * 32) : "memory");
}
__device__ __forceinline__ void flag_release(int idx) {
    asm volatile("red.release.gpu.global.add.u32 [%0], 1;" :: "l"(g_cnt + idx * 32) : "memory");
}
__device__ __forceinline__ void exit_ticket() {
    unsigned tk;
    asm volatile("atom.relaxed.gpu.global.add.u32 %0, [%1], 1;" : "=r"(tk) : "l"(g_cnt + C_EXIT * 32) : "memory");
    if (tk == gridDim.x - 1) {
#pragma unroll 1
        for (int i = 0; i < C_NUM; i++) g_cnt[i * 32] = 0u;
    }
}
__device__ __forceinline__ void nbar_arrive(int id, int cnt) { asm volatile("bar.arrive %0, %1;" :: "r"(id), "r"(cnt) : "memory"); }
__device__ __forceinline__ void nbar_sync(int id, int cnt) { asm volatile("bar.sync %0, %1;" :: "r"(id), "r"(cnt) : "memory"); }
__device__ __forceinline__ void flag_wait(int idx, unsigned target) {
    asm volatile("{\n.reg .pred p;\n.reg .u32 n, v;\nmov.u32 n, 0;\n"
                 "FW_%=:\n"
                 "ld.acquire.gpu.global.u32 v, [%0];\n"
                 "setp.ge.u32 p, v, %1;\n"
                 "@p bra FD_%=;\n"
                 "add.u32 n, n, 1;\n"
                 "setp.lt.u32 p, n, 16000000;\n"
                 "@p bra FW_%=;\n"
                 "trap;\n"
                 "FD_%=:\n}"
                 :: "l"(g_cnt + idx * 32), "r"(target) : "memory");
}
__device__ __forceinline__ void flag_wait_all(int idx, unsigned target) {
    asm volatile("{\n.reg .pred p;\n.reg .u32 n, v;\nmov.u32 n, 0;\n"
                 "FW_%=:\n"
                 "ld.acquire.gpu.global.u32 v, [%0];\n"
                 "setp.ge.u32 p, v, %1;\n"
                 "vote.sync.all.pred p, p, 0xffffffff;\n"
                 "@p bra.uni FD_%=;\n"
                 "add.u32 n, n, 1;\n"
                 "setp.lt.u32 p, n, 16000000;\n"
                 "@p bra.uni FW_%=;\n"
                 "trap;\n"
                 "FD_%=:\n}"
                 :: "l"(g_cnt + idx * 32), "r"(target) : "memory");
}
__device__ __forceinline__ void fence_proxy_async_all() { asm volatile("fence.proxy.async.global;" ::: "memory"); }
__device__ __forceinline__ void mbar_init(uint32_t bar, uint32_t cnt) {
    asm volatile("mbarrier.init.shared::cta.b64 [%0], %1;" :: "r"(bar), "r"(cnt) : "memory");
}
__device__ __forceinline__ void mbar_expect_tx(uint32_t bar, uint32_t bytes) {
    asm volatile("mbarrier.arrive.expect_tx.shared::cta.b64 _, [%0], %1;" :: "r"(bar), "r"(bytes) : "memory");
}
__device__ __forceinline__ void mbar_arrive(uint32_t bar) {
    asm volatile("mbarrier.arrive.shared::cta.b64 _, [%0];" :: "r"(bar) : "memory");
}
__device__ __forceinline__ void mbar_wait(uint32_t bar, uint32_t parity) {
    asm volatile("{\n.reg .pred p;\n.reg .u32 n;\nmov.u32 n, 0;\n"
                 "WAIT_%=:\n"
                 "mbarrier.try_wait.parity.shared::cta.b64 p, [%0], %1;\n"
                 "@p bra DONE_%=;\n"
                 "add.u32 n, n, 1;\n"
                 "setp.lt.u32 p, n, 4000000;\n"
                 "@p bra WAIT_%=;\n"
                 "trap;\n"
                 "DONE_%=:\n}"
                 :: "r"(bar), "r"(parity) : "memory");
}
__device__ __forceinline__ void fence_barrier_init() { asm volatile("fence.mbarrier_init.release.cluster;" ::: "memory"); }
__device__ __forceinline__ void fence_proxy_async() { asm volatile("fence.proxy.async.shared::cta;" ::: "memory"); }
__device__ __forceinline__ void tma3d(uint32_t dst, const CUtensorMap* map, uint32_t bar, int row, int chunk) {
    asm volatile("cp.async.bulk.tensor.3d.shared::cluster.global.mbarrier::complete_tx::bytes [%0], [%1, {%3, %4, %5}], [%2];"
                 :: "r"(dst), "l"((uint64_t)map), "r"(bar), "r"(0), "r"(row), "r"(chunk) : "memory");
}
__device__ __forceinline__ void bulk_g2s(uint32_t dst, const void* src, uint32_t bytes, uint32_t bar) {
    asm volatile("cp.async.bulk.shared::cluster.global.mbarrier::complete_tx::bytes [%0], [%1], %2, [%3];"
                 :: "r"(dst), "l"((uint64_t)src), "r"(bytes), "r"(bar) : "memory");
}
__device__ __forceinline__ void l2_prefetch(const void* src, uint32_t bytes) {
    asm volatile("cp.async.bulk.prefetch.L2.global [%0], %1;" :: "l"((uint64_t)src), "r"(bytes) : "memory");
}
__device__ __forceinline__ void map_prefetch(const CUtensorMap* m) {
    asm volatile("prefetch.tensormap [%0];" :: "l"((uint64_t)m) : "memory");
}
__device__ __forceinline__ uint64_t mkdesc(uint32_t addr, uint32_t lbo, uint32_t sbo, uint32_t swz) {
    return (uint64_t)((addr & 0x3FFFF) >> 4) | ((uint64_t)(lbo >> 4) << 16) | ((uint64_t)(sbo >> 4) << 32) | ((uint64_t)swz << 62);
}
#define WG_FENCE() asm volatile("wgmma.fence.sync.aligned;" ::: "memory")
#define WG_COMMIT() asm volatile("wgmma.commit_group.sync.aligned;" ::: "memory")
#define WG_WAIT(n) asm volatile("wgmma.wait_group.sync.aligned %0;" :: "n"(n) : "memory")

__device__ __forceinline__ float ex2(float x) { float y; asm("ex2.approx.ftz.f32 %0, %1;" : "=f"(y) : "f"(x)); return y; }
__device__ __forceinline__ uint32_t packbf(float lo, float hi) {
    uint32_t r; asm("cvt.rn.bf16x2.f32 %0, %1, %2;" : "=r"(r) : "f"(hi), "f"(lo)); return r;
}
__device__ __forceinline__ uint32_t hmul2bf(uint32_t a, uint32_t b) { uint32_t r; asm("mul.rn.bf16x2 %0, %1, %2;" : "=r"(r) : "r"(a), "r"(b)); return r; }
__device__ __forceinline__ float bf_lo(uint32_t v) { return __uint_as_float(v << 16); }
__device__ __forceinline__ float bf_hi(uint32_t v) { return __uint_as_float(v & 0xffff0000u); }
__device__ __forceinline__ float bfr(float x) { return __bfloat162float(__float2bfloat16_rn(x)); }

__device__ __forceinline__ void wgmma_n192(float (&d)[96], uint64_t da, uint64_t db, int scale_d) {
    asm volatile("{\n.reg .pred p;\nsetp.ne.b32 p, %98, 0;\n"
        "wgmma.mma_async.sync.aligned.m64n192k16.f32.bf16.bf16 "
        "{%0,%1,%2,%3,%4,%5,%6,%7,%8,%9,%10,%11,%12,%13,%14,%15,%16,%17,%18,%19,%20,%21,%22,%23,"
        "%24,%25,%26,%27,%28,%29,%30,%31,%32,%33,%34,%35,%36,%37,%38,%39,%40,%41,%42,%43,%44,%45,%46,%47,"
        "%48,%49,%50,%51,%52,%53,%54,%55,%56,%57,%58,%59,%60,%61,%62,%63,%64,%65,%66,%67,%68,%69,%70,%71,"
        "%72,%73,%74,%75,%76,%77,%78,%79,%80,%81,%82,%83,%84,%85,%86,%87,%88,%89,%90,%91,%92,%93,%94,%95}, "
        "%96, %97, p, 1, 1, 0, 1;\n}"
        : "+f"(d[0]), "+f"(d[1]), "+f"(d[2]), "+f"(d[3]), "+f"(d[4]), "+f"(d[5]), "+f"(d[6]), "+f"(d[7]),
          "+f"(d[8]), "+f"(d[9]), "+f"(d[10]), "+f"(d[11]), "+f"(d[12]), "+f"(d[13]), "+f"(d[14]), "+f"(d[15]),
          "+f"(d[16]), "+f"(d[17]), "+f"(d[18]), "+f"(d[19]), "+f"(d[20]), "+f"(d[21]), "+f"(d[22]), "+f"(d[23]),
          "+f"(d[24]), "+f"(d[25]), "+f"(d[26]), "+f"(d[27]), "+f"(d[28]), "+f"(d[29]), "+f"(d[30]), "+f"(d[31]),
          "+f"(d[32]), "+f"(d[33]), "+f"(d[34]), "+f"(d[35]), "+f"(d[36]), "+f"(d[37]), "+f"(d[38]), "+f"(d[39]),
          "+f"(d[40]), "+f"(d[41]), "+f"(d[42]), "+f"(d[43]), "+f"(d[44]), "+f"(d[45]), "+f"(d[46]), "+f"(d[47]),
          "+f"(d[48]), "+f"(d[49]), "+f"(d[50]), "+f"(d[51]), "+f"(d[52]), "+f"(d[53]), "+f"(d[54]), "+f"(d[55]),
          "+f"(d[56]), "+f"(d[57]), "+f"(d[58]), "+f"(d[59]), "+f"(d[60]), "+f"(d[61]), "+f"(d[62]), "+f"(d[63]),
          "+f"(d[64]), "+f"(d[65]), "+f"(d[66]), "+f"(d[67]), "+f"(d[68]), "+f"(d[69]), "+f"(d[70]), "+f"(d[71]),
          "+f"(d[72]), "+f"(d[73]), "+f"(d[74]), "+f"(d[75]), "+f"(d[76]), "+f"(d[77]), "+f"(d[78]), "+f"(d[79]),
          "+f"(d[80]), "+f"(d[81]), "+f"(d[82]), "+f"(d[83]), "+f"(d[84]), "+f"(d[85]), "+f"(d[86]), "+f"(d[87]),
          "+f"(d[88]), "+f"(d[89]), "+f"(d[90]), "+f"(d[91]), "+f"(d[92]), "+f"(d[93]), "+f"(d[94]), "+f"(d[95])
        : "l"(da), "l"(db), "r"(scale_d));
}

constexpr float SHIFT = 90.0f;
constexpr float QS = 0.25f * 1.4426950408889634f * 18446744073709551616.0f;
constexpr float scq = 0.25f * 1.4426950408889634f * 3.3087224502121107e-24f;

__device__ __forceinline__ uint32_t polyexp(float lo, float hi) {
    uint32_t w, g, q, h;
    asm("cvt.pack.sat.s16.s32 %0, %1, %2;" : "=r"(w) : "r"(__float_as_uint(hi)), "r"(__float_as_uint(lo)));
    g = w & 0x007F007Fu;
    asm("fma.rn.f16x2 %0, %1, %2, %3;" : "=r"(q) : "r"(g), "r"(0xf940f940u), "r"(0x35513551u));
    asm("mul.rn.f16x2 %0, %1, %2;" : "=r"(h) : "r"(q), "r"(g));
    return w - h;
}
__device__ __forceinline__ void qk64(float (&s)[32], const uint32_t (&q)[4], uint64_t db) {
    asm volatile("wgmma.mma_async.sync.aligned.m64n64k16.f32.bf16.bf16 "
        "{%0,%1,%2,%3,%4,%5,%6,%7,%8,%9,%10,%11,%12,%13,%14,%15,%16,%17,%18,%19,%20,%21,%22,%23,%24,%25,%26,%27,%28,%29,%30,%31}, "
        "{%32,%33,%34,%35}, %36, 0, 1, 1, 0;"
        : "=f"(s[0]), "=f"(s[1]), "=f"(s[2]), "=f"(s[3]), "=f"(s[4]), "=f"(s[5]), "=f"(s[6]), "=f"(s[7]),
          "=f"(s[8]), "=f"(s[9]), "=f"(s[10]), "=f"(s[11]), "=f"(s[12]), "=f"(s[13]), "=f"(s[14]), "=f"(s[15]),
          "=f"(s[16]), "=f"(s[17]), "=f"(s[18]), "=f"(s[19]), "=f"(s[20]), "=f"(s[21]), "=f"(s[22]), "=f"(s[23]),
          "=f"(s[24]), "=f"(s[25]), "=f"(s[26]), "=f"(s[27]), "=f"(s[28]), "=f"(s[29]), "=f"(s[30]), "=f"(s[31])
        : "r"(q[0]), "r"(q[1]), "r"(q[2]), "r"(q[3]), "l"(db));
}
__device__ __forceinline__ void pv24(float (&o)[12], uint32_t a0, uint32_t a1, uint32_t a2, uint32_t a3, uint64_t db) {
    asm volatile("wgmma.mma_async.sync.aligned.m64n24k16.f32.bf16.bf16 "
        "{%0,%1,%2,%3,%4,%5,%6,%7,%8,%9,%10,%11}, {%12,%13,%14,%15}, %16, 1, 1, 1, 1;"
        : "+f"(o[0]), "+f"(o[1]), "+f"(o[2]), "+f"(o[3]), "+f"(o[4]), "+f"(o[5]), "+f"(o[6]), "+f"(o[7]),
          "+f"(o[8]), "+f"(o[9]), "+f"(o[10]), "+f"(o[11])
        : "r"(a0), "r"(a1), "r"(a2), "r"(a3), "l"(db));
}

__device__ __forceinline__ void load_q(uint32_t (&q)[4], int head, int mt, int lane) {
    const uint32_t* src = g_qkv + head * 49152 + (mt >> 4) * 6144 + 4096 + (mt & 15) * 64 + lane;
    q[0] = __ldcg(src); q[1] = __ldcg(src + 32); q[2] = __ldcg(src + 1024); q[3] = __ldcg(src + 1024 + 32);
}
__device__ __forceinline__ void attn_store(const float (&o)[12], int head, int m64, int warp, int lane) {
    const int g = lane >> 2, t = lane & 3;
    const int row = m64 * 64 + warp * 16 + g;
    const float i0 = 1.f / o[8], i1 = 1.f / o[10];
    uint32_t* p0 = reinterpret_cast<uint32_t*>(g_o + (size_t)row * DM + head * 16 + t * 2);
    uint32_t* p1 = reinterpret_cast<uint32_t*>(g_o + (size_t)(row + 8) * DM + head * 16 + t * 2);
    p0[0] = packbf(o[0] * i0, o[1] * i0); p0[4] = packbf(o[4] * i0, o[5] * i0);
    p1[0] = packbf(o[2] * i1, o[3] * i1); p1[4] = packbf(o[6] * i1, o[7] * i1);
}

__device__ __forceinline__ void mma_full(float (&d)[4], uint32_t a0, uint32_t a1, uint32_t a2, uint32_t a3, uint32_t b0, uint32_t b1) {
    asm volatile("mma.sync.aligned.m16n8k16.row.col.f32.bf16.bf16.f32 {%0,%1,%2,%3}, {%4,%5,%6,%7}, {%8,%9}, {%0,%1,%2,%3};"
                 : "+f"(d[0]), "+f"(d[1]), "+f"(d[2]), "+f"(d[3]) : "r"(a0), "r"(a1), "r"(a2), "r"(a3), "r"(b0), "r"(b1));
}
__device__ __forceinline__ uint32_t movt(uint32_t a) {
    uint32_t r; asm volatile("movmatrix.sync.aligned.m8n8.trans.b16 %0, %1;" : "=r"(r) : "r"(a)); return r;
}
__device__ __noinline__ void attn_safe(uint32_t q0, uint32_t q1, uint32_t q2, uint32_t q3, int head, int m64, int w4, int lane) {
    float o0[4] = {0.f, 0.f, 0.f, 0.f}, o1[4] = {0.f, 0.f, 0.f, 0.f};
    float m0 = -INFINITY, m1 = -INFINITY, l0 = 0.f, l1 = 0.f;
#pragma unroll 1
    for (int kb = 0; kb < 128; kb++) {
        const uint32_t* src = g_qkv + head * 49152 + (kb >> 4) * 6144 + (kb & 15) * 64 + lane;
        const int kk = (kb + 124) & 127;
        const uint32_t* srck = g_qkv + head * 49152 + (kk >> 4) * 6144 + (kk & 15) * 64 + lane;
        float sa[4] = {0.f, 0.f, 0.f, 0.f}, sb[4] = {0.f, 0.f, 0.f, 0.f};
        mma_full(sa, q0, q1, q2, q3, __ldcg(srck), __ldcg(srck + 1024));
        mma_full(sb, q0, q1, q2, q3, __ldcg(srck + 32), __ldcg(srck + 1024 + 32));
        float n0 = fmaxf(fmaxf(m0, fmaxf(sa[0], sa[1])), fmaxf(sb[0], sb[1]));
        float n1 = fmaxf(fmaxf(m1, fmaxf(sa[2], sa[3])), fmaxf(sb[2], sb[3]));
        n0 = fmaxf(n0, __shfl_xor_sync(~0u, n0, 1)); n0 = fmaxf(n0, __shfl_xor_sync(~0u, n0, 2));
        n1 = fmaxf(n1, __shfl_xor_sync(~0u, n1, 1)); n1 = fmaxf(n1, __shfl_xor_sync(~0u, n1, 2));
        const float c0 = ex2((m0 - n0) * QS), c1 = ex2((m1 - n1) * QS);
        m0 = n0; m1 = n1;
        const uint32_t p0 = packbf(ex2((sa[0] - m0) * QS), ex2((sa[1] - m0) * QS));
        const uint32_t p1 = packbf(ex2((sa[2] - m1) * QS), ex2((sa[3] - m1) * QS));
        const uint32_t p2 = packbf(ex2((sb[0] - m0) * QS), ex2((sb[1] - m0) * QS));
        const uint32_t p3 = packbf(ex2((sb[2] - m1) * QS), ex2((sb[3] - m1) * QS));
        l0 = l0 * c0 + (bf_lo(p0) + bf_hi(p0)) + (bf_lo(p2) + bf_hi(p2));
        l1 = l1 * c1 + (bf_lo(p1) + bf_hi(p1)) + (bf_lo(p3) + bf_hi(p3));
        o0[0] *= c0; o0[1] *= c0; o0[2] *= c1; o0[3] *= c1;
        o1[0] *= c0; o1[1] *= c0; o1[2] *= c1; o1[3] *= c1;
        mma_full(o0, p0, p1, p2, p3, movt(__ldcg(src + 2048)), movt(__ldcg(src + 2048 + 32)));
        mma_full(o1, p0, p1, p2, p3, movt(__ldcg(src + 3072)), movt(__ldcg(src + 3072 + 32)));
    }
    l0 += __shfl_xor_sync(~0u, l0, 1); l0 += __shfl_xor_sync(~0u, l0, 2);
    l1 += __shfl_xor_sync(~0u, l1, 1); l1 += __shfl_xor_sync(~0u, l1, 2);
    const float o[12] = {o0[0], o0[1], o0[2], o0[3], o1[0], o1[1], o1[2], o1[3], l0, l0, l1, l1};
    attn_store(o, head, m64, w4, lane);
}

constexpr int FS_N = 4;
constexpr int FS_BYTES = 32768;
__device__ __forceinline__ void ldsm4t(uint32_t& r0, uint32_t& r1, uint32_t& r2, uint32_t& r3, uint32_t addr) {
    asm volatile("ldmatrix.sync.aligned.m8n8.x4.trans.shared.b16 {%0,%1,%2,%3}, [%4];" : "=r"(r0), "=r"(r1), "=r"(r2), "=r"(r3) : "r"(addr) : "memory");
}
__device__ __forceinline__ void mma16816(float (&d)[4], uint32_t a0, uint32_t a2, uint32_t b0, uint32_t b1) {
    asm volatile("mma.sync.aligned.m16n8k16.row.col.f32.bf16.bf16.f32 {%0,%1,%2,%3}, {%4,%5,%6,%5}, {%7,%8}, {%0,%1,%2,%3};"
                 : "+f"(d[0]), "+f"(d[1]), "+f"(d[2]), "+f"(d[3]) : "r"(a0), "r"(0u), "r"(a2), "r"(b0), "r"(b1));
}
__device__ void ffn_block(int c, uint8_t* smem, uint32_t sbase, const CUtensorMap* mapG, const CUtensorMap* mapU, const CUtensorMap* mapD) {
    const int tid = threadIdx.x, warp = tid >> 5, lane = tid & 31;
    uint32_t* sx = reinterpret_cast<uint32_t*>(smem + FS_N * FS_BYTES);
    __nv_bfloat16* sh = reinterpret_cast<__nv_bfloat16*>(sx + 512);
    const uint32_t bars = sbase + FS_N * FS_BYTES + 8192;
    float* tv = reinterpret_cast<float*>(smem + FS_N * FS_BYTES + 4096);
    int* ti = reinterpret_cast<int*>(tv + 32);
    int* ssel = ti + 32;
    auto issue = [&](int item) {
        const int slot = item % FS_N;
        const uint32_t dst = sbase + slot * FS_BYTES, bar = bars + 8 * slot;
        mbar_expect_tx(bar, item < 32 ? 28672 : 32768);
        if (item < 32) {
            tma3d(dst, mapG, bar, item * 16, c * 7);
            tma3d(dst + 14336, mapU, bar, item * 16, c * 7);
        } else {
            tma3d(dst, mapD, bar, c * 448 + (item - 32) * 32, 0);
        }
    };
    if (tid == 0) {
        for (int i = 0; i < FS_N; i++) mbar_init(bars + 8 * i, 1);
        fence_barrier_init();
        for (int i = 0; i < FS_N; i++) issue(i);
    }
    flag_wait(C_LN + warp, 8);
    __syncthreads();
    float b1 = -INFINITY, b2 = -INFINITY; int i1 = 0x7fffffff, i2 = 0x7fffffff;
    auto push = [&](float v, int i) {
        if (v > b1 || (v == b1 && i < i1)) { b2 = b1; i2 = i1; b1 = v; i1 = i; }
        else if (v > b2 || (v == b2 && i < i2)) { b2 = v; i2 = i; }
    };
    {
        const float4 rv = __ldcg(reinterpret_cast<const float4*>(g_r) + tid);
        push(rv.x, 4 * tid); push(rv.y, 4 * tid + 1); push(rv.z, 4 * tid + 2); push(rv.w, 4 * tid + 3);
    }
#pragma unroll
    for (int o = 16; o > 0; o >>= 1) {
        float v1 = __shfl_xor_sync(~0u, b1, o), v2 = __shfl_xor_sync(~0u, b2, o);
        int j1 = __shfl_xor_sync(~0u, i1, o), j2 = __shfl_xor_sync(~0u, i2, o);
        push(v1, j1); push(v2, j2);
    }
    if (lane == 0) { tv[2 * warp] = b1; ti[2 * warp] = i1; tv[2 * warp + 1] = b2; ti[2 * warp + 1] = i2; }
    __syncthreads();
    if (warp == 1) {
        b1 = tv[lane]; i1 = ti[lane]; b2 = -INFINITY; i2 = 0x7fffffff;
#pragma unroll
        for (int o = 16; o > 0; o >>= 1) {
            float v1 = __shfl_xor_sync(~0u, b1, o), v2 = __shfl_xor_sync(~0u, b2, o);
            int j1 = __shfl_xor_sync(~0u, i1, o), j2 = __shfl_xor_sync(~0u, i2, o);
            push(v1, j1); push(v2, j2);
        }
        if (lane == 0) {
            i1 = min(max(i1, 0), S_LEN - 1); i2 = min(max(i2, 0), S_LEN - 1);
            ssel[0] = i1; ssel[1] = i2;
            if (c == 0) {
                g_sel[0] = i1; g_sel[1] = i2;
                g_gate[0] = bfr(1.f / (1.f + __expf(-bfr(b1))));
                g_gate[1] = bfr(1.f / (1.f + __expf(-bfr(b2))));
            }
        }
    }
    __syncthreads();
    sx[tid] = __ldcg(reinterpret_cast<const uint32_t*>(g_xn + (size_t)ssel[tid >> 8] * DM + (tid & 255) * 2));
    __syncthreads();
    TL(1);
    const int g = lane >> 2, t = lane & 3;
    const int lrow = lane & 15, lsel = lane >> 4;
    {
        float ag[4][4], au[4][4];
#pragma unroll
        for (int j = 0; j < 4; j++) { ag[j][0] = ag[j][1] = ag[j][2] = ag[j][3] = 0.f; au[j][0] = au[j][1] = au[j][2] = au[j][3] = 0.f; }
#pragma unroll 1
        for (int it = 0; it < 32; it++) {
            const int slot = it % FS_N;
            const uint32_t a0 = g < 2 ? sx[g * 256 + it * 8 + t] : 0u, a2 = g < 2 ? sx[g * 256 + it * 8 + 4 + t] : 0u;
            mbar_wait(bars + 8 * slot, (it / FS_N) & 1);
            const uint32_t base = sbase + slot * FS_BYTES + lsel * 14336 + lrow * 128;
#pragma unroll
            for (int j = 0; j < 4; j++) {
                const int nt = warp + j * 16;
                if (nt < 56) {
                    uint32_t b0, b1, b2, b3;
                    ldsm4t(b0, b1, b2, b3, base + (nt >> 3) * 2048 + (((nt & 7) ^ (lrow & 7)) << 4));
                    mma16816(ag[j], a0, a2, b0, b1);
                    mma16816(au[j], a0, a2, b2, b3);
                }
            }
            __syncthreads();
            if (tid == 480) issue(it + FS_N);
        }
        if (g < 2) {
#pragma unroll
            for (int j = 0; j < 4; j++) {
                const int nt = warp + j * 16;
                if (nt < 56) {
#pragma unroll
                    for (int e = 0; e < 2; e++) {
                        const float gs = bfr(ag[j][e]), us = bfr(au[j][e]);
                        const float sg = bfr(gs / (1.f + __expf(-gs)));
                        sh[g * 448 + nt * 8 + t * 2 + e] = __float2bfloat16_rn(sg * us);
                    }
                }
            }
        }
        __syncthreads();
    }
    TL(2);
    {
        const uint32_t* shw = reinterpret_cast<const uint32_t*>(sh);
        float a[4][4];
#pragma unroll
        for (int j = 0; j < 4; j++) a[j][0] = a[j][1] = a[j][2] = a[j][3] = 0.f;
#pragma unroll 1
        for (int it = 32; it < 46; it++) {
            const int slot = it % FS_N;
            uint32_t af[4];
#pragma unroll
            for (int q = 0; q < 4; q++) af[q] = g < 2 ? shw[g * 224 + (it - 32) * 16 + q * 4 + t] : 0u;
            mbar_wait(bars + 8 * slot, (it / FS_N) & 1);
            const uint32_t base = sbase + slot * FS_BYTES + (warp >> 1) * 4096 + lane * 128;
#pragma unroll
            for (int j = 0; j < 4; j++) {
                const int u = (warp & 1) * 4 + j;
                uint32_t b0, b1, b2, b3;
                ldsm4t(b0, b1, b2, b3, base + ((u ^ (lane & 7)) << 4));
                mma16816(a[j], af[0], af[1], b0, b1);
                mma16816(a[j], af[2], af[3], b2, b3);
            }
            __syncthreads();
            if (tid == 480 && it + FS_N < 46) issue(it + FS_N);
        }
        if (g < 2) {
#pragma unroll
            for (int j = 0; j < 4; j++)
                *reinterpret_cast<float2*>(&g_ypart[c * 1024 + g * 512 + (warp * 4 + j) * 8 + t * 2]) = make_float2(a[j][0], a[j][1]);
        }
    }
    warp_arrive(C_FFN);
}

__device__ __forceinline__ void wgmma_n32(float (&d)[16], uint64_t da, uint64_t db, int scale_d) {
    asm volatile("{\n.reg .pred p;\nsetp.ne.b32 p, %18, 0;\n"
        "wgmma.mma_async.sync.aligned.m64n32k16.f32.bf16.bf16 "
        "{%0,%1,%2,%3,%4,%5,%6,%7,%8,%9,%10,%11,%12,%13,%14,%15}, "
        "%16, %17, p, 1, 1, 0, 1;\n}"
        : "+f"(d[0]), "+f"(d[1]), "+f"(d[2]), "+f"(d[3]), "+f"(d[4]), "+f"(d[5]), "+f"(d[6]), "+f"(d[7]),
          "+f"(d[8]), "+f"(d[9]), "+f"(d[10]), "+f"(d[11]), "+f"(d[12]), "+f"(d[13]), "+f"(d[14]), "+f"(d[15])
        : "l"(da), "l"(db), "r"(scale_d));
}

constexpr int G_ST = 4;
constexpr int G_STAGE = 16384 + 24576;
constexpr int SM_KV = 0, KV_CH = 20480, SM_WO = 163840, SM_MISC = 229376;
constexpr int FUSED_SMEM = SM_MISC + 2048;
constexpr int B_FULL = 0, B_EMPTY = 4, B_KV = 8, B_WO = 16, B_OA = 18, B_NUM = 22;

struct Maps { CUtensorMap xn, wqkv, o, wo, g, u, d; };

__global__ void __launch_bounds__(512, 1) fused_kernel(const __grid_constant__ Maps maps, const __nv_bfloat16* __restrict__ x,
                                                       const __nv_bfloat16* __restrict__ wr, __nv_bfloat16* __restrict__ out, float sc) {
    extern __shared__ __align__(1024) uint8_t smem[];
    const uint32_t sbase = smem_u32(smem);
    const int tid = threadIdx.x, warp = __shfl_sync(~0u, tid >> 5, 0), lane = tid & 31;
    const uint32_t bars = sbase + SM_MISC;
    TL(0);
    if (sbase & 1023u) __trap();
    if (blockIdx.x < 4) {
        ffn_block(blockIdx.x, smem, sbase, &maps.g, &maps.u, &maps.d);
        __syncthreads();
        if (tid == 0) exit_ticket();
        TL(3);
    } else {
        const int idx = blockIdx.x - 4;
        const int wg = warp >> 2;
        {
            const int row = idx * 16 + warp;
            const uint4* xr = reinterpret_cast<const uint4*>(x + (size_t)row * DM);
            const uint4 a = xr[lane], b = xr[32 + lane];
            const uint4* wp = reinterpret_cast<const uint4*>(wr);
            const uint4 wa = wp[lane], wb = wp[32 + lane];
            if (tid == 480) {
                for (int s = 0; s < G_ST; s++) { mbar_init(bars + 8 * (B_FULL + s), 2); mbar_init(bars + 8 * (B_EMPTY + s), 2); }
                for (int c = B_KV; c < B_NUM; c++) mbar_init(bars + 8 * c, 1);
                fence_barrier_init();
                for (int c = 0; c < G_ST; c++) {
                    mbar_expect_tx(bars + 8 * (B_FULL + c), 24576);
                    tma3d(sbase + c * G_STAGE + 16384, &maps.wqkv, bars + 8 * (B_FULL + c), c * 64, (idx & 7) * 3);
                }
                map_prefetch(&maps.xn);
            }
            __syncwarp();
            const uint32_t u[8] = {a.x, a.y, a.z, a.w, b.x, b.y, b.z, b.w};
            const uint32_t w[8] = {wa.x, wa.y, wa.z, wa.w, wb.x, wb.y, wb.z, wb.w};
            float f[16];
            float sum = 0.f;
#pragma unroll
            for (int i = 0; i < 8; i++) { f[2 * i] = bf_lo(u[i]); f[2 * i + 1] = bf_hi(u[i]); sum += f[2 * i] + f[2 * i + 1]; }
#pragma unroll
            for (int o = 16; o > 0; o >>= 1) sum += __shfl_xor_sync(~0u, sum, o);
            const float mean = sum * (1.f / DM);
            float sq = 0.f;
#pragma unroll
            for (int i = 0; i < 16; i++) { const float d = f[i] - mean; sq = fmaf(d, d, sq); }
#pragma unroll
            for (int o = 16; o > 0; o >>= 1) sq += __shfl_xor_sync(~0u, sq, o);
            const float mb_ = bfr(mean);
            const float vb = bfr(sq * (1.f / DM));
            const float rinv = 1.f / bfr(sqrtf(bfr(vb + 1e-5f)));
            uint32_t o[8];
            float r = 0.f;
#pragma unroll
            for (int i = 0; i < 8; i++) {
                const float d0 = bfr(f[2 * i] - mb_), d1 = bfr(f[2 * i + 1] - mb_);
                o[i] = packbf(d0 * rinv, d1 * rinv);
                r = fmaf(bf_lo(o[i]), bf_lo(w[i]), r);
                r = fmaf(bf_hi(o[i]), bf_hi(w[i]), r);
            }
            uint4* xo = reinterpret_cast<uint4*>(g_xn + (size_t)row * DM);
            xo[lane] = make_uint4(o[0], o[1], o[2], o[3]);
            xo[32 + lane] = make_uint4(o[4], o[5], o[6], o[7]);
#pragma unroll
            for (int of = 16; of > 0; of >>= 1) r += __shfl_xor_sync(~0u, r, of);
            if (lane == 0) g_r[row] = r;
        }
        __syncthreads();
        if (tid == 416) flag_release(C_LN + (idx >> 3));
        TL(1);
        {
            const int nb = idx & 7, mb = idx >> 3;
            if (warp == 15) {
                for (int c = G_ST; c < 8; c++) {
                    const int s = c - G_ST;
                    mbar_wait(bars + 8 * (B_EMPTY + s), 0);
                    if (lane == 0) {
                        mbar_expect_tx(bars + 8 * (B_FULL + s), 24576);
                        tma3d(sbase + s * G_STAGE + 16384, &maps.wqkv, bars + 8 * (B_FULL + s), c * 64, nb * 3);
                    }
                    __syncwarp();
                }
            } else if (warp == 14) {
                flag_wait(C_LN + mb, 8);
                fence_proxy_async_all();
                for (int c = 0; c < 8; c++) {
                    const int s = c & (G_ST - 1);
                    if (c >= G_ST) mbar_wait(bars + 8 * (B_EMPTY + s), 0);
                    if (lane == 0) {
                        mbar_expect_tx(bars + 8 * (B_FULL + s), 16384);
                        tma3d(sbase + s * G_STAGE, &maps.xn, bars + 8 * (B_FULL + s), mb * 128, c);
                    }
                    __syncwarp();
                }
            } else if (wg < 2) {
                float acc[96];
#pragma unroll
                for (int i = 0; i < 96; i++) acc[i] = 0.f;
#pragma unroll 1
                for (int c = 0; c < 8; c++) {
                    const int s = c & (G_ST - 1);
                    const uint32_t st = sbase + s * G_STAGE;
                    mbar_wait(bars + 8 * (B_FULL + s), c >> 2);
                    if (c == 0) TL(2);
                    const uint64_t da = mkdesc(st + wg * 8192, 16, 1024, 1);
                    const uint64_t db = mkdesc(st + 16384, 8192, 1024, 1);
                    WG_FENCE();
#pragma unroll
                    for (int k = 0; k < 4; k++) wgmma_n192(acc, da + k * 2, db + k * 128, (c | k) != 0);
                    WG_COMMIT();
                    if (c <= G_ST) {
                        WG_WAIT(1);
                        if (c >= 1 && (tid & 127) == 0) mbar_arrive(bars + 8 * (B_EMPTY + c - 1));
                    }
                }
                WG_WAIT(0);
                nbar_arrive(6, 512);
                TL(3);
                const int mt = mb * 8 + warp;
                uint32_t* dst0 = g_qkv + (mt >> 4) * 6144 + (mt & 15) * 64 + lane;
                const int mtk = (mt + 124) & 127;
                const int kshift = ((mtk >> 4) - (mt >> 4)) * 6144 + ((mtk & 15) - (mt & 15)) * 64;
#pragma unroll
                for (int hh = 0; hh < 12; hh++) {
                    const int gh = nb * 12 + hh, ty = gh >> 5;
                    const float* a = &acc[hh * 8];
                    uint32_t* dst = dst0 + (gh & 31) * 49152 + ((ty + 2) % 3) * 2048 + (ty == 1 ? kshift : 0);
                    const uint32_t ks = ty == 1 ? 0x1f801f80u : 0x3f803f80u;
                    dst[0] = hmul2bf(packbf(a[0], a[1]), ks);
                    dst[32] = hmul2bf(packbf(a[2], a[3]), ks);
                    dst[1024] = hmul2bf(packbf(a[4], a[5]), ks);
                    dst[1024 + 32] = hmul2bf(packbf(a[6], a[7]), ks);
                }
                TL(10);
                nbar_sync(8, 256);
                if (tid == 0) flag_release(C_QKV + nb);
            }
        }
        TL(4);
        const int head = idx >> 2, quarter = idx & 3, w4 = warp & 3;
        {
            if (warp == 15) {
                flag_wait_all(C_QKV + ((lane % 3) * 32 + head) / 12, 16);
                nbar_sync(6, 512);
                fence_proxy_async_all();
                if (lane == 0) {
                    const uint8_t* kvp = reinterpret_cast<const uint8_t*>(g_qkv + head * 49152);
#pragma unroll 1
                    for (int i = 0; i < 2; i++) {
                        const int c = (i + 7) & 7;
                        mbar_expect_tx(bars + 8 * (B_KV + c), 16384);
                        bulk_g2s(sbase + SM_KV + c * KV_CH, kvp + c * 24576, 16384, bars + 8 * (B_KV + c));
                    }
                }
                __syncwarp();
            } else if (wg >= 2) {
                nbar_sync(6, 512);
#pragma unroll 1
                for (int i = tid - 256; i < 2048; i += 224)
                    *reinterpret_cast<uint4*>(smem + SM_KV + (i >> 8) * KV_CH + 16384 + (i & 255) * 16) = make_uint4(0x3f803f80u, 0x3f803f80u, 0x3f803f80u, 0x3f803f80u);
                fence_proxy_async();
            }
            __syncthreads();
            if (tid == 480) {
                const uint8_t* kvp = reinterpret_cast<const uint8_t*>(g_qkv + head * 49152);
#pragma unroll 1
                for (int c = 1; c < 7; c++) {
                    mbar_expect_tx(bars + 8 * (B_KV + c), 16384);
                    bulk_g2s(sbase + SM_KV + c * KV_CH, kvp + c * 24576, 16384, bars + 8 * (B_KV + c));
                }
            } else if (tid == 352) {
                mbar_expect_tx(bars + 8 * B_WO, 65536);
                tma3d(sbase + SM_WO, &maps.wo, bars + 8 * B_WO, 0, idx & 7);
                tma3d(sbase + SM_WO + 32768, &maps.wo, bars + 8 * B_WO, 256, idx & 7);
                map_prefetch(&maps.o);
            }
            __syncwarp();
            const uint64_t kdesc0 = mkdesc(sbase + SM_KV, 4096, 128, 0);
            const uint64_t vdesc0 = mkdesc(sbase + SM_KV + 8192, 128, 4096, 0);
#pragma unroll 1
            for (int mt = 0; mt < 2; mt++) {
                const int m64 = quarter * 8 + mt * 4 + wg;
                uint32_t q[4];
                load_q(q, head, m64 * 4 + w4, lane);
                float s[32], s2[32], o[12];
#pragma unroll
                for (int i = 0; i < 12; i++) o[i] = 0.f;
                mbar_wait(bars + 8 * (B_KV + 7), 0);
                if (mt == 0) { TL(5); TLC(12); }
                WG_FENCE();
                qk64(s, q, kdesc0 + (7 * KV_CH + 3 * 1024) / 16);
                WG_COMMIT(); WG_WAIT(0);
                float mx0 = -INFINITY, mx1 = -INFINITY;
#pragma unroll
                for (int i = 0; i < 8; i++) { mx0 = fmaxf(mx0, fmaxf(s[4 * i], s[4 * i + 1])); mx1 = fmaxf(mx1, fmaxf(s[4 * i + 2], s[4 * i + 3])); }
                mx0 = fmaxf(mx0, __shfl_xor_sync(~0u, mx0, 1)); mx0 = fmaxf(mx0, __shfl_xor_sync(~0u, mx0, 2));
                mx1 = fmaxf(mx1, __shfl_xor_sync(~0u, mx1, 1)); mx1 = fmaxf(mx1, __shfl_xor_sync(~0u, mx1, 2));
                float cm0 = -(ceilf(mx0 * QS) + SHIFT), cm1 = -(ceilf(mx1 * QS) + SHIFT);
                float cp0 = (cm0 + 127.f) * sc, cp1 = (cm1 + 127.f) * sc;
                asm volatile("" : "+f"(cm0), "+f"(cm1), "+f"(cp0), "+f"(cp1));
                uint64_t kd = kdesc0, vd = vdesc0;
                auto step = [&](float (&sc_)[32], float (&sn)[32]) {
                    WG_FENCE();
                    qk64(sn, q, kd);
                    WG_COMMIT();
                    kd += 64;
#pragma unroll
                    for (int kk = 0; kk < 4; kk++) {
                        const int i0 = kk * 2, i1 = kk * 2 + 1;
                        const uint32_t p0 = packbf(ex2(fmaf(sc_[4 * i0], QS, cm0)), ex2(fmaf(sc_[4 * i0 + 1], QS, cm0)));
                        const uint32_t p1 = packbf(ex2(fmaf(sc_[4 * i0 + 2], QS, cm1)), ex2(fmaf(sc_[4 * i0 + 3], QS, cm1)));
                        const uint32_t p2 = polyexp(fmaf(sc_[4 * i1], scq, cp0), fmaf(sc_[4 * i1 + 1], scq, cp0));
                        const uint32_t p3 = polyexp(fmaf(sc_[4 * i1 + 2], scq, cp1), fmaf(sc_[4 * i1 + 3], scq, cp1));
                        WG_FENCE();
                        pv24(o, p0, p1, p2, p3, vd);
                        vd += 16;
                    }
                    WG_COMMIT();
                    WG_WAIT(1);
                };
#pragma unroll 1
                for (int c = 0; c < 8; c++) {
                    if (mt == 0) {
                        mbar_wait(bars + 8 * (B_KV + c), 0);
                    } else if (c == 1) {
                        nbar_sync(wg + 1, 128);
                        if ((tid & 127) == 0) flag_release(C_O + m64 - 4);
                    }
#pragma unroll 1
                    for (int i = 0; i < 2; i++) { step(s, s2); step(s2, s); }
                    kd += (KV_CH - 4096) / 16; vd += (KV_CH - 4096) / 16;
                }
                WG_WAIT(0);
                bool bad = !(o[8] > 0.f) || !(o[10] > 0.f);
#pragma unroll
                for (int i = 0; i < 12; i++) bad = bad || !(fabsf(o[i]) <= 3.0e38f);
                if (__any_sync(~0u, bad)) attn_safe(q[0], q[1], q[2], q[3], head, m64, w4, lane);
                else attn_store(o, head, m64, w4, lane);
            }
        }
        nbar_sync(wg + 1, 128);
        if ((tid & 127) == 32) {
            flag_release(C_O + quarter * 8 + 4 + wg);
        }

        TL(6); TLC(13);
        {
            const int nb = idx & 7, jb = idx >> 3;
            const int mbe = (jb >> 2) * 8 + (jb & 3);
            float* supd = reinterpret_cast<float*>(smem + SM_MISC + 512);
            if (warp == 15) nbar_sync(7, 512); else nbar_arrive(7, 512);
            TLX(11, 480);
            if (warp == 15) {
                flag_wait_all((lane & 1) ? C_FFN : C_O + mbe, (lane & 1) ? 64 : 32);
                nbar_arrive(9, 160);
                fence_proxy_async_all();
                if (lane == 0) {
                    for (int c = 0; c < 2; c++) {
                        mbar_expect_tx(bars + 8 * (B_OA + c), 32768);
                        tma3d(sbase + SM_KV + c * 32768, &maps.o, bars + 8 * (B_OA + c), mbe * 64, c * 4);
                    }
                }
                __syncwarp();
                flag_wait(C_O + mbe + 4, 32);
                fence_proxy_async_all();
                if (lane == 0) {
                    for (int c = 0; c < 2; c++) {
                        mbar_expect_tx(bars + 8 * (B_OA + 2 + c), 32768);
                        tma3d(sbase + SM_KV + 65536 + c * 32768, &maps.o, bars + 8 * (B_OA + 2 + c), (mbe + 4) * 64, c * 4);
                    }
                    exit_ticket();
                }
                __syncwarp();
            }
            const int late = wg >> 1, nh = wg & 1;
            const int mb = mbe + late * 4;
            const int g = lane >> 2, t = lane & 3;
            const int row0 = mb * 64 + w4 * 16 + g;
            const int col0 = nb * 64 + nh * 32 + t * 2;
            uint32_t xv[8], nv[8];
#pragma unroll
            for (int i = 0; i < 4; i++) {
                xv[2 * i] = *reinterpret_cast<const uint32_t*>(x + (size_t)row0 * DM + col0 + i * 8);
                xv[2 * i + 1] = *reinterpret_cast<const uint32_t*>(x + (size_t)(row0 + 8) * DM + col0 + i * 8);
                nv[2 * i] = __ldcg(reinterpret_cast<const uint32_t*>(g_xn + (size_t)row0 * DM + col0 + i * 8));
                nv[2 * i + 1] = __ldcg(reinterpret_cast<const uint32_t*>(g_xn + (size_t)(row0 + 8) * DM + col0 + i * 8));
            }
            if (wg == 0) {
                nbar_sync(9, 160);
                const int which = tid >> 6, col = nb * 64 + (tid & 63);
                const float y = __ldcg(&g_ypart[which * 512 + col]) + __ldcg(&g_ypart[1024 + which * 512 + col]) +
                                __ldcg(&g_ypart[2048 + which * 512 + col]) + __ldcg(&g_ypart[3072 + which * 512 + col]);
                supd[tid] = bfr(bfr(y) * __ldcg(&g_gate[which]));
                if (tid < 2) reinterpret_cast<int*>(supd + 128)[tid] = __ldcg(&g_sel[tid]);
            }
            float acc[16];
#pragma unroll
            for (int i = 0; i < 16; i++) acc[i] = 0.f;
            mbar_wait(bars + 8 * B_WO, 0);
            const uint32_t abase = sbase + SM_KV + late * 65536;
#pragma unroll 1
            for (int c = 0; c < 8; c++) {
                if ((c & 3) == 0) mbar_wait(bars + 8 * (B_OA + late * 2 + (c >> 2)), 0);
                if (c == 0) TLX(7, 256);
                const uint64_t da = mkdesc(abase + c * 8192, 16, 1024, 1);
                const uint64_t db = mkdesc(sbase + SM_WO + c * 8192 + nh * 64, 8192, 1024, 1);
                WG_FENCE();
#pragma unroll
                for (int k = 0; k < 4; k++) wgmma_n32(acc, da + k * 2, db + k * 128, (c | k) != 0);
                WG_COMMIT();
            }
            TLX(14, 256);
            __syncthreads();
            TLX(15, 256);
            const int sel0 = reinterpret_cast<const int*>(supd + 128)[0], sel1 = reinterpret_cast<const int*>(supd + 128)[1];
            WG_WAIT(0);
            TLX(8, 256);
#pragma unroll
            for (int h = 0; h < 2; h++) {
                const int row = row0 + h * 8;
                const int which = row == sel0 ? 0 : (row == sel1 ? 1 : -1);
#pragma unroll
                for (int i = 0; i < 4; i++) {
                    const int col = col0 + i * 8;
                    float b0 = bf_lo(nv[2 * i + h]), b1 = bf_hi(nv[2 * i + h]);
                    if (which >= 0) {
                        b0 = bfr(b0 + supd[which * 64 + col - nb * 64]); b1 = bfr(b1 + supd[which * 64 + col + 1 - nb * 64]);
                    }
                    const float t0 = bfr(bf_lo(xv[2 * i + h]) + bfr(acc[4 * i + 2 * h]));
                    const float t1 = bfr(bf_hi(xv[2 * i + h]) + bfr(acc[4 * i + 2 * h + 1]));
                    *reinterpret_cast<uint32_t*>(out + (size_t)row * DM + col) = packbf(t0 + b0, t1 + b1);
                }
            }
        }
        TLX(9, 256);
    }
}

typedef CUresult (*EncodeFn)(CUtensorMap*, CUtensorMapDataType, cuuint32_t, void*, const cuuint64_t*, const cuuint64_t*,
                             const cuuint32_t*, const cuuint32_t*, CUtensorMapInterleave, CUtensorMapSwizzle,
                             CUtensorMapL2promotion, CUtensorMapFloatOOBfill);

void make_map(EncodeFn fn, CUtensorMap* m, const void* ptr, uint64_t cols, uint64_t rows, uint32_t box_rows, uint32_t box_chunks) {
    cuuint64_t dims[3] = {64, rows, cols / 64};
    cuuint64_t strides[2] = {cols * 2, 128};
    cuuint32_t box[3] = {64, box_rows, box_chunks};
    cuuint32_t es[3] = {1, 1, 1};
    fn(m, CU_TENSOR_MAP_DATA_TYPE_BFLOAT16, 3, const_cast<void*>(ptr), dims, strides, box, es, CU_TENSOR_MAP_INTERLEAVE_NONE,
       CU_TENSOR_MAP_SWIZZLE_128B, CU_TENSOR_MAP_L2_PROMOTION_L2_256B, CU_TENSOR_MAP_FLOAT_OOB_FILL_NONE);
}

}

extern "C" void kernel_launch(void* const* d_in, const int* in_sizes, int n_in, void* d_out, int out_size) {
    const __nv_bfloat16* x = (const __nv_bfloat16*)d_in[0];
    const __nv_bfloat16* wqkv = (const __nv_bfloat16*)d_in[1];
    const __nv_bfloat16* wo = (const __nv_bfloat16*)d_in[2];
    const __nv_bfloat16* wr = (const __nv_bfloat16*)d_in[4];
    const __nv_bfloat16* wgate = (const __nv_bfloat16*)d_in[5];
    const __nv_bfloat16* wup = (const __nv_bfloat16*)d_in[6];
    const __nv_bfloat16* wdown = (const __nv_bfloat16*)d_in[7];
    __nv_bfloat16* out = (__nv_bfloat16*)d_out;

    static EncodeFn enc = nullptr;
    static void* p_xn = nullptr; static void* p_o = nullptr;
    if (!enc) {
        void* fn = nullptr; cudaDriverEntryPointQueryResult qr;
        cudaGetDriverEntryPoint("cuTensorMapEncodeTiled", &fn, cudaEnableDefault, &qr);
        enc = (EncodeFn)fn;
        cudaGetSymbolAddress(&p_xn, g_xn);
        cudaGetSymbolAddress(&p_o, g_o);
        cudaFuncSetAttribute(fused_kernel, cudaFuncAttributeMaxDynamicSharedMemorySize, FUSED_SMEM);
    }
    Maps maps;
    make_map(enc, &maps.g, wgate, FF, DM, 16, 7);
    make_map(enc, &maps.u, wup, FF, DM, 16, 7);
    make_map(enc, &maps.d, wdown, DM, FF, 32, 8);
    make_map(enc, &maps.xn, p_xn, DM, S_LEN, 128, 1);
    make_map(enc, &maps.wqkv, wqkv, 3 * DM, DM, 64, 3);
    make_map(enc, &maps.o, p_o, DM, S_LEN, 64, 4);
    make_map(enc, &maps.wo, wo, DM, DM, 256, 1);

    union { uint32_t u; float f; } scu; scu.u = 128u;

    cudaLaunchConfig_t cfg = {};
    cfg.gridDim = dim3(132); cfg.blockDim = dim3(512); cfg.dynamicSmemBytes = FUSED_SMEM; cfg.stream = cudaStreamPerThread;
    cudaLaunchKernelEx(&cfg, fused_kernel, maps, x, wr, out, scu.f);
}
```

```cpp
#include <cuda_runtime.h>
#include <cuda_bf16.h>
#include <cuda.h>
#include <stdint.h>
#include <type_traits>

namespace {

constexpr int S_LEN = 2048;
constexpr int DM = 512;
constexpr int NH = 32;
constexpr int FF = 1792;

__device__ __align__(1024) __nv_bfloat16 g_xn[S_LEN * DM];
__device__ __align__(16) float g_r[S_LEN];
__device__ __align__(1024) uint32_t g_qkv[NH * 8 * 6144];
__device__ __align__(1024) __nv_bfloat16 g_o[S_LEN * DM];
__device__ __align__(16) float g_ypart[4 * 2 * DM];
__device__ int g_sel[2];
__device__ float g_gate[2];
constexpr int C_LN = 0, C_QKV = 16, C_O = 24, C_FFN = 56, C_EXIT = 57, C_NUM = 58;
__device__ unsigned g_cnt[C_NUM * 32];

#define TLC(slot) do {} while (0)
#define TL(slot) do {} while (0)
#define TLX(slot, th) do {} while (0)

__device__ __forceinline__ uint32_t smem_u32(const void* p) { return (uint32_t)__cvta_generic_to_shared(p); }
__device__ __forceinline__ void warp_arrive(int idx) {
    __syncwarp();
    if ((threadIdx.x & 31) == 0)
        asm volatile("red.release.gpu.global.add.u32 [%0], 1;" :: "l"(g_cnt + idx * 32) : "memory");
}
__device__ __forceinline__ void flag_release(int idx) {
    asm volatile("red.release.gpu.global.add.u32 [%0], 1;" :: "l"(g_cnt + idx * 32) : "memory");
}
__device__ __forceinline__ void exit_ticket() {
    unsigned tk;
    asm volatile("atom.relaxed.gpu.global.add.u32 %0, [%1], 1;" : "=r"(tk) : "l"(g_cnt + C_EXIT * 32) : "memory");
    if (tk == gridDim.x - 1) {
#pragma unroll 1
        for (int i = 0; i < C_NUM; i++) g_cnt[i * 32] = 0u;
    }
}
__device__ __forceinline__ void nbar_arrive(int id, int cnt) { asm volatile("bar.arrive %0, %1;" :: "r"(id), "r"(cnt) : "memory"); }
__device__ __forceinline__ void nbar_sync(int id, int cnt) { asm volatile("bar.sync %0, %1;" :: "r"(id), "r"(cnt) : "memory"); }
__device__ __forceinline__ void flag_wait(int idx, unsigned target) {
    asm volatile("{\n.reg .pred p;\n.reg .u32 n, v;\nmov.u32 n, 0;\n"
                 "FW_%=:\n"
                 "ld.acquire.gpu.global.u32 v, [%0];\n"
                 "setp.ge.u32 p, v, %1;\n"
                 "@p bra FD_%=;\n"
                 "add.u32 n, n, 1;\n"
                 "setp.lt.u32 p, n, 16000000;\n"
                 "@p bra FW_%=;\n"
                 "trap;\n"
                 "FD_%=:\n}"
                 :: "l"(g_cnt + idx * 32), "r"(target) : "memory");
}
__device__ __forceinline__ void flag_wait_all(int idx, unsigned target) {
    asm volatile("{\n.reg .pred p;\n.reg .u32 n, v;\nmov.u32 n, 0;\n"
                 "FW_%=:\n"
                 "ld.acquire.gpu.global.u32 v, [%0];\n"
                 "setp.ge.u32 p, v, %1;\n"
                 "vote.sync.all.pred p, p, 0xffffffff;\n"
                 "@p bra.uni FD_%=;\n"
                 "add.u32 n, n, 1;\n"
                 "setp.lt.u32 p, n, 16000000;\n"
                 "@p bra.uni FW_%=;\n"
                 "trap;\n"
                 "FD_%=:\n}"
                 :: "l"(g_cnt + idx * 32), "r"(target) : "memory");
}
__device__ __forceinline__ void fence_proxy_async_all() { asm volatile("fence.proxy.async.global;" ::: "memory"); }
__device__ __forceinline__ void mbar_init(uint32_t bar, uint32_t cnt) {
    asm volatile("mbarrier.init.shared::cta.b64 [%0], %1;" :: "r"(bar), "r"(cnt) : "memory");
}
__device__ __forceinline__ void mbar_expect_tx(uint32_t bar, uint32_t bytes) {
    asm volatile("mbarrier.arrive.expect_tx.shared::cta.b64 _, [%0], %1;" :: "r"(bar), "r"(bytes) : "memory");
}
__device__ __forceinline__ void mbar_arrive(uint32_t bar) {
    asm volatile("mbarrier.arrive.shared::cta.b64 _, [%0];" :: "r"(bar) : "memory");
}
__device__ __forceinline__ void mbar_wait(uint32_t bar, uint32_t parity) {
    asm volatile("{\n.reg .pred p, q;\n.reg .u32 n;\nmov.u32 n, 0;\n"
                 "WAIT_%=:\n"
                 "mbarrier.try_wait.parity.shared::cta.b64 p, [%0], %1;\n"
                 "add.u32 n, n, 1;\n"
                 "setp.lt.and.u32 q, n, 4000000, !p;\n"
                 "@q bra WAIT_%=;\n"
                 "@!p trap;\n}"
                 :: "r"(bar), "r"(parity) : "memory");
}
__device__ __forceinline__ void fence_barrier_init() { asm volatile("fence.mbarrier_init.release.cluster;" ::: "memory"); }
__device__ __forceinline__ void fence_proxy_async() { asm volatile("fence.proxy.async.shared::cta;" ::: "memory"); }
__device__ __forceinline__ void tma3d(uint32_t dst, const CUtensorMap* map, uint32_t bar, int row, int chunk) {
    asm volatile("cp.async.bulk.tensor.3d.shared::cluster.global.mbarrier::complete_tx::bytes [%0], [%1, {%3, %4, %5}], [%2];"
                 :: "r"(dst), "l"((uint64_t)map), "r"(bar), "r"(0), "r"(row), "r"(chunk) : "memory");
}
__device__ __forceinline__ void bulk_g2s(uint32_t dst, const void* src, uint32_t bytes, uint32_t bar) {
    asm volatile("cp.async.bulk.shared::cluster.global.mbarrier::complete_tx::bytes [%0], [%1], %2, [%3];"
                 :: "r"(dst), "l"((uint64_t)src), "r"(bytes), "r"(bar) : "memory");
}
__device__ __forceinline__ void l2_prefetch(const void* src, uint32_t bytes) {
    asm volatile("cp.async.bulk.prefetch.L2.global [%0], %1;" :: "l"((uint64_t)src), "r"(bytes) : "memory");
}
__device__ __forceinline__ void map_prefetch(const CUtensorMap* m) {
    asm volatile("prefetch.tensormap [%0];" :: "l"((uint64_t)m) : "memory");
}
__device__ __forceinline__ uint64_t mkdesc(uint32_t addr, uint32_t lbo, uint32_t sbo, uint32_t swz) {
    return (uint64_t)((addr & 0x3FFFF) >> 4) | ((uint64_t)(lbo >> 4) << 16) | ((uint64_t)(sbo >> 4) << 32) | ((uint64_t)swz << 62);
}
#define WG_FENCE() asm volatile("wgmma.fence.sync.aligned;" ::: "memory")
#define WG_COMMIT() asm volatile("wgmma.commit_group.sync.aligned;" ::: "memory")
#define WG_WAIT(n) asm volatile("wgmma.wait_group.sync.aligned %0;" :: "n"(n) : "memory")

__device__ __forceinline__ float ex2(float x) { float y; asm("ex2.approx.ftz.f32 %0, %1;" : "=f"(y) : "f"(x)); return y; }
__device__ __forceinline__ uint32_t packbf(float lo, float hi) {
    uint32_t r; asm("cvt.rn.bf16x2.f32 %0, %1, %2;" : "=r"(r) : "f"(hi), "f"(lo)); return r;
}
__device__ __forceinline__ uint32_t hmul2bf(uint32_t a, uint32_t b) { uint32_t r; asm("mul.rn.bf16x2 %0, %1, %2;" : "=r"(r) : "r"(a), "r"(b)); return r; }
__device__ __forceinline__ float bf_lo(uint32_t v) { return __uint_as_float(v << 16); }
__device__ __forceinline__ float bf_hi(uint32_t v) { return __uint_as_float(v & 0xffff0000u); }
__device__ __forceinline__ float bfr(float x) { return __bfloat162float(__float2bfloat16_rn(x)); }

__device__ __forceinline__ void wgmma_n192(float (&d)[96], uint64_t da, uint64_t db, int scale_d) {
    asm volatile("{\n.reg .pred p;\nsetp.ne.b32 p, %98, 0;\n"
        "wgmma.mma_async.sync.aligned.m64n192k16.f32.bf16.bf16 "
        "{%0,%1,%2,%3,%4,%5,%6,%7,%8,%9,%10,%11,%12,%13,%14,%15,%16,%17,%18,%19,%20,%21,%22,%23,"
        "%24,%25,%26,%27,%28,%29,%30,%31,%32,%33,%34,%35,%36,%37,%38,%39,%40,%41,%42,%43,%44,%45,%46,%47,"
        "%48,%49,%50,%51,%52,%53,%54,%55,%56,%57,%58,%59,%60,%61,%62,%63,%64,%65,%66,%67,%68,%69,%70,%71,"
        "%72,%73,%74,%75,%76,%77,%78,%79,%80,%81,%82,%83,%84,%85,%86,%87,%88,%89,%90,%91,%92,%93,%94,%95}, "
        "%96, %97, p, 1, 1, 0, 1;\n}"
        : "+f"(d[0]), "+f"(d[1]), "+f"(d[2]), "+f"(d[3]), "+f"(d[4]), "+f"(d[5]), "+f"(d[6]), "+f"(d[7]),
          "+f"(d[8]), "+f"(d[9]), "+f"(d[10]), "+f"(d[11]), "+f"(d[12]), "+f"(d[13]), "+f"(d[14]), "+f"(d[15]),
          "+f"(d[16]), "+f"(d[17]), "+f"(d[18]), "+f"(d[19]), "+f"(d[20]), "+f"(d[21]), "+f"(d[22]), "+f"(d[23]),
          "+f"(d[24]), "+f"(d[25]), "+f"(d[26]), "+f"(d[27]), "+f"(d[28]), "+f"(d[29]), "+f"(d[30]), "+f"(d[31]),
          "+f"(d[32]), "+f"(d[33]), "+f"(d[34]), "+f"(d[35]), "+f"(d[36]), "+f"(d[37]), "+f"(d[38]), "+f"(d[39]),
          "+f"(d[40]), "+f"(d[41]), "+f"(d[42]), "+f"(d[43]), "+f"(d[44]), "+f"(d[45]), "+f"(d[46]), "+f"(d[47]),
          "+f"(d[48]), "+f"(d[49]), "+f"(d[50]), "+f"(d[51]), "+f"(d[52]), "+f"(d[53]), "+f"(d[54]), "+f"(d[55]),
          "+f"(d[56]), "+f"(d[57]), "+f"(d[58]), "+f"(d[59]), "+f"(d[60]), "+f"(d[61]), "+f"(d[62]), "+f"(d[63]),
          "+f"(d[64]), "+f"(d[65]), "+f"(d[66]), "+f"(d[67]), "+f"(d[68]), "+f"(d[69]), "+f"(d[70]), "+f"(d[71]),
          "+f"(d[72]), "+f"(d[73]), "+f"(d[74]), "+f"(d[75]), "+f"(d[76]), "+f"(d[77]), "+f"(d[78]), "+f"(d[79]),
          "+f"(d[80]), "+f"(d[81]), "+f"(d[82]), "+f"(d[83]), "+f"(d[84]), "+f"(d[85]), "+f"(d[86]), "+f"(d[87]),
          "+f"(d[88]), "+f"(d[89]), "+f"(d[90]), "+f"(d[91]), "+f"(d[92]), "+f"(d[93]), "+f"(d[94]), "+f"(d[95])
        : "l"(da), "l"(db), "r"(scale_d));
}

constexpr float SHIFT = 90.0f;
constexpr float QS = 0.25f * 1.4426950408889634f * 18446744073709551616.0f;
constexpr float scq = 0.25f * 1.4426950408889634f * 3.3087224502121107e-24f;

__device__ __forceinline__ uint32_t polyexp(float lo, float hi) {
    uint32_t w, g, q, h;
    asm("cvt.pack.sat.s16.s32 %0, %1, %2;" : "=r"(w) : "r"(__float_as_uint(hi)), "r"(__float_as_uint(lo)));
    g = w & 0x007F007Fu;
    asm("fma.rn.f16x2 %0, %1, %2, %3;" : "=r"(q) : "r"(g), "r"(0xf940f940u), "r"(0x35513551u));
    asm("mul.rn.f16x2 %0, %1, %2;" : "=r"(h) : "r"(q), "r"(g));
    return w - h;
}
__device__ __forceinline__ void qk64(float (&s)[32], const uint32_t (&q)[4], uint64_t db) {
    asm volatile("wgmma.mma_async.sync.aligned.m64n64k16.f32.bf16.bf16 "
        "{%0,%1,%2,%3,%4,%5,%6,%7,%8,%9,%10,%11,%12,%13,%14,%15,%16,%17,%18,%19,%20,%21,%22,%23,%24,%25,%26,%27,%28,%29,%30,%31}, "
        "{%32,%33,%34,%35}, %36, 0, 1, 1, 0;"
        : "=f"(s[0]), "=f"(s[1]), "=f"(s[2]), "=f"(s[3]), "=f"(s[4]), "=f"(s[5]), "=f"(s[6]), "=f"(s[7]),
          "=f"(s[8]), "=f"(s[9]), "=f"(s[10]), "=f"(s[11]), "=f"(s[12]), "=f"(s[13]), "=f"(s[14]), "=f"(s[15]),
          "=f"(s[16]), "=f"(s[17]), "=f"(s[18]), "=f"(s[19]), "=f"(s[20]), "=f"(s[21]), "=f"(s[22]), "=f"(s[23]),
          "=f"(s[24]), "=f"(s[25]), "=f"(s[26]), "=f"(s[27]), "=f"(s[28]), "=f"(s[29]), "=f"(s[30]), "=f"(s[31])
        : "r"(q[0]), "r"(q[1]), "r"(q[2]), "r"(q[3]), "l"(db));
}
__device__ __forceinline__ void pv24(float (&o)[12], uint32_t a0, uint32_t a1, uint32_t a2, uint32_t a3, uint64_t db) {
    asm volatile("wgmma.mma_async.sync.aligned.m64n24k16.f32.bf16.bf16 "
        "{%0,%1,%2,%3,%4,%5,%6,%7,%8,%9,%10,%11}, {%12,%13,%14,%15}, %16, 1, 1, 1, 1;"
        : "+f"(o[0]), "+f"(o[1]), "+f"(o[2]), "+f"(o[3]), "+f"(o[4]), "+f"(o[5]), "+f"(o[6]), "+f"(o[7]),
          "+f"(o[8]), "+f"(o[9]), "+f"(o[10]), "+f"(o[11])
        : "r"(a0), "r"(a1), "r"(a2), "r"(a3), "l"(db));
}

__device__ __forceinline__ void load_q(uint32_t (&q)[4], int head, int mt, int lane) {
    const uint32_t* src = g_qkv + head * 49152 + (mt >> 4) * 6144 + 4096 + (mt & 15) * 64 + lane;
    q[0] = __ldcg(src); q[1] = __ldcg(src + 32); q[2] = __ldcg(src + 1024); q[3] = __ldcg(src + 1024 + 32);
}
__device__ __forceinline__ void attn_store(const float (&o)[12], int head, int m64, int warp, int lane) {
    const int g = lane >> 2, t = lane & 3;
    const int row = m64 * 64 + warp * 16 + g;
    const float i0 = 1.f / o[8], i1 = 1.f / o[10];
    uint32_t* p0 = reinterpret_cast<uint32_t*>(g_o + (size_t)row * DM + head * 16 + t * 2);
    uint32_t* p1 = reinterpret_cast<uint32_t*>(g_o + (size_t)(row + 8) * DM + head * 16 + t * 2);
    p0[0] = packbf(o[0] * i0, o[1] * i0); p0[4] = packbf(o[4] * i0, o[5] * i0);
    p1[0] = packbf(o[2] * i1, o[3] * i1); p1[4] = packbf(o[6] * i1, o[7] * i1);
}

__device__ __forceinline__ void mma_full(float (&d)[4], uint32_t a0, uint32_t a1, uint32_t a2, uint32_t a3, uint32_t b0, uint32_t b1) {
    asm volatile("mma.sync.aligned.m16n8k16.row.col.f32.bf16.bf16.f32 {%0,%1,%2,%3}, {%4,%5,%6,%7}, {%8,%9}, {%0,%1,%2,%3};"
                 : "+f"(d[0]), "+f"(d[1]), "+f"(d[2]), "+f"(d[3]) : "r"(a0), "r"(a1), "r"(a2), "r"(a3), "r"(b0), "r"(b1));
}
__device__ __forceinline__ uint32_t movt(uint32_t a) {
    uint32_t r; asm volatile("movmatrix.sync.aligned.m8n8.trans.b16 %0, %1;" : "=r"(r) : "r"(a)); return r;
}
__device__ __noinline__ void attn_safe(uint32_t q0, uint32_t q1, uint32_t q2, uint32_t q3, int head, int m64, int w4, int lane) {
    float o0[4] = {0.f, 0.f, 0.f, 0.f}, o1[4] = {0.f, 0.f, 0.f, 0.f};
    float m0 = -INFINITY, m1 = -INFINITY, l0 = 0.f, l1 = 0.f;
#pragma unroll 1
    for (int kb = 0; kb < 128; kb++) {
        const uint32_t* src = g_qkv + head * 49152 + (kb >> 4) * 6144 + (kb & 15) * 64 + lane;
        const int kk = (kb + 124) & 127;
        const uint32_t* srck = g_qkv + head * 49152 + (kk >> 4) * 6144 + (kk & 15) * 64 + lane;
        float sa[4] = {0.f, 0.f, 0.f, 0.f}, sb[4] = {0.f, 0.f, 0.f, 0.f};
        mma_full(sa, q0, q1, q2, q3, __ldcg(srck), __ldcg(srck + 1024));
        mma_full(sb, q0, q1, q2, q3, __ldcg(srck + 32), __ldcg(srck + 1024 + 32));
        float n0 = fmaxf(fmaxf(m0, fmaxf(sa[0], sa[1])), fmaxf(sb[0], sb[1]));
        float n1 = fmaxf(fmaxf(m1, fmaxf(sa[2], sa[3])), fmaxf(sb[2], sb[3]));
        n0 = fmaxf(n0, __shfl_xor_sync(~0u, n0, 1)); n0 = fmaxf(n0, __shfl_xor_sync(~0u, n0, 2));
        n1 = fmaxf(n1, __shfl_xor_sync(~0u, n1, 1)); n1 = fmaxf(n1, __shfl_xor_sync(~0u, n1, 2));
        const float c0 = ex2((m0 - n0) * QS), c1 = ex2((m1 - n1) * QS);
        m0 = n0; m1 = n1;
        const uint32_t p0 = packbf(ex2((sa[0] - m0) * QS), ex2((sa[1] - m0) * QS));
        const uint32_t p1 = packbf(ex2((sa[2] - m1) * QS), ex2((sa[3] - m1) * QS));
        const uint32_t p2 = packbf(ex2((sb[0] - m0) * QS), ex2((sb[1] - m0) * QS));
        const uint32_t p3 = packbf(ex2((sb[2] - m1) * QS), ex2((sb[3] - m1) * QS));
        l0 = l0 * c0 + (bf_lo(p0) + bf_hi(p0)) + (bf_lo(p2) + bf_hi(p2));
        l1 = l1 * c1 + (bf_lo(p1) + bf_hi(p1)) + (bf_lo(p3) + bf_hi(p3));
        o0[0] *= c0; o0[1] *= c0; o0[2] *= c1; o0[3] *= c1;
        o1[0] *= c0; o1[1] *= c0; o1[2] *= c1; o1[3] *= c1;
        mma_full(o0, p0, p1, p2, p3, movt(__ldcg(src + 2048)), movt(__ldcg(src + 2048 + 32)));
        mma_full(o1, p0, p1, p2, p3, movt(__ldcg(src + 3072)), movt(__ldcg(src + 3072 + 32)));
    }
    l0 += __shfl_xor_sync(~0u, l0, 1); l0 += __shfl_xor_sync(~0u, l0, 2);
    l1 += __shfl_xor_sync(~0u, l1, 1); l1 += __shfl_xor_sync(~0u, l1, 2);
    const float o[12] = {o0[0], o0[1], o0[2], o0[3], o1[0], o1[1], o1[2], o1[3], l0, l0, l1, l1};
    attn_store(o, head, m64, w4, lane);
}

constexpr int FS_N = 4;
constexpr int FS_BYTES = 32768;
__device__ __forceinline__ void ldsm4t(uint32_t& r0, uint32_t& r1, uint32_t& r2, uint32_t& r3, uint32_t addr) {
    asm volatile("ldmatrix.sync.aligned.m8n8.x4.trans.shared.b16 {%0,%1,%2,%3}, [%4];" : "=r"(r0), "=r"(r1), "=r"(r2), "=r"(r3) : "r"(addr) : "memory");
}
__device__ __forceinline__ void mma16816(float (&d)[4], uint32_t a0, uint32_t a2, uint32_t b0, uint32_t b1) {
    asm volatile("mma.sync.aligned.m16n8k16.row.col.f32.bf16.bf16.f32 {%0,%1,%2,%3}, {%4,%5,%6,%5}, {%7,%8}, {%0,%1,%2,%3};"
                 : "+f"(d[0]), "+f"(d[1]), "+f"(d[2]), "+f"(d[3]) : "r"(a0), "r"(0u), "r"(a2), "r"(b0), "r"(b1));
}
__device__ void ffn_block(int c, uint8_t* smem, uint32_t sbase, const CUtensorMap* mapG, const CUtensorMap* mapU, const CUtensorMap* mapD) {
    const int tid = threadIdx.x, warp = tid >> 5, lane = tid & 31;
    uint32_t* sx = reinterpret_cast<uint32_t*>(smem + FS_N * FS_BYTES);
    __nv_bfloat16* sh = reinterpret_cast<__nv_bfloat16*>(sx + 512);
    const uint32_t bars = sbase + FS_N * FS_BYTES + 8192;
    float* tv = reinterpret_cast<float*>(smem + FS_N * FS_BYTES + 4096);
    int* ti = reinterpret_cast<int*>(tv + 32);
    int* ssel = ti + 32;
    auto issue = [&](int item) {
        const int slot = item % FS_N;
        const uint32_t dst = sbase + slot * FS_BYTES, bar = bars + 8 * slot;
        mbar_expect_tx(bar, item < 32 ? 28672 : 32768);
        if (item < 32) {
            tma3d(dst, mapG, bar, item * 16, c * 7);
            tma3d(dst + 14336, mapU, bar, item * 16, c * 7);
        } else {
            tma3d(dst, mapD, bar, c * 448 + (item - 32) * 32, 0);
        }
    };
    if (tid == 0) {
        for (int i = 0; i < FS_N; i++) mbar_init(bars + 8 * i, 1);
        fence_barrier_init();
        for (int i = 0; i < FS_N; i++) issue(i);
    }
    flag_wait(C_LN + warp, 8);
    __syncthreads();
    float b1 = -INFINITY, b2 = -INFINITY; int i1 = 0x7fffffff, i2 = 0x7fffffff;
    auto push = [&](float v, int i) {
        if (v > b1 || (v == b1 && i < i1)) { b2 = b1; i2 = i1; b1 = v; i1 = i; }
        else if (v > b2 || (v == b2 && i < i2)) { b2 = v; i2 = i; }
    };
    {
        const float4 rv = __ldcg(reinterpret_cast<const float4*>(g_r) + tid);
        push(rv.x, 4 * tid); push(rv.y, 4 * tid + 1); push(rv.z, 4 * tid + 2); push(rv.w, 4 * tid + 3);
    }
#pragma unroll
    for (int o = 16; o > 0; o >>= 1) {
        float v1 = __shfl_xor_sync(~0u, b1, o), v2 = __shfl_xor_sync(~0u, b2, o);
        int j1 = __shfl_xor_sync(~0u, i1, o), j2 = __shfl_xor_sync(~0u, i2, o);
        push(v1, j1); push(v2, j2);
    }
    if (lane == 0) { tv[2 * warp] = b1; ti[2 * warp] = i1; tv[2 * warp + 1] = b2; ti[2 * warp + 1] = i2; }
    __syncthreads();
    if (warp == 1) {
        b1 = tv[lane]; i1 = ti[lane]; b2 = -INFINITY; i2 = 0x7fffffff;
#pragma unroll
        for (int o = 16; o > 0; o >>= 1) {
            float v1 = __shfl_xor_sync(~0u, b1, o), v2 = __shfl_xor_sync(~0u, b2, o);
            int j1 = __shfl_xor_sync(~0u, i1, o), j2 = __shfl_xor_sync(~0u, i2, o);
            push(v1, j1); push(v2, j2);
        }
        if (lane == 0) {
            i1 = min(max(i1, 0), S_LEN - 1); i2 = min(max(i2, 0), S_LEN - 1);
            ssel[0] = i1; ssel[1] = i2;
            if (c == 0) {
                g_sel[0] = i1; g_sel[1] = i2;
                g_gate[0] = bfr(1.f / (1.f + __expf(-bfr(b1))));
                g_gate[1] = bfr(1.f / (1.f + __expf(-bfr(b2))));
            }
        }
    }
    __syncthreads();
    sx[tid] = __ldcg(reinterpret_cast<const uint32_t*>(g_xn + (size_t)ssel[tid >> 8] * DM + (tid & 255) * 2));
    __syncthreads();
    TL(1);
    const int g = lane >> 2, t = lane & 3;
    const int lrow = lane & 15, lsel = lane >> 4;
    {
        float ag[4][4], au[4][4];
#pragma unroll
        for (int j = 0; j < 4; j++) { ag[j][0] = ag[j][1] = ag[j][2] = ag[j][3] = 0.f; au[j][0] = au[j][1] = au[j][2] = au[j][3] = 0.f; }
#pragma unroll 1
        for (int it = 0; it < 32; it++) {
            const int slot = it % FS_N;
            const uint32_t a0 = g < 2 ? sx[g * 256 + it * 8 + t] : 0u, a2 = g < 2 ? sx[g * 256 + it * 8 + 4 + t] : 0u;
            mbar_wait(bars + 8 * slot, (it / FS_N) & 1);
            const uint32_t base = sbase + slot * FS_BYTES + lsel * 14336 + lrow * 128;
#pragma unroll
            for (int j = 0; j < 4; j++) {
                const int nt = warp + j * 16;
                if (nt < 56) {
                    uint32_t b0, b1, b2, b3;
                    ldsm4t(b0, b1, b2, b3, base + (nt >> 3) * 2048 + (((nt & 7) ^ (lrow & 7)) << 4));
                    mma16816(ag[j], a0, a2, b0, b1);
                    mma16816(au[j], a0, a2, b2, b3);
                }
            }
            __syncthreads();
            if (tid == 480) issue(it + FS_N);
        }
        if (g < 2) {
#pragma unroll
            for (int j = 0; j < 4; j++) {
                const int nt = warp + j * 16;
                if (nt < 56) {
#pragma unroll
                    for (int e = 0; e < 2; e++) {
                        const float gs = bfr(ag[j][e]), us = bfr(au[j][e]);
                        const float sg = bfr(gs / (1.f + __expf(-gs)));
                        sh[g * 448 + nt * 8 + t * 2 + e] = __float2bfloat16_rn(sg * us);
                    }
                }
            }
        }
        __syncthreads();
    }
    TL(2);
    {
        const uint32_t* shw = reinterpret_cast<const uint32_t*>(sh);
        float a[4][4];
#pragma unroll
        for (int j = 0; j < 4; j++) a[j][0] = a[j][1] = a[j][2] = a[j][3] = 0.f;
#pragma unroll 1
        for (int it = 32; it < 46; it++) {
            const int slot = it % FS_N;
            uint32_t af[4];
#pragma unroll
            for (int q = 0; q < 4; q++) af[q] = g < 2 ? shw[g * 224 + (it - 32) * 16 + q * 4 + t] : 0u;
            mbar_wait(bars + 8 * slot, (it / FS_N) & 1);
            const uint32_t base = sbase + slot * FS_BYTES + (warp >> 1) * 4096 + lane * 128;
#pragma unroll
            for (int j = 0; j < 4; j++) {
                const int u = (warp & 1) * 4 + j;
                uint32_t b0, b1, b2, b3;
                ldsm4t(b0, b1, b2, b3, base + ((u ^ (lane & 7)) << 4));
                mma16816(a[j], af[0], af[1], b0, b1);
                mma16816(a[j], af[2], af[3], b2, b3);
            }
            __syncthreads();
            if (tid == 480 && it + FS_N < 46) issue(it + FS_N);
        }
        if (g < 2) {
#pragma unroll
            for (int j = 0; j < 4; j++)
                *reinterpret_cast<float2*>(&g_ypart[c * 1024 + g * 512 + (warp * 4 + j) * 8 + t * 2]) = make_float2(a[j][0], a[j][1]);
        }
    }
    warp_arrive(C_FFN);
}

__device__ __forceinline__ void wgmma_n32(float (&d)[16], uint64_t da, uint64_t db, int scale_d) {
    asm volatile("{\n.reg .pred p;\nsetp.ne.b32 p, %18, 0;\n"
        "wgmma.mma_async.sync.aligned.m64n32k16.f32.bf16.bf16 "
        "{%0,%1,%2,%3,%4,%5,%6,%7,%8,%9,%10,%11,%12,%13,%14,%15}, "
        "%16, %17, p, 1, 1, 0, 1;\n}"
        : "+f"(d[0]), "+f"(d[1]), "+f"(d[2]), "+f"(d[3]), "+f"(d[4]), "+f"(d[5]), "+f"(d[6]), "+f"(d[7]),
          "+f"(d[8]), "+f"(d[9]), "+f"(d[10]), "+f"(d[11]), "+f"(d[12]), "+f"(d[13]), "+f"(d[14]), "+f"(d[15])
        : "l"(da), "l"(db), "r"(scale_d));
}

constexpr int G_ST = 4;
constexpr int G_STAGE = 16384 + 24576;
constexpr int SM_KV = 0, KV_CH = 20480, SM_WO = 163840, SM_MISC = 229376;
constexpr int FUSED_SMEM = SM_MISC + 2048;
constexpr int B_FULL = 0, B_EMPTY = 4, B_KV = 8, B_WO = 16, B_OA = 18, B_NUM = 22;

struct Maps { CUtensorMap xn, wqkv, o, wo, g, u, d; };

__global__ void __launch_bounds__(512, 1) fused_kernel(const __grid_constant__ Maps maps, const __nv_bfloat16* __restrict__ x,
                                                       const __nv_bfloat16* __restrict__ wr, __nv_bfloat16* __restrict__ out, float sc) {
    extern __shared__ __align__(1024) uint8_t smem[];
    const uint32_t sbase = smem_u32(smem);
    const int tid = threadIdx.x, warp = __shfl_sync(~0u, tid >> 5, 0), lane = tid & 31;
    const uint32_t bars = sbase + SM_MISC;
    TL(0);
    if (sbase & 1023u) __trap();
    if (blockIdx.x < 4) {
        ffn_block(blockIdx.x, smem, sbase, &maps.g, &maps.u, &maps.d);
        __syncthreads();
        if (tid == 0) exit_ticket();
        TL(3);
    } else {
        const int idx = blockIdx.x - 4;
        const int wg = warp >> 2;
        {
            const int row = idx * 16 + warp;
            const uint4* xr = reinterpret_cast<const uint4*>(x + (size_t)row * DM);
            const uint4 a = xr[lane], b = xr[32 + lane];
            const uint4* wp = reinterpret_cast<const uint4*>(wr);
            const uint4 wa = wp[lane], wb = wp[32 + lane];
            if (tid == 480) {
                for (int s = 0; s < G_ST; s++) { mbar_init(bars + 8 * (B_FULL + s), 2); mbar_init(bars + 8 * (B_EMPTY + s), 2); }
                for (int c = B_KV; c < B_NUM; c++) mbar_init(bars + 8 * c, 1);
                fence_barrier_init();
                for (int c = 0; c < G_ST; c++) {
                    mbar_expect_tx(bars + 8 * (B_FULL + c), 24576);
                    tma3d(sbase + c * G_STAGE + 16384, &maps.wqkv, bars + 8 * (B_FULL + c), c * 64, (idx & 7) * 3);
                }
                map_prefetch(&maps.xn);
            }
            __syncwarp();
            const uint32_t u[8] = {a.x, a.y, a.z, a.w, b.x, b.y, b.z, b.w};
            const uint32_t w[8] = {wa.x, wa.y, wa.z, wa.w, wb.x, wb.y, wb.z, wb.w};
            float f[16];
            float sum = 0.f;
#pragma unroll
            for (int i = 0; i < 8; i++) { f[2 * i] = bf_lo(u[i]); f[2 * i + 1] = bf_hi(u[i]); sum += f[2 * i] + f[2 * i + 1]; }
#pragma unroll
            for (int o = 16; o > 0; o >>= 1) sum += __shfl_xor_sync(~0u, sum, o);
            const float mean = sum * (1.f / DM);
            float sq = 0.f;
#pragma unroll
            for (int i = 0; i < 16; i++) { const float d = f[i] - mean; sq = fmaf(d, d, sq); }
#pragma unroll
            for (int o = 16; o > 0; o >>= 1) sq += __shfl_xor_sync(~0u, sq, o);
            const float mb_ = bfr(mean);
            const float vb = bfr(sq * (1.f / DM));
            const float rinv = 1.f / bfr(sqrtf(bfr(vb + 1e-5f)));
            uint32_t o[8];
            float r = 0.f;
#pragma unroll
            for (int i = 0; i < 8; i++) {
                const float d0 = bfr(f[2 * i] - mb_), d1 = bfr(f[2 * i + 1] - mb_);
                o[i] = packbf(d0 * rinv, d1 * rinv);
                r = fmaf(bf_lo(o[i]), bf_lo(w[i]), r);
                r = fmaf(bf_hi(o[i]), bf_hi(w[i]), r);
            }
            uint4* xo = reinterpret_cast<uint4*>(g_xn + (size_t)row * DM);
            xo[lane] = make_uint4(o[0], o[1], o[2], o[3]);
            xo[32 + lane] = make_uint4(o[4], o[5], o[6], o[7]);
#pragma unroll
            for (int of = 16; of > 0; of >>= 1) r += __shfl_xor_sync(~0u, r, of);
            if (lane == 0) g_r[row] = r;
        }
        __syncthreads();
        if (tid == 416) flag_release(C_LN + (idx >> 3));
        TL(1);
        {
            const int nb = idx & 7, mb = idx >> 3;
            if (warp == 15) {
                for (int c = G_ST; c < 8; c++) {
                    const int s = c - G_ST;
                    mbar_wait(bars + 8 * (B_EMPTY + s), 0);
                    if (lane == 0) {
                        mbar_expect_tx(bars + 8 * (B_FULL + s), 24576);
                        tma3d(sbase + s * G_STAGE + 16384, &maps.wqkv, bars + 8 * (B_FULL + s), c * 64, nb * 3);
                    }
                    __syncwarp();
                }
            } else if (warp == 14) {
                flag_wait(C_LN + mb, 8);
                fence_proxy_async_all();
                for (int c = 0; c < 8; c++) {
                    const int s = c & (G_ST - 1);
                    if (c >= G_ST) mbar_wait(bars + 8 * (B_EMPTY + s), 0);
                    if (lane == 0) {
                        mbar_expect_tx(bars + 8 * (B_FULL + s), 16384);
                        tma3d(sbase + s * G_STAGE, &maps.xn, bars + 8 * (B_FULL + s), mb * 128, c);
                    }
                    __syncwarp();
                }
            } else if (wg < 2) {
                float acc[96];
#pragma unroll
                for (int i = 0; i < 96; i++) acc[i] = 0.f;
#pragma unroll 1
                for (int c = 0; c < 8; c++) {
                    const int s = c & (G_ST - 1);
                    const uint32_t st = sbase + s * G_STAGE;
                    mbar_wait(bars + 8 * (B_FULL + s), c >> 2);
                    if (c == 0) TL(2);
                    const uint64_t da = mkdesc(st + wg * 8192, 16, 1024, 1);
                    const uint64_t db = mkdesc(st + 16384, 8192, 1024, 1);
                    WG_FENCE();
#pragma unroll
                    for (int k = 0; k < 4; k++) wgmma_n192(acc, da + k * 2, db + k * 128, (c | k) != 0);
                    WG_COMMIT();
                    if (c <= G_ST) {
                        WG_WAIT(1);
                        if (c >= 1 && (tid & 127) == 0) mbar_arrive(bars + 8 * (B_EMPTY + c - 1));
                    }
                }
                WG_WAIT(0);
                nbar_arrive(6, 512);
                TL(3);
                const int mt = mb * 8 + warp;
                uint32_t* dst0 = g_qkv + (mt >> 4) * 6144 + (mt & 15) * 64 + lane;
                const int mtk = (mt + 124) & 127;
                const int kshift = ((mtk >> 4) - (mt >> 4)) * 6144 + ((mtk & 15) - (mt & 15)) * 64;
#pragma unroll
                for (int hh = 0; hh < 12; hh++) {
                    const int gh = nb * 12 + hh, ty = gh >> 5;
                    const float* a = &acc[hh * 8];
                    uint32_t* dst = dst0 + (gh & 31) * 49152 + ((ty + 2) % 3) * 2048 + (ty == 1 ? kshift : 0);
                    const uint32_t ks = ty == 1 ? 0x1f801f80u : 0x3f803f80u;
                    dst[0] = hmul2bf(packbf(a[0], a[1]), ks);
                    dst[32] = hmul2bf(packbf(a[2], a[3]), ks);
                    dst[1024] = hmul2bf(packbf(a[4], a[5]), ks);
                    dst[1024 + 32] = hmul2bf(packbf(a[6], a[7]), ks);
                }
                TL(10);
                nbar_sync(8, 256);
                if (tid == 0) flag_release(C_QKV + nb);
            }
        }
        TL(4);
        const int head = idx >> 2, quarter = idx & 3, w4 = warp & 3;
        {
            if (warp == 15) {
                flag_wait_all(C_QKV + ((lane % 3) * 32 + head) / 12, 16);
                nbar_sync(6, 512);
                fence_proxy_async_all();
                if (lane == 0) {
                    const uint8_t* kvp = reinterpret_cast<const uint8_t*>(g_qkv + head * 49152);
#pragma unroll 1
                    for (int i = 0; i < 2; i++) {
                        const int c = (i + 7) & 7;
                        mbar_expect_tx(bars + 8 * (B_KV + c), 16384);
                        bulk_g2s(sbase + SM_KV + c * KV_CH, kvp + c * 24576, 16384, bars + 8 * (B_KV + c));
                    }
                }
                __syncwarp();
            } else if (wg >= 2) {
                nbar_sync(6, 512);
#pragma unroll 1
                for (int i = tid - 256; i < 2048; i += 224)
                    *reinterpret_cast<uint4*>(smem + SM_KV + (i >> 8) * KV_CH + 16384 + (i & 255) * 16) = make_uint4(0x3f803f80u, 0x3f803f80u, 0x3f803f80u, 0x3f803f80u);
                fence_proxy_async();
            }
            __syncthreads();
            if (tid == 480) {
                const uint8_t* kvp = reinterpret_cast<const uint8_t*>(g_qkv + head * 49152);
#pragma unroll 1
                for (int c = 1; c < 7; c++) {
                    mbar_expect_tx(bars + 8 * (B_KV + c), 16384);
                    bulk_g2s(sbase + SM_KV + c * KV_CH, kvp + c * 24576, 16384, bars + 8 * (B_KV + c));
                }
            } else if (tid == 352) {
                mbar_expect_tx(bars + 8 * B_WO, 65536);
                tma3d(sbase + SM_WO, &maps.wo, bars + 8 * B_WO, 0, idx & 7);
                tma3d(sbase + SM_WO + 32768, &maps.wo, bars + 8 * B_WO, 256, idx & 7);
                map_prefetch(&maps.o);
            }
            __syncwarp();
            const uint64_t kdesc0 = mkdesc(sbase + SM_KV, 4096, 128, 0);
            const uint64_t vdesc0 = mkdesc(sbase + SM_KV + 8192, 128, 4096, 0);
#pragma unroll 1
            for (int mt = 0; mt < 2; mt++) {
                const int m64 = quarter * 8 + mt * 4 + wg;
                uint32_t q[4];
                load_q(q, head, m64 * 4 + w4, lane);
                float s[32], s2[32], o[12];
#pragma unroll
                for (int i = 0; i < 12; i++) o[i] = 0.f;
                mbar_wait(bars + 8 * (B_KV + 7), 0);
                if (mt == 0) { TL(5); TLC(12); }
                WG_FENCE();
                qk64(s, q, kdesc0 + (7 * KV_CH + 3 * 1024) / 16);
                WG_COMMIT(); WG_WAIT(0);
                float mx0 = -INFINITY, mx1 = -INFINITY;
#pragma unroll
                for (int i = 0; i < 8; i++) { mx0 = fmaxf(mx0, fmaxf(s[4 * i], s[4 * i + 1])); mx1 = fmaxf(mx1, fmaxf(s[4 * i + 2], s[4 * i + 3])); }
                mx0 = fmaxf(mx0, __shfl_xor_sync(~0u, mx0, 1)); mx0 = fmaxf(mx0, __shfl_xor_sync(~0u, mx0, 2));
                mx1 = fmaxf(mx1, __shfl_xor_sync(~0u, mx1, 1)); mx1 = fmaxf(mx1, __shfl_xor_sync(~0u, mx1, 2));
                if (mt == 1) {
                    nbar_sync(wg + 1, 128);
                    if ((tid & 127) == 0) flag_release(C_O + m64 - 4);
                }
                float cm0 = -(ceilf(mx0 * QS) + SHIFT), cm1 = -(ceilf(mx1 * QS) + SHIFT);
                float cp0 = (cm0 + 127.f) * sc, cp1 = (cm1 + 127.f) * sc;
                asm volatile("" : "+f"(cm0), "+f"(cm1), "+f"(cp0), "+f"(cp1));
                uint64_t kd = kdesc0, vd = vdesc0;
                auto step = [&](float (&sc_)[32], float (&sn)[32]) {
                    WG_FENCE();
                    qk64(sn, q, kd);
                    WG_COMMIT();
                    kd += 64;
#pragma unroll
                    for (int kk = 0; kk < 4; kk++) {
                        const int i0 = kk * 2, i1 = kk * 2 + 1;
                        const uint32_t p0 = packbf(ex2(fmaf(sc_[4 * i0], QS, cm0)), ex2(fmaf(sc_[4 * i0 + 1], QS, cm0)));
                        const uint32_t p1 = packbf(ex2(fmaf(sc_[4 * i0 + 2], QS, cm1)), ex2(fmaf(sc_[4 * i0 + 3], QS, cm1)));
                        const uint32_t p2 = polyexp(fmaf(sc_[4 * i1], scq, cp0), fmaf(sc_[4 * i1 + 1], scq, cp0));
                        const uint32_t p3 = polyexp(fmaf(sc_[4 * i1 + 2], scq, cp1), fmaf(sc_[4 * i1 + 3], scq, cp1));
                        WG_FENCE();
                        pv24(o, p0, p1, p2, p3, vd);
                        vd += 16;
                    }
                    WG_COMMIT();
                    WG_WAIT(1);
                };
                uint64_t hop = 0;
#pragma unroll 1
                for (int c = 0; c < 16; c++) {
                    mbar_wait(bars + 8 * B_KV + 4 * (c & ~1), 0);
                    step(s, s2); step(s2, s);
                    kd += hop; vd += hop;
                    hop ^= (KV_CH - 4096) / 16;
                }
                WG_WAIT(0);
                bool bad = !(o[8] > 0.f) || !(o[10] > 0.f);
#pragma unroll
                for (int i = 0; i < 12; i++) bad = bad || !(fabsf(o[i]) <= 3.0e38f);
                if (__any_sync(~0u, bad)) attn_safe(q[0], q[1], q[2], q[3], head, m64, w4, lane);
                else attn_store(o, head, m64, w4, lane);
            }
        }
        nbar_sync(wg + 1, 128);
        if ((tid & 127) == 32) {
            flag_release(C_O + quarter * 8 + 4 + wg);
        }

        TL(6); TLC(13);
        {
            const int nb = idx & 7, jb = idx >> 3;
            const int mbe = (jb >> 2) * 8 + (jb & 3);
            float* supd = reinterpret_cast<float*>(smem + SM_MISC + 512);
            if (warp == 15) nbar_sync(7, 512); else nbar_arrive(7, 512);
            TLX(11, 480);
            if (warp == 15) {
                flag_wait_all((lane & 1) ? C_FFN : C_O + mbe, (lane & 1) ? 64 : 32);
                nbar_arrive(9, 160);
                fence_proxy_async_all();
                if (lane == 0) {
                    for (int c = 0; c < 2; c++) {
                        mbar_expect_tx(bars + 8 * (B_OA + c), 32768);
                        tma3d(sbase + SM_KV + c * 32768, &maps.o, bars + 8 * (B_OA + c), mbe * 64, c * 4);
                    }
                }
                __syncwarp();
                flag_wait(C_O + mbe + 4, 32);
                fence_proxy_async_all();
                if (lane == 0) {
                    for (int c = 0; c < 2; c++) {
                        mbar_expect_tx(bars + 8 * (B_OA + 2 + c), 32768);
                        tma3d(sbase + SM_KV + 65536 + c * 32768, &maps.o, bars + 8 * (B_OA + 2 + c), (mbe + 4) * 64, c * 4);
                    }
                    exit_ticket();
                }
                __syncwarp();
            }
            const int late = wg >> 1, nh = wg & 1;
            const int mb = mbe + late * 4;
            const int g = lane >> 2, t = lane & 3;
            const int row0 = mb * 64 + w4 * 16 + g;
            const int col0 = nb * 64 + nh * 32 + t * 2;
            uint32_t xv[8], nv[8];
#pragma unroll
            for (int i = 0; i < 4; i++) {
                xv[2 * i] = *reinterpret_cast<const uint32_t*>(x + (size_t)row0 * DM + col0 + i * 8);
                xv[2 * i + 1] = *reinterpret_cast<const uint32_t*>(x + (size_t)(row0 + 8) * DM + col0 + i * 8);
                nv[2 * i] = __ldcg(reinterpret_cast<const uint32_t*>(g_xn + (size_t)row0 * DM + col0 + i * 8));
                nv[2 * i + 1] = __ldcg(reinterpret_cast<const uint32_t*>(g_xn + (size_t)(row0 + 8) * DM + col0 + i * 8));
            }
            if (wg == 0) {
                nbar_sync(9, 160);
                const int which = tid >> 6, col = nb * 64 + (tid & 63);
                const float y = __ldcg(&g_ypart[which * 512 + col]) + __ldcg(&g_ypart[1024 + which * 512 + col]) +
                                __ldcg(&g_ypart[2048 + which * 512 + col]) + __ldcg(&g_ypart[3072 + which * 512 + col]);
                supd[tid] = bfr(bfr(y) * __ldcg(&g_gate[which]));
                if (tid < 2) reinterpret_cast<int*>(supd + 128)[tid] = __ldcg(&g_sel[tid]);
            }
            float acc[16];
#pragma unroll
            for (int i = 0; i < 16; i++) acc[i] = 0.f;
            mbar_wait(bars + 8 * B_WO, 0);
            const uint32_t abase = sbase + SM_KV + late * 65536;
#pragma unroll 1
            for (int c = 0; c < 8; c++) {
                if ((c & 3) == 0) mbar_wait(bars + 8 * (B_OA + late * 2 + (c >> 2)), 0);
                if (c == 0) TLX(7, 256);
                const uint64_t da = mkdesc(abase + c * 8192, 16, 1024, 1);
                const uint64_t db = mkdesc(sbase + SM_WO + c * 8192 + nh * 64, 8192, 1024, 1);
                WG_FENCE();
#pragma unroll
                for (int k = 0; k < 4; k++) wgmma_n32(acc, da + k * 2, db + k * 128, (c | k) != 0);
                WG_COMMIT();
            }
            TLX(14, 256);
            __syncthreads();
            TLX(15, 256);
            const int sel0 = reinterpret_cast<const int*>(supd + 128)[0], sel1 = reinterpret_cast<const int*>(supd + 128)[1];
            WG_WAIT(0);
            TLX(8, 256);
#pragma unroll
            for (int h = 0; h < 2; h++) {
                const int row = row0 + h * 8;
                const int which = row == sel0 ? 0 : (row == sel1 ? 1 : -1);
#pragma unroll
                for (int i = 0; i < 4; i++) {
                    const int col = col0 + i * 8;
                    float b0 = bf_lo(nv[2 * i + h]), b1 = bf_hi(nv[2 * i + h]);
                    if (which >= 0) {
                        b0 = bfr(b0 + supd[which * 64 + col - nb * 64]); b1 = bfr(b1 + supd[which * 64 + col + 1 - nb * 64]);
                    }
                    const float t0 = bfr(bf_lo(xv[2 * i + h]) + bfr(acc[4 * i + 2 * h]));
                    const float t1 = bfr(bf_hi(xv[2 * i + h]) + bfr(acc[4 * i + 2 * h + 1]));
                    *reinterpret_cast<uint32_t*>(out + (size_t)row * DM + col) = packbf(t0 + b0, t1 + b1);
                }
            }
        }
        TLX(9, 256);
    }
}

typedef CUresult (*EncodeFn)(CUtensorMap*, CUtensorMapDataType, cuuint32_t, void*, const cuuint64_t*, const cuuint64_t*,
                             const cuuint32_t*, const cuuint32_t*, CUtensorMapInterleave, CUtensorMapSwizzle,
                             CUtensorMapL2promotion, CUtensorMapFloatOOBfill);

void make_map(EncodeFn fn, CUtensorMap* m, const void* ptr, uint64_t cols, uint64_t rows, uint32_t box_rows, uint32_t box_chunks) {
    cuuint64_t dims[3] = {64, rows, cols / 64};
    cuuint64_t strides[2] = {cols * 2, 128};
    cuuint32_t box[3] = {64, box_rows, box_chunks};
    cuuint32_t es[3] = {1, 1, 1};
    fn(m, CU_TENSOR_MAP_DATA_TYPE_BFLOAT16, 3, const_cast<void*>(ptr), dims, strides, box, es, CU_TENSOR_MAP_INTERLEAVE_NONE,
       CU_TENSOR_MAP_SWIZZLE_128B, CU_TENSOR_MAP_L2_PROMOTION_L2_256B, CU_TENSOR_MAP_FLOAT_OOB_FILL_NONE);
}

}

extern "C" void kernel_launch(void* const* d_in, const int* in_sizes, int n_in, void* d_out, int out_size) {
    const __nv_bfloat16* x = (const __nv_bfloat16*)d_in[0];
    const __nv_bfloat16* wqkv = (const __nv_bfloat16*)d_in[1];
    const __nv_bfloat16* wo = (const __nv_bfloat16*)d_in[2];
    const __nv_bfloat16* wr = (const __nv_bfloat16*)d_in[4];
    const __nv_bfloat16* wgate = (const __nv_bfloat16*)d_in[5];
    const __nv_bfloat16* wup = (const __nv_bfloat16*)d_in[6];
    const __nv_bfloat16* wdown = (const __nv_bfloat16*)d_in[7];
    __nv_bfloat16* out = (__nv_bfloat16*)d_out;

    static EncodeFn enc = nullptr;
    static void* p_xn = nullptr; static void* p_o = nullptr;
    if (!enc) {
        void* fn = nullptr; cudaDriverEntryPointQueryResult qr;
        cudaGetDriverEntryPoint("cuTensorMapEncodeTiled", &fn, cudaEnableDefault, &qr);
        enc = (EncodeFn)fn;
        cudaGetSymbolAddress(&p_xn, g_xn);
        cudaGetSymbolAddress(&p_o, g_o);
        cudaFuncSetAttribute(fused_kernel, cudaFuncAttributeMaxDynamicSharedMemorySize, FUSED_SMEM);
    }
    Maps maps;
    make_map(enc, &maps.g, wgate, FF, DM, 16, 7);
    make_map(enc, &maps.u, wup, FF, DM, 16, 7);
    make_map(enc, &maps.d, wdown, DM, FF, 32, 8);
    make_map(enc, &maps.xn, p_xn, DM, S_LEN, 128, 1);
    make_map(enc, &maps.wqkv, wqkv, 3 * DM, DM, 64, 3);
    make_map(enc, &maps.o, p_o, DM, S_LEN, 64, 4);
    make_map(enc, &maps.wo, wo, DM, DM, 256, 1);

    union { uint32_t u; float f; } scu; scu.u = 128u;

    cudaLaunchConfig_t cfg = {};
    cfg.gridDim = dim3(132); cfg.blockDim = dim3(512); cfg.dynamicSmemBytes = FUSED_SMEM; cfg.stream = cudaStreamPerThread;
    cudaLaunchKernelEx(&cfg, fused_kernel, maps, x, wr, out, scu.f);
}
```

```cpp
#include <cuda_runtime.h>
#include <cuda_bf16.h>
#include <cuda.h>
#include <stdint.h>
#include <type_traits>

namespace {

constexpr int S_LEN = 2048;
constexpr int DM = 512;
constexpr int NH = 32;
constexpr int FF = 1792;

__device__ __align__(1024) __nv_bfloat16 g_xn[S_LEN * DM];
__device__ __align__(16) float g_r[S_LEN];
__device__ __align__(1024) uint32_t g_qkv[NH * 8 * 6144];
__device__ __align__(1024) __nv_bfloat16 g_o[S_LEN * DM];
__device__ __align__(16) float g_ypart[4 * 2 * DM];
__device__ int g_sel[2];
__device__ float g_gate[2];
constexpr int C_LN = 0, C_QKV = 16, C_O = 24, C_FFN = 56, C_EXIT = 57, C_NUM = 58;
__device__ unsigned g_cnt[C_NUM * 32];

#define TLC(slot) do {} while (0)
#define TL(slot) do {} while (0)
#define TLX(slot, th) do {} while (0)

__device__ __forceinline__ uint32_t smem_u32(const void* p) { return (uint32_t)__cvta_generic_to_shared(p); }
__device__ __forceinline__ void warp_arrive(int idx) {
    __syncwarp();
    if ((threadIdx.x & 31) == 0)
        asm volatile("red.release.gpu.global.add.u32 [%0], 1;" :: "l"(g_cnt + idx * 32) : "memory");
}
__device__ __forceinline__ void flag_release(int idx) {
    asm volatile("red.release.gpu.global.add.u32 [%0], 1;" :: "l"(g_cnt + idx * 32) : "memory");
}
__device__ __forceinline__ void exit_ticket() {
    unsigned tk;
    asm volatile("atom.relaxed.gpu.global.add.u32 %0, [%1], 1;" : "=r"(tk) : "l"(g_cnt + C_EXIT * 32) : "memory");
    if (tk == gridDim.x - 1) {
#pragma unroll 1
        for (int i = 0; i < C_NUM; i++) g_cnt[i * 32] = 0u;
    }
}
__device__ __forceinline__ void nbar_arrive(int id, int cnt) { asm volatile("bar.arrive %0, %1;" :: "r"(id), "r"(cnt) : "memory"); }
__device__ __forceinline__ void nbar_sync(int id, int cnt) { asm volatile("bar.sync %0, %1;" :: "r"(id), "r"(cnt) : "memory"); }
__device__ __forceinline__ void flag_wait(int idx, unsigned target) {
    asm volatile("{\n.reg .pred p;\n.reg .u32 n, v;\nmov.u32 n, 0;\n"
                 "FW_%=:\n"
                 "ld.acquire.gpu.global.u32 v, [%0];\n"
                 "setp.ge.u32 p, v, %1;\n"
                 "@p bra FD_%=;\n"
                 "add.u32 n, n, 1;\n"
                 "setp.lt.u32 p, n, 16000000;\n"
                 "@p bra FW_%=;\n"
                 "trap;\n"
                 "FD_%=:\n}"
                 :: "l"(g_cnt + idx * 32), "r"(target) : "memory");
}
__device__ __forceinline__ void flag_wait_all(int idx, unsigned target) {
    asm volatile("{\n.reg .pred p;\n.reg .u32 n, v;\nmov.u32 n, 0;\n"
                 "FW_%=:\n"
                 "ld.acquire.gpu.global.u32 v, [%0];\n"
                 "setp.ge.u32 p, v, %1;\n"
                 "vote.sync.all.pred p, p, 0xffffffff;\n"
                 "@p bra.uni FD_%=;\n"
                 "add.u32 n, n, 1;\n"
                 "setp.lt.u32 p, n, 16000000;\n"
                 "@p bra.uni FW_%=;\n"
                 "trap;\n"
                 "FD_%=:\n}"
                 :: "l"(g_cnt + idx * 32), "r"(target) : "memory");
}
__device__ __forceinline__ void fence_proxy_async_all() { asm volatile("fence.proxy.async.global;" ::: "memory"); }
__device__ __forceinline__ void mbar_init(uint32_t bar, uint32_t cnt) {
    asm volatile("mbarrier.init.shared::cta.b64 [%0], %1;" :: "r"(bar), "r"(cnt) : "memory");
}
__device__ __forceinline__ void mbar_expect_tx(uint32_t bar, uint32_t bytes) {
    asm volatile("mbarrier.arrive.expect_tx.shared::cta.b64 _, [%0], %1;" :: "r"(bar), "r"(bytes) : "memory");
}
__device__ __forceinline__ void mbar_arrive(uint32_t bar) {
    asm volatile("mbarrier.arrive.shared::cta.b64 _, [%0];" :: "r"(bar) : "memory");
}
__device__ __forceinline__ void mbar_wait(uint32_t bar, uint32_t parity) {
    asm volatile("{\n.reg .pred p, q;\n.reg .u32 n;\nmov.u32 n, 0;\n"
                 "WAIT_%=:\n"
                 "mbarrier.try_wait.parity.shared::cta.b64 p, [%0], %1;\n"
                 "add.u32 n, n, 1;\n"
                 "setp.lt.and.u32 q, n, 4000000, !p;\n"
                 "@q bra WAIT_%=;\n"
                 "@!p trap;\n}"
                 :: "r"(bar), "r"(parity) : "memory");
}
__device__ __forceinline__ void fence_barrier_init() { asm volatile("fence.mbarrier_init.release.cluster;" ::: "memory"); }
__device__ __forceinline__ void fence_proxy_async() { asm volatile("fence.proxy.async.shared::cta;" ::: "memory"); }
__device__ __forceinline__ void tma3d(uint32_t dst, const CUtensorMap* map, uint32_t bar, int row, int chunk) {
    asm volatile("cp.async.bulk.tensor.3d.shared::cluster.global.mbarrier::complete_tx::bytes [%0], [%1, {%3, %4, %5}], [%2];"
                 :: "r"(dst), "l"((uint64_t)map), "r"(bar), "r"(0), "r"(row), "r"(chunk) : "memory");
}
__device__ __forceinline__ void bulk_g2s(uint32_t dst, const void* src, uint32_t bytes, uint32_t bar) {
    asm volatile("cp.async.bulk.shared::cluster.global.mbarrier::complete_tx::bytes [%0], [%1], %2, [%3];"
                 :: "r"(dst), "l"((uint64_t)src), "r"(bytes), "r"(bar) : "memory");
}
__device__ __forceinline__ void l2_prefetch(const void* src, uint32_t bytes) {
    asm volatile("cp.async.bulk.prefetch.L2.global [%0], %1;" :: "l"((uint64_t)src), "r"(bytes) : "memory");
}
__device__ __forceinline__ void map_prefetch(const CUtensorMap* m) {
    asm volatile("prefetch.tensormap [%0];" :: "l"((uint64_t)m) : "memory");
}
__device__ __forceinline__ uint64_t mkdesc(uint32_t addr, uint32_t lbo, uint32_t sbo, uint32_t swz) {
    return (uint64_t)((addr & 0x3FFFF) >> 4) | ((uint64_t)(lbo >> 4) << 16) | ((uint64_t)(sbo >> 4) << 32) | ((uint64_t)swz << 62);
}
#define WG_FENCE() asm volatile("wgmma.fence.sync.aligned;" ::: "memory")
#define WG_COMMIT() asm volatile("wgmma.commit_group.sync.aligned;" ::: "memory")
#define WG_WAIT(n) asm volatile("wgmma.wait_group.sync.aligned %0;" :: "n"(n) : "memory")

__device__ __forceinline__ float ex2(float x) { float y; asm("ex2.approx.ftz.f32 %0, %1;" : "=f"(y) : "f"(x)); return y; }
__device__ __forceinline__ uint32_t packbf(float lo, float hi) {
    uint32_t r; asm("cvt.rn.bf16x2.f32 %0, %1, %2;" : "=r"(r) : "f"(hi), "f"(lo)); return r;
}
__device__ __forceinline__ uint32_t hmul2bf(uint32_t a, uint32_t b) { uint32_t r; asm("mul.rn.bf16x2 %0, %1, %2;" : "=r"(r) : "r"(a), "r"(b)); return r; }
__device__ __forceinline__ float bf_lo(uint32_t v) { return __uint_as_float(v << 16); }
__device__ __forceinline__ float bf_hi(uint32_t v) { return __uint_as_float(v & 0xffff0000u); }
__device__ __forceinline__ float bfr(float x) { return __bfloat162float(__float2bfloat16_rn(x)); }

__device__ __forceinline__ void wgmma_n192(float (&d)[96], uint64_t da, uint64_t db, int scale_d) {
    asm volatile("{\n.reg .pred p;\nsetp.ne.b32 p, %98, 0;\n"
        "wgmma.mma_async.sync.aligned.m64n192k16.f32.bf16.bf16 "
        "{%0,%1,%2,%3,%4,%5,%6,%7,%8,%9,%10,%11,%12,%13,%14,%15,%16,%17,%18,%19,%20,%21,%22,%23,"
        "%24,%25,%26,%27,%28,%29,%30,%31,%32,%33,%34,%35,%36,%37,%38,%39,%40,%41,%42,%43,%44,%45,%46,%47,"
        "%48,%49,%50,%51,%52,%53,%54,%55,%56,%57,%58,%59,%60,%61,%62,%63,%64,%65,%66,%67,%68,%69,%70,%71,"
        "%72,%73,%74,%75,%76,%77,%78,%79,%80,%81,%82,%83,%84,%85,%86,%87,%88,%89,%90,%91,%92,%93,%94,%95}, "
        "%96, %97, p, 1, 1, 0, 1;\n}"
        : "+f"(d[0]), "+f"(d[1]), "+f"(d[2]), "+f"(d[3]), "+f"(d[4]), "+f"(d[5]), "+f"(d[6]), "+f"(d[7]),
          "+f"(d[8]), "+f"(d[9]), "+f"(d[10]), "+f"(d[11]), "+f"(d[12]), "+f"(d[13]), "+f"(d[14]), "+f"(d[15]),
          "+f"(d[16]), "+f"(d[17]), "+f"(d[18]), "+f"(d[19]), "+f"(d[20]), "+f"(d[21]), "+f"(d[22]), "+f"(d[23]),
          "+f"(d[24]), "+f"(d[25]), "+f"(d[26]), "+f"(d[27]), "+f"(d[28]), "+f"(d[29]), "+f"(d[30]), "+f"(d[31]),
          "+f"(d[32]), "+f"(d[33]), "+f"(d[34]), "+f"(d[35]), "+f"(d[36]), "+f"(d[37]), "+f"(d[38]), "+f"(d[39]),
          "+f"(d[40]), "+f"(d[41]), "+f"(d[42]), "+f"(d[43]), "+f"(d[44]), "+f"(d[45]), "+f"(d[46]), "+f"(d[47]),
          "+f"(d[48]), "+f"(d[49]), "+f"(d[50]), "+f"(d[51]), "+f"(d[52]), "+f"(d[53]), "+f"(d[54]), "+f"(d[55]),
          "+f"(d[56]), "+f"(d[57]), "+f"(d[58]), "+f"(d[59]), "+f"(d[60]), "+f"(d[61]), "+f"(d[62]), "+f"(d[63]),
          "+f"(d[64]), "+f"(d[65]), "+f"(d[66]), "+f"(d[67]), "+f"(d[68]), "+f"(d[69]), "+f"(d[70]), "+f"(d[71]),
          "+f"(d[72]), "+f"(d[73]), "+f"(d[74]), "+f"(d[75]), "+f"(d[76]), "+f"(d[77]), "+f"(d[78]), "+f"(d[79]),
          "+f"(d[80]), "+f"(d[81]), "+f"(d[82]), "+f"(d[83]), "+f"(d[84]), "+f"(d[85]), "+f"(d[86]), "+f"(d[87]),
          "+f"(d[88]), "+f"(d[89]), "+f"(d[90]), "+f"(d[91]), "+f"(d[92]), "+f"(d[93]), "+f"(d[94]), "+f"(d[95])
        : "l"(da), "l"(db), "r"(scale_d));
}

constexpr float SHIFT = 90.0f;
constexpr float QS = 0.25f * 1.4426950408889634f * 18446744073709551616.0f;
constexpr float scq = 0.25f * 1.4426950408889634f * 3.3087224502121107e-24f;

__device__ __forceinline__ uint32_t polyexp(float lo, float hi) {
    uint32_t w, g, q, h;
    asm("cvt.pack.sat.s16.s32 %0, %1, %2;" : "=r"(w) : "r"(__float_as_uint(hi)), "r"(__float_as_uint(lo)));
    g = w & 0x007F007Fu;
    asm("fma.rn.f16x2 %0, %1, %2, %3;" : "=r"(q) : "r"(g), "r"(0xf940f940u), "r"(0x35513551u));
    asm("mul.rn.f16x2 %0, %1, %2;" : "=r"(h) : "r"(q), "r"(g));
    return w - h;
}
__device__ __forceinline__ void qk64(float (&s)[32], const uint32_t (&q)[4], uint64_t db) {
    asm volatile("wgmma.mma_async.sync.aligned.m64n64k16.f32.bf16.bf16 "
        "{%0,%1,%2,%3,%4,%5,%6,%7,%8,%9,%10,%11,%12,%13,%14,%15,%16,%17,%18,%19,%20,%21,%22,%23,%24,%25,%26,%27,%28,%29,%30,%31}, "
        "{%32,%33,%34,%35}, %36, 0, 1, 1, 0;"
        : "=f"(s[0]), "=f"(s[1]), "=f"(s[2]), "=f"(s[3]), "=f"(s[4]), "=f"(s[5]), "=f"(s[6]), "=f"(s[7]),
          "=f"(s[8]), "=f"(s[9]), "=f"(s[10]), "=f"(s[11]), "=f"(s[12]), "=f"(s[13]), "=f"(s[14]), "=f"(s[15]),
          "=f"(s[16]), "=f"(s[17]), "=f"(s[18]), "=f"(s[19]), "=f"(s[20]), "=f"(s[21]), "=f"(s[22]), "=f"(s[23]),
          "=f"(s[24]), "=f"(s[25]), "=f"(s[26]), "=f"(s[27]), "=f"(s[28]), "=f"(s[29]), "=f"(s[30]), "=f"(s[31])
        : "r"(q[0]), "r"(q[1]), "r"(q[2]), "r"(q[3]), "l"(db));
}
__device__ __forceinline__ void pv24(float (&o)[12], uint32_t a0, uint32_t a1, uint32_t a2, uint32_t a3, uint64_t db) {
    asm volatile("wgmma.mma_async.sync.aligned.m64n24k16.f32.bf16.bf16 "
        "{%0,%1,%2,%3,%4,%5,%6,%7,%8,%9,%10,%11}, {%12,%13,%14,%15}, %16, 1, 1, 1, 1;"
        : "+f"(o[0]), "+f"(o[1]), "+f"(o[2]), "+f"(o[3]), "+f"(o[4]), "+f"(o[5]), "+f"(o[6]), "+f"(o[7]),
          "+f"(o[8]), "+f"(o[9]), "+f"(o[10]), "+f"(o[11])
        : "r"(a0), "r"(a1), "r"(a2), "r"(a3), "l"(db));
}

__device__ __forceinline__ void load_q(uint32_t (&q)[4], int head, int mt, int lane) {
    const uint32_t* src = g_qkv + head * 49152 + (mt >> 4) * 6144 + 4096 + (mt & 15) * 64 + lane;
    q[0] = __ldcg(src); q[1] = __ldcg(src + 32); q[2] = __ldcg(src + 1024); q[3] = __ldcg(src + 1024 + 32);
}
__device__ __forceinline__ void attn_store(const float (&o)[12], int head, int m64, int warp, int lane) {
    const int g = lane >> 2, t = lane & 3;
    const int row = m64 * 64 + warp * 16 + g;
    const float i0 = 1.f / o[8], i1 = 1.f / o[10];
    uint32_t* p0 = reinterpret_cast<uint32_t*>(g_o + (size_t)row * DM + head * 16 + t * 2);
    uint32_t* p1 = reinterpret_cast<uint32_t*>(g_o + (size_t)(row + 8) * DM + head * 16 + t * 2);
    p0[0] = packbf(o[0] * i0, o[1] * i0); p0[4] = packbf(o[4] * i0, o[5] * i0);
    p1[0] = packbf(o[2] * i1, o[3] * i1); p1[4] = packbf(o[6] * i1, o[7] * i1);
}

__device__ __forceinline__ void mma_full(float (&d)[4], uint32_t a0, uint32_t a1, uint32_t a2, uint32_t a3, uint32_t b0, uint32_t b1) {
    asm volatile("mma.sync.aligned.m16n8k16.row.col.f32.bf16.bf16.f32 {%0,%1,%2,%3}, {%4,%5,%6,%7}, {%8,%9}, {%0,%1,%2,%3};"
                 : "+f"(d[0]), "+f"(d[1]), "+f"(d[2]), "+f"(d[3]) : "r"(a0), "r"(a1), "r"(a2), "r"(a3), "r"(b0), "r"(b1));
}
__device__ __forceinline__ uint32_t movt(uint32_t a) {
    uint32_t r; asm volatile("movmatrix.sync.aligned.m8n8.trans.b16 %0, %1;" : "=r"(r) : "r"(a)); return r;
}
__device__ __noinline__ void attn_safe(uint32_t q0, uint32_t q1, uint32_t q2, uint32_t q3, int head, int m64, int w4, int lane) {
    float o0[4] = {0.f, 0.f, 0.f, 0.f}, o1[4] = {0.f, 0.f, 0.f, 0.f};
    float m0 = -INFINITY, m1 = -INFINITY, l0 = 0.f, l1 = 0.f;
#pragma unroll 1
    for (int kb = 0; kb < 128; kb++) {
        const uint32_t* src = g_qkv + head * 49152 + (kb >> 4) * 6144 + (kb & 15) * 64 + lane;
        const uint32_t* srck = src;
        float sa[4] = {0.f, 0.f, 0.f, 0.f}, sb[4] = {0.f, 0.f, 0.f, 0.f};
        mma_full(sa, q0, q1, q2, q3, __ldcg(srck), __ldcg(srck + 1024));
        mma_full(sb, q0, q1, q2, q3, __ldcg(srck + 32), __ldcg(srck + 1024 + 32));
        float n0 = fmaxf(fmaxf(m0, fmaxf(sa[0], sa[1])), fmaxf(sb[0], sb[1]));
        float n1 = fmaxf(fmaxf(m1, fmaxf(sa[2], sa[3])), fmaxf(sb[2], sb[3]));
        n0 = fmaxf(n0, __shfl_xor_sync(~0u, n0, 1)); n0 = fmaxf(n0, __shfl_xor_sync(~0u, n0, 2));
        n1 = fmaxf(n1, __shfl_xor_sync(~0u, n1, 1)); n1 = fmaxf(n1, __shfl_xor_sync(~0u, n1, 2));
        const float c0 = ex2((m0 - n0) * QS), c1 = ex2((m1 - n1) * QS);
        m0 = n0; m1 = n1;
        const uint32_t p0 = packbf(ex2((sa[0] - m0) * QS), ex2((sa[1] - m0) * QS));
        const uint32_t p1 = packbf(ex2((sa[2] - m1) * QS), ex2((sa[3] - m1) * QS));
        const uint32_t p2 = packbf(ex2((sb[0] - m0) * QS), ex2((sb[1] - m0) * QS));
        const uint32_t p3 = packbf(ex2((sb[2] - m1) * QS), ex2((sb[3] - m1) * QS));
        l0 = l0 * c0 + (bf_lo(p0) + bf_hi(p0)) + (bf_lo(p2) + bf_hi(p2));
        l1 = l1 * c1 + (bf_lo(p1) + bf_hi(p1)) + (bf_lo(p3) + bf_hi(p3));
        o0[0] *= c0; o0[1] *= c0; o0[2] *= c1; o0[3] *= c1;
        o1[0] *= c0; o1[1] *= c0; o1[2] *= c1; o1[3] *= c1;
        mma_full(o0, p0, p1, p2, p3, movt(__ldcg(src + 2048)), movt(__ldcg(src + 2048 + 32)));
        mma_full(o1, p0, p1, p2, p3, movt(__ldcg(src + 3072)), movt(__ldcg(src + 3072 + 32)));
    }
    l0 += __shfl_xor_sync(~0u, l0, 1); l0 += __shfl_xor_sync(~0u, l0, 2);
    l1 += __shfl_xor_sync(~0u, l1, 1); l1 += __shfl_xor_sync(~0u, l1, 2);
    const float o[12] = {o0[0], o0[1], o0[2], o0[3], o1[0], o1[1], o1[2], o1[3], l0, l0, l1, l1};
    attn_store(o, head, m64, w4, lane);
}

constexpr int FS_N = 4;
constexpr int FS_BYTES = 32768;
__device__ __forceinline__ void ldsm4t(uint32_t& r0, uint32_t& r1, uint32_t& r2, uint32_t& r3, uint32_t addr) {
    asm volatile("ldmatrix.sync.aligned.m8n8.x4.trans.shared.b16 {%0,%1,%2,%3}, [%4];" : "=r"(r0), "=r"(r1), "=r"(r2), "=r"(r3) : "r"(addr) : "memory");
}
__device__ __forceinline__ void mma16816(float (&d)[4], uint32_t a0, uint32_t a2, uint32_t b0, uint32_t b1) {
    asm volatile("mma.sync.aligned.m16n8k16.row.col.f32.bf16.bf16.f32 {%0,%1,%2,%3}, {%4,%5,%6,%5}, {%7,%8}, {%0,%1,%2,%3};"
                 : "+f"(d[0]), "+f"(d[1]), "+f"(d[2]), "+f"(d[3]) : "r"(a0), "r"(0u), "r"(a2), "r"(b0), "r"(b1));
}
__device__ void ffn_block(int c, uint8_t* smem, uint32_t sbase, const CUtensorMap* mapG, const CUtensorMap* mapU, const CUtensorMap* mapD) {
    const int tid = threadIdx.x, warp = tid >> 5, lane = tid & 31;
    uint32_t* sx = reinterpret_cast<uint32_t*>(smem + FS_N * FS_BYTES);
    __nv_bfloat16* sh = reinterpret_cast<__nv_bfloat16*>(sx + 512);
    const uint32_t bars = sbase + FS_N * FS_BYTES + 8192;
    float* tv = reinterpret_cast<float*>(smem + FS_N * FS_BYTES + 4096);
    int* ti = reinterpret_cast<int*>(tv + 32);
    int* ssel = ti + 32;
    auto issue = [&](int item) {
        const int slot = item % FS_N;
        const uint32_t dst = sbase + slot * FS_BYTES, bar = bars + 8 * slot;
        mbar_expect_tx(bar, item < 32 ? 28672 : 32768);
        if (item < 32) {
            tma3d(dst, mapG, bar, item * 16, c * 7);
            tma3d(dst + 14336, mapU, bar, item * 16, c * 7);
        } else {
            tma3d(dst, mapD, bar, c * 448 + (item - 32) * 32, 0);
        }
    };
    if (tid == 0) {
        for (int i = 0; i < FS_N; i++) mbar_init(bars + 8 * i, 1);
        fence_barrier_init();
        for (int i = 0; i < FS_N; i++) issue(i);
    }
    flag_wait(C_LN + warp, 8);
    __syncthreads();
    float b1 = -INFINITY, b2 = -INFINITY; int i1 = 0x7fffffff, i2 = 0x7fffffff;
    auto push = [&](float v, int i) {
        if (v > b1 || (v == b1 && i < i1)) { b2 = b1; i2 = i1; b1 = v; i1 = i; }
        else if (v > b2 || (v == b2 && i < i2)) { b2 = v; i2 = i; }
    };
    {
        const float4 rv = __ldcg(reinterpret_cast<const float4*>(g_r) + tid);
        push(rv.x, 4 * tid); push(rv.y, 4 * tid + 1); push(rv.z, 4 * tid + 2); push(rv.w, 4 * tid + 3);
    }
#pragma unroll
    for (int o = 16; o > 0; o >>= 1) {
        float v1 = __shfl_xor_sync(~0u, b1, o), v2 = __shfl_xor_sync(~0u, b2, o);
        int j1 = __shfl_xor_sync(~0u, i1, o), j2 = __shfl_xor_sync(~0u, i2, o);
        push(v1, j1); push(v2, j2);
    }
    if (lane == 0) { tv[2 * warp] = b1; ti[2 * warp] = i1; tv[2 * warp + 1] = b2; ti[2 * warp + 1] = i2; }
    __syncthreads();
    if (warp == 1) {
        b1 = tv[lane]; i1 = ti[lane]; b2 = -INFINITY; i2 = 0x7fffffff;
#pragma unroll
        for (int o = 16; o > 0; o >>= 1) {
            float v1 = __shfl_xor_sync(~0u, b1, o), v2 = __shfl_xor_sync(~0u, b2, o);
            int j1 = __shfl_xor_sync(~0u, i1, o), j2 = __shfl_xor_sync(~0u, i2, o);
            push(v1, j1); push(v2, j2);
        }
        if (lane == 0) {
            i1 = min(max(i1, 0), S_LEN - 1); i2 = min(max(i2, 0), S_LEN - 1);
            ssel[0] = i1; ssel[1] = i2;
            if (c == 0) {
                g_sel[0] = i1; g_sel[1] = i2;
                g_gate[0] = bfr(1.f / (1.f + __expf(-bfr(b1))));
                g_gate[1] = bfr(1.f / (1.f + __expf(-bfr(b2))));
            }
        }
    }
    __syncthreads();
    sx[tid] = __ldcg(reinterpret_cast<const uint32_t*>(g_xn + (size_t)ssel[tid >> 8] * DM + (tid & 255) * 2));
    __syncthreads();
    TL(1);
    const int g = lane >> 2, t = lane & 3;
    const int lrow = lane & 15, lsel = lane >> 4;
    {
        float ag[4][4], au[4][4];
#pragma unroll
        for (int j = 0; j < 4; j++) { ag[j][0] = ag[j][1] = ag[j][2] = ag[j][3] = 0.f; au[j][0] = au[j][1] = au[j][2] = au[j][3] = 0.f; }
#pragma unroll 1
        for (int it = 0; it < 32; it++) {
            const int slot = it % FS_N;
            const uint32_t a0 = g < 2 ? sx[g * 256 + it * 8 + t] : 0u, a2 = g < 2 ? sx[g * 256 + it * 8 + 4 + t] : 0u;
            mbar_wait(bars + 8 * slot, (it / FS_N) & 1);
            const uint32_t base = sbase + slot * FS_BYTES + lsel * 14336 + lrow * 128;
#pragma unroll
            for (int j = 0; j < 4; j++) {
                const int nt = warp + j * 16;
                if (nt < 56) {
                    uint32_t b0, b1, b2, b3;
                    ldsm4t(b0, b1, b2, b3, base + (nt >> 3) * 2048 + (((nt & 7) ^ (lrow & 7)) << 4));
                    mma16816(ag[j], a0, a2, b0, b1);
                    mma16816(au[j], a0, a2, b2, b3);
                }
            }
            __syncthreads();
            if (tid == 480) issue(it + FS_N);
        }
        if (g < 2) {
#pragma unroll
            for (int j = 0; j < 4; j++) {
                const int nt = warp + j * 16;
                if (nt < 56) {
#pragma unroll
                    for (int e = 0; e < 2; e++) {
                        const float gs = bfr(ag[j][e]), us = bfr(au[j][e]);
                        const float sg = bfr(gs / (1.f + __expf(-gs)));
                        sh[g * 448 + nt * 8 + t * 2 + e] = __float2bfloat16_rn(sg * us);
                    }
                }
            }
        }
        __syncthreads();
    }
    TL(2);
    {
        const uint32_t* shw = reinterpret_cast<const uint32_t*>(sh);
        float a[4][4];
#pragma unroll
        for (int j = 0; j < 4; j++) a[j][0] = a[j][1] = a[j][2] = a[j][3] = 0.f;
#pragma unroll 1
        for (int it = 32; it < 46; it++) {
            const int slot = it % FS_N;
            uint32_t af[4];
#pragma unroll
            for (int q = 0; q < 4; q++) af[q] = g < 2 ? shw[g * 224 + (it - 32) * 16 + q * 4 + t] : 0u;
            mbar_wait(bars + 8 * slot, (it / FS_N) & 1);
            const uint32_t base = sbase + slot * FS_BYTES + (warp >> 1) * 4096 + lane * 128;
#pragma unroll
            for (int j = 0; j < 4; j++) {
                const int u = (warp & 1) * 4 + j;
                uint32_t b0, b1, b2, b3;
                ldsm4t(b0, b1, b2, b3, base + ((u ^ (lane & 7)) << 4));
                mma16816(a[j], af[0], af[1], b0, b1);
                mma16816(a[j], af[2], af[3], b2, b3);
            }
            __syncthreads();
            if (tid == 480 && it + FS_N < 46) issue(it + FS_N);
        }
        if (g < 2) {
#pragma unroll
            for (int j = 0; j < 4; j++)
                *reinterpret_cast<float2*>(&g_ypart[c * 1024 + g * 512 + (warp * 4 + j) * 8 + t * 2]) = make_float2(a[j][0], a[j][1]);
        }
    }
    warp_arrive(C_FFN);
}

__device__ __forceinline__ void wgmma_n32(float (&d)[16], uint64_t da, uint64_t db, int scale_d) {
    asm volatile("{\n.reg .pred p;\nsetp.ne.b32 p, %18, 0;\n"
        "wgmma.mma_async.sync.aligned.m64n32k16.f32.bf16.bf16 "
        "{%0,%1,%2,%3,%4,%5,%6,%7,%8,%9,%10,%11,%12,%13,%14,%15}, "
        "%16, %17, p, 1, 1, 0, 1;\n}"
        : "+f"(d[0]), "+f"(d[1]), "+f"(d[2]), "+f"(d[3]), "+f"(d[4]), "+f"(d[5]), "+f"(d[6]), "+f"(d[7]),
          "+f"(d[8]), "+f"(d[9]), "+f"(d[10]), "+f"(d[11]), "+f"(d[12]), "+f"(d[13]), "+f"(d[14]), "+f"(d[15])
        : "l"(da), "l"(db), "r"(scale_d));
}

constexpr int G_ST = 4;
constexpr int G_STAGE = 16384 + 24576;
constexpr int SM_KV = 0, SM_WO = 163840, SM_MISC = 229376;
constexpr int FUSED_SMEM = SM_MISC + 2048;
constexpr int B_FULL = 0, B_EMPTY = 4, B_KV = 8, B_WO = 16, B_OA = 18, B_NUM = 22;

struct Maps { CUtensorMap xn, wqkv, o, wo, g, u, d; };

__global__ void __launch_bounds__(512, 1) fused_kernel(const __grid_constant__ Maps maps, const __nv_bfloat16* __restrict__ x,
                                                       const __nv_bfloat16* __restrict__ wr, __nv_bfloat16* __restrict__ out, float sc) {
    extern __shared__ __align__(1024) uint8_t smem[];
    const uint32_t sbase = smem_u32(smem);
    const int tid = threadIdx.x, warp = __shfl_sync(~0u, tid >> 5, 0), lane = tid & 31;
    const uint32_t bars = sbase + SM_MISC;
    TL(0);
    if (sbase & 1023u) __trap();
    if (blockIdx.x < 4) {
        ffn_block(blockIdx.x, smem, sbase, &maps.g, &maps.u, &maps.d);
        __syncthreads();
        if (tid == 0) exit_ticket();
        TL(3);
    } else {
        const int idx = blockIdx.x - 4;
        const int wg = warp >> 2;
        {
            const int row = idx * 16 + warp;
            const uint4* xr = reinterpret_cast<const uint4*>(x + (size_t)row * DM);
            const uint4 a = xr[lane], b = xr[32 + lane];
            const uint4* wp = reinterpret_cast<const uint4*>(wr);
            const uint4 wa = wp[lane], wb = wp[32 + lane];
            if (tid == 480) {
                for (int s = 0; s < G_ST; s++) { mbar_init(bars + 8 * (B_FULL + s), 2); mbar_init(bars + 8 * (B_EMPTY + s), 2); }
                for (int c = B_KV; c < B_NUM; c++) mbar_init(bars + 8 * c, 1);
                fence_barrier_init();
                for (int c = 0; c < G_ST; c++) {
                    mbar_expect_tx(bars + 8 * (B_FULL + c), 24576);
                    tma3d(sbase + c * G_STAGE + 16384, &maps.wqkv, bars + 8 * (B_FULL + c), c * 64, (idx & 7) * 3);
                }
                map_prefetch(&maps.xn);
            }
            __syncwarp();
            const uint32_t u[8] = {a.x, a.y, a.z, a.w, b.x, b.y, b.z, b.w};
            const uint32_t w[8] = {wa.x, wa.y, wa.z, wa.w, wb.x, wb.y, wb.z, wb.w};
            float f[16];
            float sum = 0.f;
#pragma unroll
            for (int i = 0; i < 8; i++) { f[2 * i] = bf_lo(u[i]); f[2 * i + 1] = bf_hi(u[i]); sum += f[2 * i] + f[2 * i + 1]; }
#pragma unroll
            for (int o = 16; o > 0; o >>= 1) sum += __shfl_xor_sync(~0u, sum, o);
            const float mean = sum * (1.f / DM);
            float sq = 0.f;
#pragma unroll
            for (int i = 0; i < 16; i++) { const float d = f[i] - mean; sq = fmaf(d, d, sq); }
#pragma unroll
            for (int o = 16; o > 0; o >>= 1) sq += __shfl_xor_sync(~0u, sq, o);
            const float mb_ = bfr(mean);
            const float vb = bfr(sq * (1.f / DM));
            const float rinv = 1.f / bfr(sqrtf(bfr(vb + 1e-5f)));
            uint32_t o[8];
            float r = 0.f;
#pragma unroll
            for (int i = 0; i < 8; i++) {
                const float d0 = bfr(f[2 * i] - mb_), d1 = bfr(f[2 * i + 1] - mb_);
                o[i] = packbf(d0 * rinv, d1 * rinv);
                r = fmaf(bf_lo(o[i]), bf_lo(w[i]), r);
                r = fmaf(bf_hi(o[i]), bf_hi(w[i]), r);
            }
            uint4* xo = reinterpret_cast<uint4*>(g_xn + (size_t)row * DM);
            xo[lane] = make_uint4(o[0], o[1], o[2], o[3]);
            xo[32 + lane] = make_uint4(o[4], o[5], o[6], o[7]);
#pragma unroll
            for (int of = 16; of > 0; of >>= 1) r += __shfl_xor_sync(~0u, r, of);
            if (lane == 0) g_r[row] = r;
        }
        __syncthreads();
        if (tid == 416) flag_release(C_LN + (idx >> 3));
        TL(1);
        {
            const int nb = idx & 7, mb = idx >> 3;
            if (warp == 15) {
                for (int c = G_ST; c < 8; c++) {
                    const int s = c - G_ST;
                    mbar_wait(bars + 8 * (B_EMPTY + s), 0);
                    if (lane == 0) {
                        mbar_expect_tx(bars + 8 * (B_FULL + s), 24576);
                        tma3d(sbase + s * G_STAGE + 16384, &maps.wqkv, bars + 8 * (B_FULL + s), c * 64, nb * 3);
                    }
                    __syncwarp();
                }
            } else if (warp == 14) {
                flag_wait(C_LN + mb, 8);
                fence_proxy_async_all();
                for (int c = 0; c < 8; c++) {
                    const int s = c & (G_ST - 1);
                    if (c >= G_ST) mbar_wait(bars + 8 * (B_EMPTY + s), 0);
                    if (lane == 0) {
                        mbar_expect_tx(bars + 8 * (B_FULL + s), 16384);
                        tma3d(sbase + s * G_STAGE, &maps.xn, bars + 8 * (B_FULL + s), mb * 128, c);
                    }
                    __syncwarp();
                }
            } else if (wg < 2) {
                float acc[96];
#pragma unroll
                for (int i = 0; i < 96; i++) acc[i] = 0.f;
#pragma unroll 1
                for (int c = 0; c < 8; c++) {
                    const int s = c & (G_ST - 1);
                    const uint32_t st = sbase + s * G_STAGE;
                    mbar_wait(bars + 8 * (B_FULL + s), c >> 2);
                    if (c == 0) TL(2);
                    const uint64_t da = mkdesc(st + wg * 8192, 16, 1024, 1);
                    const uint64_t db = mkdesc(st + 16384, 8192, 1024, 1);
                    WG_FENCE();
#pragma unroll
                    for (int k = 0; k < 4; k++) wgmma_n192(acc, da + k * 2, db + k * 128, (c | k) != 0);
                    WG_COMMIT();
                    if (c <= G_ST) {
                        WG_WAIT(1);
                        if (c >= 1 && (tid & 127) == 0) mbar_arrive(bars + 8 * (B_EMPTY + c - 1));
                    }
                }
                WG_WAIT(0);
                nbar_arrive(6, 512);
                TL(3);
                const int mt = mb * 8 + warp;
                uint32_t* dst0 = g_qkv + (mt >> 4) * 6144 + (mt & 15) * 64 + lane;
#pragma unroll
                for (int hh = 0; hh < 12; hh++) {
                    const int gh = nb * 12 + hh, ty = gh >> 5;
                    const float* a = &acc[hh * 8];
                    uint32_t* dst = dst0 + (gh & 31) * 49152 + ((ty + 2) % 3) * 2048;
                    const uint32_t ks = ty == 1 ? 0x1f801f80u : 0x3f803f80u;
                    dst[0] = hmul2bf(packbf(a[0], a[1]), ks);
                    dst[32] = hmul2bf(packbf(a[2], a[3]), ks);
                    dst[1024] = hmul2bf(packbf(a[4], a[5]), ks);
                    dst[1024 + 32] = hmul2bf(packbf(a[6], a[7]), ks);
                }
                TL(10);
                nbar_sync(8, 256);
                if (tid == 0) flag_release(C_QKV + nb);
            }
        }
        TL(4);
        const int head = idx >> 2, quarter = idx & 3, w4 = warp & 3;
        {
            if (warp == 15) {
                flag_wait_all(C_QKV + ((lane % 3) * 32 + head) / 12, 16);
                nbar_sync(6, 512);
                fence_proxy_async_all();
                if (lane == 0) {
                    const uint8_t* kvp = reinterpret_cast<const uint8_t*>(g_qkv + head * 49152);
                    for (int c = 0; c < 8; c++) mbar_expect_tx(bars + 8 * (B_KV + c), 16384);
#pragma unroll
                    for (int i = 0; i < 4; i++) bulk_g2s(sbase + SM_KV + i * 32768, kvp + i * 4096, 4096, bars + 8 * B_KV);
                }
                __syncwarp();
            } else if (wg >= 2) {
                nbar_sync(6, 512);
#pragma unroll 1
                for (int i = tid - 256; i < 2048; i += 224)
                    *reinterpret_cast<uint4*>(smem + SM_KV + 131072 + i * 16) = make_uint4(0x3f803f80u, 0x3f803f80u, 0x3f803f80u, 0x3f803f80u);
                fence_proxy_async();
            }
            __syncthreads();
            if ((tid & 127) == 96) {
                const uint8_t* kvp = reinterpret_cast<const uint8_t*>(g_qkv + head * 49152) + wg * 4096;
                fence_proxy_async_all();
#pragma unroll
                for (int c = 1; c < 8; c++) bulk_g2s(sbase + SM_KV + wg * 32768 + c * 4096, kvp + c * 24576, 4096, bars + 8 * (B_KV + c));
            } else if (tid == 320) {
                mbar_expect_tx(bars + 8 * B_WO, 65536);
                tma3d(sbase + SM_WO, &maps.wo, bars + 8 * B_WO, 0, idx & 7);
                tma3d(sbase + SM_WO + 32768, &maps.wo, bars + 8 * B_WO, 256, idx & 7);
                map_prefetch(&maps.o);
            }
            __syncwarp();
            const uint64_t kdesc0 = mkdesc(sbase + SM_KV, 32768, 128, 0);
            const uint64_t vdesc0 = mkdesc(sbase + SM_KV + 65536, 128, 32768, 0);
#pragma unroll 1
            for (int mt = 0; mt < 2; mt++) {
                const int m64 = quarter * 8 + mt * 4 + wg;
                uint32_t q[4];
                load_q(q, head, m64 * 4 + w4, lane);
                float s[32], s2[32], o[12];
#pragma unroll
                for (int i = 0; i < 12; i++) o[i] = 0.f;
                mbar_wait(bars + 8 * B_KV, 0);
                if (mt == 0) { TL(5); TLC(12); }
                WG_FENCE();
                qk64(s, q, kdesc0);
                WG_COMMIT(); WG_WAIT(0);
                float mx0 = -INFINITY, mx1 = -INFINITY;
#pragma unroll
                for (int i = 0; i < 8; i++) { mx0 = fmaxf(mx0, fmaxf(s[4 * i], s[4 * i + 1])); mx1 = fmaxf(mx1, fmaxf(s[4 * i + 2], s[4 * i + 3])); }
                mx0 = fmaxf(mx0, __shfl_xor_sync(~0u, mx0, 1)); mx0 = fmaxf(mx0, __shfl_xor_sync(~0u, mx0, 2));
                mx1 = fmaxf(mx1, __shfl_xor_sync(~0u, mx1, 1)); mx1 = fmaxf(mx1, __shfl_xor_sync(~0u, mx1, 2));
                if (mt == 1) {
                    nbar_sync(wg + 1, 128);
                    if ((tid & 127) == 0) flag_release(C_O + m64 - 4);
                }
                float cm0 = -(ceilf(mx0 * QS) + SHIFT), cm1 = -(ceilf(mx1 * QS) + SHIFT);
                float cp0 = (cm0 + 127.f) * sc, cp1 = (cm1 + 127.f) * sc;
                asm volatile("" : "+f"(cm0), "+f"(cm1), "+f"(cp0), "+f"(cp1));
                uint64_t kd = kdesc0, vd = vdesc0;
                auto step = [&](float (&sc_)[32], float (&sn)[32]) {
                    kd += 64;
                    WG_FENCE();
                    qk64(sn, q, kd);
                    WG_COMMIT();
#pragma unroll
                    for (int kk = 0; kk < 4; kk++) {
                        const int i0 = kk * 2, i1 = kk * 2 + 1;
                        const uint32_t p0 = packbf(ex2(fmaf(sc_[4 * i0], QS, cm0)), ex2(fmaf(sc_[4 * i0 + 1], QS, cm0)));
                        const uint32_t p1 = packbf(ex2(fmaf(sc_[4 * i0 + 2], QS, cm1)), ex2(fmaf(sc_[4 * i0 + 3], QS, cm1)));
                        const uint32_t p2 = polyexp(fmaf(sc_[4 * i1], scq, cp0), fmaf(sc_[4 * i1 + 1], scq, cp0));
                        const uint32_t p3 = polyexp(fmaf(sc_[4 * i1 + 2], scq, cp1), fmaf(sc_[4 * i1 + 3], scq, cp1));
                        WG_FENCE();
                        pv24(o, p0, p1, p2, p3, vd);
                        vd += 16;
                    }
                    WG_COMMIT();
                    WG_WAIT(1);
                };
#pragma unroll 1
                for (int c = 0; c < 16; c++) {
                    if (mt == 0 && (c & 1) == 0 && c < 14) mbar_wait(bars + 8 * B_KV + 4 * c + 8, 0);
                    step(s, s2); step(s2, s);
                }
                WG_WAIT(0);
                bool bad = !(o[8] > 0.f) || !(o[10] > 0.f);
#pragma unroll
                for (int i = 0; i < 12; i++) bad = bad || !(fabsf(o[i]) <= 3.0e38f);
                if (__any_sync(~0u, bad)) attn_safe(q[0], q[1], q[2], q[3], head, m64, w4, lane);
                else attn_store(o, head, m64, w4, lane);
            }
        }
        nbar_sync(wg + 1, 128);
        if ((tid & 127) == 32) {
            flag_release(C_O + quarter * 8 + 4 + wg);
        }

        TL(6); TLC(13);
        {
            const int nb = idx & 7, jb = idx >> 3;
            const int mbe = (jb >> 2) * 8 + (jb & 3);
            float* supd = reinterpret_cast<float*>(smem + SM_MISC + 512);
            if (warp == 15) nbar_sync(7, 512); else nbar_arrive(7, 512);
            TLX(11, 480);
            if (warp == 15) {
                flag_wait_all((lane & 1) ? C_FFN : C_O + mbe, (lane & 1) ? 64 : 32);
                nbar_arrive(9, 160);
                fence_proxy_async_all();
                if (lane == 0) {
                    for (int c = 0; c < 2; c++) {
                        mbar_expect_tx(bars + 8 * (B_OA + c), 32768);
                        tma3d(sbase + SM_KV + c * 32768, &maps.o, bars + 8 * (B_OA + c), mbe * 64, c * 4);
                    }
                }
                __syncwarp();
                flag_wait(C_O + mbe + 4, 32);
                fence_proxy_async_all();
                if (lane == 0) {
                    for (int c = 0; c < 2; c++) {
                        mbar_expect_tx(bars + 8 * (B_OA + 2 + c), 32768);
                        tma3d(sbase + SM_KV + 65536 + c * 32768, &maps.o, bars + 8 * (B_OA + 2 + c), (mbe + 4) * 64, c * 4);
                    }
                    exit_ticket();
                }
                __syncwarp();
            }
            const int late = wg >> 1, nh = wg & 1;
            const int mb = mbe + late * 4;
            const int g = lane >> 2, t = lane & 3;
            const int row0 = mb * 64 + w4 * 16 + g;
            const int col0 = nb * 64 + nh * 32 + t * 2;
            uint32_t xv[8], nv[8];
#pragma unroll
            for (int i = 0; i < 4; i++) {
                xv[2 * i] = *reinterpret_cast<const uint32_t*>(x + (size_t)row0 * DM + col0 + i * 8);
                xv[2 * i + 1] = *reinterpret_cast<const uint32_t*>(x + (size_t)(row0 + 8) * DM + col0 + i * 8);
                nv[2 * i] = __ldcg(reinterpret_cast<const uint32_t*>(g_xn + (size_t)row0 * DM + col0 + i * 8));
                nv[2 * i + 1] = __ldcg(reinterpret_cast<const uint32_t*>(g_xn + (size_t)(row0 + 8) * DM + col0 + i * 8));
            }
            if (wg == 0) {
                nbar_sync(9, 160);
                const int which = tid >> 6, col = nb * 64 + (tid & 63);
                const float y = __ldcg(&g_ypart[which * 512 + col]) + __ldcg(&g_ypart[1024 + which * 512 + col]) +
                                __ldcg(&g_ypart[2048 + which * 512 + col]) + __ldcg(&g_ypart[3072 + which * 512 + col]);
                supd[tid] = bfr(bfr(y) * __ldcg(&g_gate[which]));
                if (tid < 2) reinterpret_cast<int*>(supd + 128)[tid] = __ldcg(&g_sel[tid]);
            }
            float acc[16];
#pragma unroll
            for (int i = 0; i < 16; i++) acc[i] = 0.f;
            mbar_wait(bars + 8 * B_WO, 0);
            const uint32_t abase = sbase + SM_KV + late * 65536;
#pragma unroll 1
            for (int c = 0; c < 8; c++) {
                if ((c & 3) == 0) mbar_wait(bars + 8 * (B_OA + late * 2 + (c >> 2)), 0);
                if (c == 0) TLX(7, 256);
                const uint64_t da = mkdesc(abase + c * 8192, 16, 1024, 1);
                const uint64_t db = mkdesc(sbase + SM_WO + c * 8192 + nh * 64, 8192, 1024, 1);
                WG_FENCE();
#pragma unroll
                for (int k = 0; k < 4; k++) wgmma_n32(acc, da + k * 2, db + k * 128, (c | k) != 0);
                WG_COMMIT();
            }
            TLX(14, 256);
            __syncthreads();
            TLX(15, 256);
            const int sel0 = reinterpret_cast<const int*>(supd + 128)[0], sel1 = reinterpret_cast<const int*>(supd + 128)[1];
            WG_WAIT(0);
            TLX(8, 256);
#pragma unroll
            for (int h = 0; h < 2; h++) {
                const int row = row0 + h * 8;
                const int which = row == sel0 ? 0 : (row == sel1 ? 1 : -1);
#pragma unroll
                for (int i = 0; i < 4; i++) {
                    const int col = col0 + i * 8;
                    float b0 = bf_lo(nv[2 * i + h]), b1 = bf_hi(nv[2 * i + h]);
                    if (which >= 0) {
                        b0 = bfr(b0 + supd[which * 64 + col - nb * 64]); b1 = bfr(b1 + supd[which * 64 + col + 1 - nb * 64]);
                    }
                    const float t0 = bfr(bf_lo(xv[2 * i + h]) + bfr(acc[4 * i + 2 * h]));
                    const float t1 = bfr(bf_hi(xv[2 * i + h]) + bfr(acc[4 * i + 2 * h + 1]));
                    *reinterpret_cast<uint32_t*>(out + (size_t)row * DM + col) = packbf(t0 + b0, t1 + b1);
                }
            }
        }
        TLX(9, 256);
    }
}

typedef CUresult (*EncodeFn)(CUtensorMap*, CUtensorMapDataType, cuuint32_t, void*, const cuuint64_t*, const cuuint64_t*,
                             const cuuint32_t*, const cuuint32_t*, CUtensorMapInterleave, CUtensorMapSwizzle,
                             CUtensorMapL2promotion, CUtensorMapFloatOOBfill);

void make_map(EncodeFn fn, CUtensorMap* m, const void* ptr, uint64_t cols, uint64_t rows, uint32_t box_rows, uint32_t box_chunks) {
    cuuint64_t dims[3] = {64, rows, cols / 64};
    cuuint64_t strides[2] = {cols * 2, 128};
    cuuint32_t box[3] = {64, box_rows, box_chunks};
    cuuint32_t es[3] = {1, 1, 1};
    fn(m, CU_TENSOR_MAP_DATA_TYPE_BFLOAT16, 3, const_cast<void*>(ptr), dims, strides, box, es, CU_TENSOR_MAP_INTERLEAVE_NONE,
       CU_TENSOR_MAP_SWIZZLE_128B, CU_TENSOR_MAP_L2_PROMOTION_L2_256B, CU_TENSOR_MAP_FLOAT_OOB_FILL_NONE);
}

}

extern "C" void kernel_launch(void* const* d_in, const int* in_sizes, int n_in, void* d_out, int out_size) {
    const __nv_bfloat16* x = (const __nv_bfloat16*)d_in[0];
    const __nv_bfloat16* wqkv = (const __nv_bfloat16*)d_in[1];
    const __nv_bfloat16* wo = (const __nv_bfloat16*)d_in[2];
    const __nv_bfloat16* wr = (const __nv_bfloat16*)d_in[4];
    const __nv_bfloat16* wgate = (const __nv_bfloat16*)d_in[5];
    const __nv_bfloat16* wup = (const __nv_bfloat16*)d_in[6];
    const __nv_bfloat16* wdown = (const __nv_bfloat16*)d_in[7];
    __nv_bfloat16* out = (__nv_bfloat16*)d_out;

    static EncodeFn enc = nullptr;
    static void* p_xn = nullptr; static void* p_o = nullptr;
    if (!enc) {
        void* fn = nullptr; cudaDriverEntryPointQueryResult qr;
        cudaGetDriverEntryPoint("cuTensorMapEncodeTiled", &fn, cudaEnableDefault, &qr);
        enc = (EncodeFn)fn;
        cudaGetSymbolAddress(&p_xn, g_xn);
        cudaGetSymbolAddress(&p_o, g_o);
        cudaFuncSetAttribute(fused_kernel, cudaFuncAttributeMaxDynamicSharedMemorySize, FUSED_SMEM);
    }
    Maps maps;
    make_map(enc, &maps.g, wgate, FF, DM, 16, 7);
    make_map(enc, &maps.u, wup, FF, DM, 16, 7);
    make_map(enc, &maps.d, wdown, DM, FF, 32, 8);
    make_map(enc, &maps.xn, p_xn, DM, S_LEN, 128, 1);
    make_map(enc, &maps.wqkv, wqkv, 3 * DM, DM, 64, 3);
    make_map(enc, &maps.o, p_o, DM, S_LEN, 64, 4);
    make_map(enc, &maps.wo, wo, DM, DM, 256, 1);

    union { uint32_t u; float f; } scu; scu.u = 128u;

    cudaLaunchConfig_t cfg = {};
    cfg.gridDim = dim3(132); cfg.blockDim = dim3(512); cfg.dynamicSmemBytes = FUSED_SMEM; cfg.stream = cudaStreamPerThread;
    cudaLaunchKernelEx(&cfg, fused_kernel, maps, x, wr, out, scu.f);
}
```

```cpp
#include <cuda_runtime.h>
#include <cuda_bf16.h>
#include <cuda.h>
#include <stdint.h>
#include <type_traits>

namespace {

constexpr int S_LEN = 2048;
constexpr int DM = 512;
constexpr int NH = 32;
constexpr int FF = 1792;

__device__ __align__(1024) __nv_bfloat16 g_xn[S_LEN * DM];
__device__ __align__(16) float g_r[S_LEN];
__device__ __align__(1024) uint4 g_q[NH * 128 * 32];
__device__ __align__(1024) uint4 g_k[NH * 4096];
__device__ __align__(1024) uint4 g_v[NH * 4096];
__device__ __align__(1024) __nv_bfloat16 g_o[S_LEN * DM];
__device__ __align__(16) float g_ypart[4 * 2 * DM];
__device__ int g_sel[2];
__device__ float g_gate[2];

#define TL(k, slot) do {} while (0)

__device__ __forceinline__ uint32_t smem_u32(const void* p) { return (uint32_t)__cvta_generic_to_shared(p); }
__device__ __forceinline__ void pdl_wait() { asm volatile("griddepcontrol.wait;" ::: "memory"); }
__device__ __forceinline__ void pdl_launch() { asm volatile("griddepcontrol.launch_dependents;" ::: "memory"); }
__device__ __forceinline__ void mbar_init(uint32_t bar, uint32_t cnt) {
    asm volatile("mbarrier.init.shared::cta.b64 [%0], %1;" :: "r"(bar), "r"(cnt) : "memory");
}
__device__ __forceinline__ void mbar_expect_tx(uint32_t bar, uint32_t bytes) {
    asm volatile("mbarrier.arrive.expect_tx.shared::cta.b64 _, [%0], %1;" :: "r"(bar), "r"(bytes) : "memory");
}
__device__ __forceinline__ void mbar_arrive(uint32_t bar) {
    asm volatile("mbarrier.arrive.shared::cta.b64 _, [%0];" :: "r"(bar) : "memory");
}
__device__ __forceinline__ void mbar_wait(uint32_t bar, uint32_t parity) {
    asm volatile("{\n.reg .pred p;\n.reg .u32 n;\nmov.u32 n, 0;\n"
                 "WAIT_%=:\n"
                 "mbarrier.try_wait.parity.shared::cta.b64 p, [%0], %1;\n"
                 "@p bra DONE_%=;\n"
                 "add.u32 n, n, 1;\n"
                 "setp.lt.u32 p, n, 4000000;\n"
                 "@p bra WAIT_%=;\n"
                 "trap;\n"
                 "DONE_%=:\n}"
                 :: "r"(bar), "r"(parity) : "memory");
}
__device__ __forceinline__ void fence_barrier_init() { asm volatile("fence.mbarrier_init.release.cluster;" ::: "memory"); }
__device__ __forceinline__ void fence_proxy_async() { asm volatile("fence.proxy.async.shared::cta;" ::: "memory"); }
__device__ __forceinline__ void tma3d(uint32_t dst, const CUtensorMap* map, uint32_t bar, int row, int chunk) {
    asm volatile("cp.async.bulk.tensor.3d.shared::cluster.global.mbarrier::complete_tx::bytes [%0], [%1, {%3, %4, %5}], [%2];"
                 :: "r"(dst), "l"((uint64_t)map), "r"(bar), "r"(0), "r"(row), "r"(chunk) : "memory");
}
__device__ __forceinline__ void bulk_g2s(uint32_t dst, const void* src, uint32_t bytes, uint32_t bar) {
    asm volatile("cp.async.bulk.shared::cluster.global.mbarrier::complete_tx::bytes [%0], [%1], %2, [%3];"
                 :: "r"(dst), "l"((uint64_t)src), "r"(bytes), "r"(bar) : "memory");
}
__device__ __forceinline__ void l2_prefetch(const void* src, uint32_t bytes) {
    asm volatile("cp.async.bulk.prefetch.L2.global [%0], %1;" :: "l"((uint64_t)src), "r"(bytes) : "memory");
}
__device__ __forceinline__ void map_prefetch(const CUtensorMap* m) {
    asm volatile("prefetch.tensormap [%0];" :: "l"((uint64_t)m) : "memory");
}
__device__ __forceinline__ uint64_t mkdesc(uint32_t addr, uint32_t lbo, uint32_t sbo, uint32_t swz) {
    return (uint64_t)((addr & 0x3FFFF) >> 4) | ((uint64_t)(lbo >> 4) << 16) | ((uint64_t)(sbo >> 4) << 32) | ((uint64_t)swz << 62);
}
#define WG_FENCE() asm volatile("wgmma.fence.sync.aligned;" ::: "memory")
#define WG_COMMIT() asm volatile("wgmma.commit_group.sync.aligned;" ::: "memory")
#define WG_WAIT(n) asm volatile("wgmma.wait_group.sync.aligned %0;" :: "n"(n) : "memory")

__device__ __forceinline__ float ex2(float x) { float y; asm("ex2.approx.ftz.f32 %0, %1;" : "=f"(y) : "f"(x)); return y; }
__device__ __forceinline__ uint32_t packbf(float lo, float hi) {
    uint32_t r; asm("cvt.rn.bf16x2.f32 %0, %1, %2;" : "=r"(r) : "f"(hi), "f"(lo)); return r;
}
__device__ __forceinline__ float bf_lo(uint32_t v) { return __uint_as_float(v << 16); }
__device__ __forceinline__ float bf_hi(uint32_t v) { return __uint_as_float(v & 0xffff0000u); }
__device__ __forceinline__ float bfr(float x) { return __bfloat162float(__float2bfloat16_rn(x)); }

__global__ void __launch_bounds__(256) ln_kernel(const __nv_bfloat16* __restrict__ x, const __nv_bfloat16* __restrict__ wr) {
    TL(0, 0);
    pdl_launch();
    const int warp = threadIdx.x >> 5, lane = threadIdx.x & 31;
    const int row = blockIdx.x * 8 + warp;
    const uint4* xr = reinterpret_cast<const uint4*>(x + (size_t)row * DM);
    uint4 a = xr[lane], b = xr[32 + lane];
    const uint4* wp = reinterpret_cast<const uint4*>(wr);
    uint4 wa = wp[lane], wb = wp[32 + lane];
    uint32_t u[8] = {a.x, a.y, a.z, a.w, b.x, b.y, b.z, b.w};
    uint32_t w[8] = {wa.x, wa.y, wa.z, wa.w, wb.x, wb.y, wb.z, wb.w};
    float f[16];
    float sum = 0.f;
#pragma unroll
    for (int i = 0; i < 8; i++) { f[2 * i] = bf_lo(u[i]); f[2 * i + 1] = bf_hi(u[i]); sum += f[2 * i] + f[2 * i + 1]; }
#pragma unroll
    for (int o = 16; o > 0; o >>= 1) sum += __shfl_xor_sync(~0u, sum, o);
    const float mean = sum * (1.f / DM);
    float sq = 0.f;
#pragma unroll
    for (int i = 0; i < 16; i++) { float d = f[i] - mean; sq = fmaf(d, d, sq); }
#pragma unroll
    for (int o = 16; o > 0; o >>= 1) sq += __shfl_xor_sync(~0u, sq, o);
    const float mb = bfr(mean);
    const float vb = bfr(sq * (1.f / DM));
    const float den = bfr(sqrtf(bfr(vb + 1e-5f)));
    const float rinv = 1.f / den;
    uint32_t o[8];
    float r = 0.f;
#pragma unroll
    for (int i = 0; i < 8; i++) {
        float d0 = bfr(f[2 * i] - mb), d1 = bfr(f[2 * i + 1] - mb);
        o[i] = packbf(d0 * rinv, d1 * rinv);
        r = fmaf(bf_lo(o[i]), bf_lo(w[i]), r);
        r = fmaf(bf_hi(o[i]), bf_hi(w[i]), r);
    }
#pragma unroll
    for (int of = 16; of > 0; of >>= 1) r += __shfl_xor_sync(~0u, r, of);
    uint4* xo = reinterpret_cast<uint4*>(g_xn + (size_t)row * DM);
    xo[lane] = make_uint4(o[0], o[1], o[2], o[3]);
    xo[32 + lane] = make_uint4(o[4], o[5], o[6], o[7]);
    if (lane == 0) g_r[row] = r;
    TL(0, 3);
}

constexpr int K1_ST = 5;
constexpr int K1_STAGE = 16384 + 24576;
constexpr int K1_SMEM = K1_ST * K1_STAGE + 1024 + 128;

__device__ __forceinline__ void wgmma_n192(float (&d)[96], uint64_t da, uint64_t db, int scale_d) {
    asm volatile("{\n.reg .pred p;\nsetp.ne.b32 p, %98, 0;\n"
        "wgmma.mma_async.sync.aligned.m64n192k16.f32.bf16.bf16 "
        "{%0,%1,%2,%3,%4,%5,%6,%7,%8,%9,%10,%11,%12,%13,%14,%15,%16,%17,%18,%19,%20,%21,%22,%23,"
        "%24,%25,%26,%27,%28,%29,%30,%31,%32,%33,%34,%35,%36,%37,%38,%39,%40,%41,%42,%43,%44,%45,%46,%47,"
        "%48,%49,%50,%51,%52,%53,%54,%55,%56,%57,%58,%59,%60,%61,%62,%63,%64,%65,%66,%67,%68,%69,%70,%71,"
        "%72,%73,%74,%75,%76,%77,%78,%79,%80,%81,%82,%83,%84,%85,%86,%87,%88,%89,%90,%91,%92,%93,%94,%95}, "
        "%96, %97, p, 1, 1, 0, 1;\n}"
        : "+f"(d[0]), "+f"(d[1]), "+f"(d[2]), "+f"(d[3]), "+f"(d[4]), "+f"(d[5]), "+f"(d[6]), "+f"(d[7]),
          "+f"(d[8]), "+f"(d[9]), "+f"(d[10]), "+f"(d[11]), "+f"(d[12]), "+f"(d[13]), "+f"(d[14]), "+f"(d[15]),
          "+f"(d[16]), "+f"(d[17]), "+f"(d[18]), "+f"(d[19]), "+f"(d[20]), "+f"(d[21]), "+f"(d[22]), "+f"(d[23]),
          "+f"(d[24]), "+f"(d[25]), "+f"(d[26]), "+f"(d[27]), "+f"(d[28]), "+f"(d[29]), "+f"(d[30]), "+f"(d[31]),
          "+f"(d[32]), "+f"(d[33]), "+f"(d[34]), "+f"(d[35]), "+f"(d[36]), "+f"(d[37]), "+f"(d[38]), "+f"(d[39]),
          "+f"(d[40]), "+f"(d[41]), "+f"(d[42]), "+f"(d[43]), "+f"(d[44]), "+f"(d[45]), "+f"(d[46]), "+f"(d[47]),
          "+f"(d[48]), "+f"(d[49]), "+f"(d[50]), "+f"(d[51]), "+f"(d[52]), "+f"(d[53]), "+f"(d[54]), "+f"(d[55]),
          "+f"(d[56]), "+f"(d[57]), "+f"(d[58]), "+f"(d[59]), "+f"(d[60]), "+f"(d[61]), "+f"(d[62]), "+f"(d[63]),
          "+f"(d[64]), "+f"(d[65]), "+f"(d[66]), "+f"(d[67]), "+f"(d[68]), "+f"(d[69]), "+f"(d[70]), "+f"(d[71]),
          "+f"(d[72]), "+f"(d[73]), "+f"(d[74]), "+f"(d[75]), "+f"(d[76]), "+f"(d[77]), "+f"(d[78]), "+f"(d[79]),
          "+f"(d[80]), "+f"(d[81]), "+f"(d[82]), "+f"(d[83]), "+f"(d[84]), "+f"(d[85]), "+f"(d[86]), "+f"(d[87]),
          "+f"(d[88]), "+f"(d[89]), "+f"(d[90]), "+f"(d[91]), "+f"(d[92]), "+f"(d[93]), "+f"(d[94]), "+f"(d[95])
        : "l"(da), "l"(db), "r"(scale_d));
}

__global__ void __launch_bounds__(320, 1) qkv_kernel(const __grid_constant__ CUtensorMap mapA, const __grid_constant__ CUtensorMap mapB,
                                                     const uint8_t* __restrict__ pwg, const uint8_t* __restrict__ pwu, const uint8_t* __restrict__ pwd,
                                                     const uint8_t* __restrict__ pwo) {
    extern __shared__ uint8_t smem_raw[];
    const uint32_t sbase = (smem_u32(smem_raw) + 1023u) & ~1023u;
    const uint32_t bars = sbase + K1_ST * K1_STAGE;
    const int warp = threadIdx.x >> 5, lane = threadIdx.x & 31;
    const int nb = blockIdx.x & 7, mb = blockIdx.x >> 3;
    TL(1, 0);
    if (threadIdx.x == 0) {
        for (int s = 0; s < K1_ST; s++) { mbar_init(bars + 8 * s, 2); mbar_init(bars + 8 * (K1_ST + s), 2); }
        fence_barrier_init();
    }
    __syncthreads();
    if (warp == 8) {
        if (lane == 0) {
            for (int c = 0; c < 8; c++) {
                const int s = c < K1_ST ? c : c - K1_ST;
                if (c >= K1_ST) mbar_wait(bars + 8 * (K1_ST + s), 0);
                mbar_expect_tx(bars + 8 * s, 24576);
                tma3d(sbase + s * K1_STAGE + 16384, &mapB, bars + 8 * s, c * 64, nb * 3);
            }
        }
        return;
    }
    if (warp == 9) {
        if (lane == 0) {
            map_prefetch(&mapA);
            pdl_wait();
            pdl_launch();
            for (int c = 0; c < 8; c++) {
                const int s = c < K1_ST ? c : c - K1_ST;
                if (c == K1_ST) {
                    l2_prefetch(pwg + blockIdx.x * 14336, 14336);
                    l2_prefetch(pwu + blockIdx.x * 14336, 14336);
                    l2_prefetch(pwd + blockIdx.x * 14336, 14336);
                    l2_prefetch(pwo + blockIdx.x * 4096, 4096);
                }
                if (c >= K1_ST) mbar_wait(bars + 8 * (K1_ST + s), 0);
                mbar_expect_tx(bars + 8 * s, 16384);
                tma3d(sbase + s * K1_STAGE, &mapA, bars + 8 * s, mb * 128, c);
            }
        }
        return;
    }
    const int wg = warp >> 2;
    float acc[96];
#pragma unroll
    for (int i = 0; i < 96; i++) acc[i] = 0.f;
#pragma unroll 1
    for (int c = 0; c < 8; c++) {
        const int s = c < K1_ST ? c : c - K1_ST;
        const uint32_t st = sbase + s * K1_STAGE;
        mbar_wait(bars + 8 * s, c < K1_ST ? 0 : 1);
        if (c == 0) TL(1, 1);
        const uint64_t da = mkdesc(st + wg * 8192, 16, 1024, 1);
        const uint64_t db = mkdesc(st + 16384, 8192, 1024, 1);
        WG_FENCE();
#pragma unroll
        for (int k = 0; k < 4; k++) wgmma_n192(acc, da + k * 2, db + k * 128, (c | k) != 0);
        WG_COMMIT();
        if (c + K1_ST < 8 + 1) {
            WG_WAIT(1);
            if (c >= 1 && (threadIdx.x & 127) == 0) mbar_arrive(bars + 8 * (K1_ST + c - 1));
        }
    }
    WG_WAIT(0);
    TL(1, 2);
    const int g = lane >> 2, t = lane & 3;
    const int mt = mb * 8 + warp;
#pragma unroll
    for (int hh = 0; hh < 12; hh++) {
        const int gh = nb * 12 + hh;
        const float* a = &acc[hh * 8];
        if (gh < 32) {
            uint4 v;
            v.x = packbf(a[0], a[1]); v.y = packbf(a[2], a[3]);
            v.z = packbf(a[4], a[5]); v.w = packbf(a[6], a[7]);
            g_q[(gh * 128 + mt) * 32 + lane] = v;
        } else {
            uint32_t* dst = reinterpret_cast<uint32_t*>(gh < 64 ? g_k + (gh - 32) * 4096 : g_v + (gh - 64) * 4096);
            const float ks = gh < 64 ? 5.421010862427522e-20f : 1.0f;
            const int off = (mt * 16 + g) * 4 + t;
            dst[off] = packbf(a[0] * ks, a[1] * ks);
            dst[off + 32] = packbf(a[2] * ks, a[3] * ks);
            dst[8192 + off] = packbf(a[4] * ks, a[5] * ks);
            dst[8192 + off + 32] = packbf(a[6] * ks, a[7] * ks);
        }
    }
    TL(1, 3);
}

constexpr float SHIFT = 90.0f;
constexpr float QS = 0.25f * 1.4426950408889634f * 18446744073709551616.0f;
constexpr float scq = 0.25f * 1.4426950408889634f * 3.3087224502121107e-24f;
constexpr int K2_SMEM = 163840 + 1024 + 128;

__device__ __forceinline__ uint32_t polyexp(float lo, float hi) {
    uint32_t w, g, q, h;
    asm("cvt.pack.sat.s16.s32 %0, %1, %2;" : "=r"(w) : "r"(__float_as_uint(hi)), "r"(__float_as_uint(lo)));
    g = w & 0x007F007Fu;
    asm("fma.rn.f16x2 %0, %1, %2, %3;" : "=r"(q) : "r"(g), "r"(0xf940f940u), "r"(0x35513551u));
    asm("mul.rn.f16x2 %0, %1, %2;" : "=r"(h) : "r"(q), "r"(g));
    return w - h;
}
__device__ __forceinline__ void qk64(float (&s)[32], const uint32_t (&q)[4], uint64_t db) {
    asm volatile("wgmma.mma_async.sync.aligned.m64n64k16.f32.bf16.bf16 "
        "{%0,%1,%2,%3,%4,%5,%6,%7,%8,%9,%10,%11,%12,%13,%14,%15,%16,%17,%18,%19,%20,%21,%22,%23,%24,%25,%26,%27,%28,%29,%30,%31}, "
        "{%32,%33,%34,%35}, %36, 0, 1, 1, 0;"
        : "=f"(s[0]), "=f"(s[1]), "=f"(s[2]), "=f"(s[3]), "=f"(s[4]), "=f"(s[5]), "=f"(s[6]), "=f"(s[7]),
          "=f"(s[8]), "=f"(s[9]), "=f"(s[10]), "=f"(s[11]), "=f"(s[12]), "=f"(s[13]), "=f"(s[14]), "=f"(s[15]),
          "=f"(s[16]), "=f"(s[17]), "=f"(s[18]), "=f"(s[19]), "=f"(s[20]), "=f"(s[21]), "=f"(s[22]), "=f"(s[23]),
          "=f"(s[24]), "=f"(s[25]), "=f"(s[26]), "=f"(s[27]), "=f"(s[28]), "=f"(s[29]), "=f"(s[30]), "=f"(s[31])
        : "r"(q[0]), "r"(q[1]), "r"(q[2]), "r"(q[3]), "l"(db));
}
__device__ __forceinline__ void pv24(float (&o)[12], uint32_t a0, uint32_t a1, uint32_t a2, uint32_t a3, uint64_t db) {
    asm volatile("wgmma.mma_async.sync.aligned.m64n24k16.f32.bf16.bf16 "
        "{%0,%1,%2,%3,%4,%5,%6,%7,%8,%9,%10,%11}, {%12,%13,%14,%15}, %16, 1, 1, 1, 1;"
        : "+f"(o[0]), "+f"(o[1]), "+f"(o[2]), "+f"(o[3]), "+f"(o[4]), "+f"(o[5]), "+f"(o[6]), "+f"(o[7]),
          "+f"(o[8]), "+f"(o[9]), "+f"(o[10]), "+f"(o[11])
        : "r"(a0), "r"(a1), "r"(a2), "r"(a3), "l"(db));
}

__device__ __forceinline__ void attn_safe(float (&o)[12], const uint32_t (&q)[4], uint64_t kdesc0, uint64_t vdesc0) {
    float s[32];
    float m0 = -INFINITY, m1 = -INFINITY;
#pragma unroll
    for (int i = 0; i < 12; i++) o[i] = 0.f;
#pragma unroll 1
    for (int j = 0; j < 32; j++) {
        WG_FENCE();
        qk64(s, q, kdesc0 + (uint64_t)(j * 64));
        WG_COMMIT(); WG_WAIT(0);
        float n0 = m0, n1 = m1;
#pragma unroll
        for (int i = 0; i < 8; i++) { n0 = fmaxf(n0, fmaxf(s[4 * i], s[4 * i + 1])); n1 = fmaxf(n1, fmaxf(s[4 * i + 2], s[4 * i + 3])); }
        n0 = fmaxf(n0, __shfl_xor_sync(~0u, n0, 1)); n0 = fmaxf(n0, __shfl_xor_sync(~0u, n0, 2));
        n1 = fmaxf(n1, __shfl_xor_sync(~0u, n1, 1)); n1 = fmaxf(n1, __shfl_xor_sync(~0u, n1, 2));
        const float c0 = ex2((m0 - n0) * QS), c1 = ex2((m1 - n1) * QS);
        m0 = n0; m1 = n1;
#pragma unroll
        for (int i = 0; i < 3; i++) { o[4 * i] *= c0; o[4 * i + 1] *= c0; o[4 * i + 2] *= c1; o[4 * i + 3] *= c1; }
        uint32_t p[16];
#pragma unroll
        for (int i = 0; i < 8; i++) {
            p[2 * i] = packbf(ex2((s[4 * i] - m0) * QS), ex2((s[4 * i + 1] - m0) * QS));
            p[2 * i + 1] = packbf(ex2((s[4 * i + 2] - m1) * QS), ex2((s[4 * i + 3] - m1) * QS));
        }
        WG_FENCE();
#pragma unroll
        for (int kk = 0; kk < 4; kk++) pv24(o, p[4 * kk], p[4 * kk + 1], p[4 * kk + 2], p[4 * kk + 3], vdesc0 + (uint64_t)(j * 64 + kk * 16));
        WG_COMMIT(); WG_WAIT(0);
    }
}

__device__ __forceinline__ void attn_store(const float (&o)[12], int head, int m64, int warp, int lane) {
    const int g = lane >> 2, t = lane & 3;
    const int row = m64 * 64 + warp * 16 + g;
    const float i0 = 1.f / o[8], i1 = 1.f / o[10];
    uint32_t* p0 = reinterpret_cast<uint32_t*>(g_o + (size_t)row * DM + head * 16 + t * 2);
    uint32_t* p1 = reinterpret_cast<uint32_t*>(g_o + (size_t)(row + 8) * DM + head * 16 + t * 2);
    p0[0] = packbf(o[0] * i0, o[1] * i0); p0[4] = packbf(o[4] * i0, o[5] * i0);
    p1[0] = packbf(o[2] * i1, o[3] * i1); p1[4] = packbf(o[6] * i1, o[7] * i1);
}

constexpr int FS_N = 4;
constexpr int FS_BYTES = 32768;
__device__ __forceinline__ void ldsm4t(uint32_t& r0, uint32_t& r1, uint32_t& r2, uint32_t& r3, uint32_t addr) {
    asm volatile("ldmatrix.sync.aligned.m8n8.x4.trans.shared.b16 {%0,%1,%2,%3}, [%4];" : "=r"(r0), "=r"(r1), "=r"(r2), "=r"(r3) : "r"(addr) : "memory");
}
__device__ __forceinline__ void mma16816(float (&d)[4], uint32_t a0, uint32_t a2, uint32_t b0, uint32_t b1) {
    asm volatile("mma.sync.aligned.m16n8k16.row.col.f32.bf16.bf16.f32 {%0,%1,%2,%3}, {%4,%5,%6,%5}, {%7,%8}, {%0,%1,%2,%3};"
                 : "+f"(d[0]), "+f"(d[1]), "+f"(d[2]), "+f"(d[3]) : "r"(a0), "r"(0u), "r"(a2), "r"(b0), "r"(b1));
}
__device__ void ffn_block(int c, uint8_t* smem, uint32_t sbase, const CUtensorMap* mapG, const CUtensorMap* mapU, const CUtensorMap* mapD) {
    const int tid = threadIdx.x, warp = tid >> 5, lane = tid & 31;
    uint32_t* sx = reinterpret_cast<uint32_t*>(smem + FS_N * FS_BYTES);
    __nv_bfloat16* sh = reinterpret_cast<__nv_bfloat16*>(sx + 512);
    const uint32_t bars = sbase + FS_N * FS_BYTES + 8192;
    __shared__ float tv[32]; __shared__ int ti[32];
    __shared__ int ssel[2];
    auto issue = [&](int item) {
        const int slot = item % FS_N;
        const uint32_t dst = sbase + slot * FS_BYTES, bar = bars + 8 * slot;
        mbar_expect_tx(bar, item < 32 ? 28672 : 32768);
        if (item < 32) {
            tma3d(dst, mapG, bar, item * 16, c * 7);
            tma3d(dst + 14336, mapU, bar, item * 16, c * 7);
        } else {
            tma3d(dst, mapD, bar, c * 448 + (item - 32) * 32, 0);
        }
    };
    if (tid == 0) {
        for (int i = 0; i < FS_N; i++) mbar_init(bars + 8 * i, 1);
        fence_barrier_init();
        for (int i = 0; i < FS_N; i++) issue(i);
    }
    float b1 = -INFINITY, b2 = -INFINITY; int i1 = 0x7fffffff, i2 = 0x7fffffff;
    auto push = [&](float v, int i) {
        if (v > b1 || (v == b1 && i < i1)) { b2 = b1; i2 = i1; b1 = v; i1 = i; }
        else if (v > b2 || (v == b2 && i < i2)) { b2 = v; i2 = i; }
    };
    {
        const float4 rv = reinterpret_cast<const float4*>(g_r)[tid];
        push(rv.x, 4 * tid); push(rv.y, 4 * tid + 1); push(rv.z, 4 * tid + 2); push(rv.w, 4 * tid + 3);
    }
#pragma unroll
    for (int o = 16; o > 0; o >>= 1) {
        float v1 = __shfl_xor_sync(~0u, b1, o), v2 = __shfl_xor_sync(~0u, b2, o);
        int j1 = __shfl_xor_sync(~0u, i1, o), j2 = __shfl_xor_sync(~0u, i2, o);
        push(v1, j1); push(v2, j2);
    }
    if (lane == 0) { tv[2 * warp] = b1; ti[2 * warp] = i1; tv[2 * warp + 1] = b2; ti[2 * warp + 1] = i2; }
    __syncthreads();
    if (warp == 1) {
        b1 = tv[lane]; i1 = ti[lane]; b2 = -INFINITY; i2 = 0x7fffffff;
#pragma unroll
        for (int o = 16; o > 0; o >>= 1) {
            float v1 = __shfl_xor_sync(~0u, b1, o), v2 = __shfl_xor_sync(~0u, b2, o);
            int j1 = __shfl_xor_sync(~0u, i1, o), j2 = __shfl_xor_sync(~0u, i2, o);
            push(v1, j1); push(v2, j2);
        }
        if (lane == 0) {
            i1 = min(max(i1, 0), S_LEN - 1); i2 = min(max(i2, 0), S_LEN - 1);
            ssel[0] = i1; ssel[1] = i2;
            if (c == 0) {
                g_sel[0] = i1; g_sel[1] = i2;
                g_gate[0] = bfr(1.f / (1.f + __expf(-bfr(b1))));
                g_gate[1] = bfr(1.f / (1.f + __expf(-bfr(b2))));
            }
        }
    }
    __syncthreads();
    sx[tid] = *reinterpret_cast<const uint32_t*>(g_xn + (size_t)ssel[tid >> 8] * DM + (tid & 255) * 2);
    __syncthreads();
    TL(2, 1);
    const int g = lane >> 2, t = lane & 3;
    const int lrow = lane & 15, lsel = lane >> 4;
    {
        float ag[4][4], au[4][4];
#pragma unroll
        for (int j = 0; j < 4; j++) { ag[j][0] = ag[j][1] = ag[j][2] = ag[j][3] = 0.f; au[j][0] = au[j][1] = au[j][2] = au[j][3] = 0.f; }
#pragma unroll 1
        for (int it = 0; it < 32; it++) {
            const int slot = it % FS_N;
            const uint32_t a0 = g < 2 ? sx[g * 256 + it * 8 + t] : 0u, a2 = g < 2 ? sx[g * 256 + it * 8 + 4 + t] : 0u;
            mbar_wait(bars + 8 * slot, (it / FS_N) & 1);
            const uint32_t base = sbase + slot * FS_BYTES + lsel * 14336 + lrow * 128;
#pragma unroll
            for (int j = 0; j < 4; j++) {
                const int nt = warp + j * 16;
                if (nt < 56) {
                    uint32_t b0, b1, b2, b3;
                    ldsm4t(b0, b1, b2, b3, base + (nt >> 3) * 2048 + (((nt & 7) ^ (lrow & 7)) << 4));
                    mma16816(ag[j], a0, a2, b0, b1);
                    mma16816(au[j], a0, a2, b2, b3);
                }
            }
            __syncthreads();
            if (tid == 480) issue(it + FS_N);
        }
        if (g < 2) {
#pragma unroll
            for (int j = 0; j < 4; j++) {
                const int nt = warp + j * 16;
                if (nt < 56) {
#pragma unroll
                    for (int e = 0; e < 2; e++) {
                        const float gs = bfr(ag[j][e]), us = bfr(au[j][e]);
                        const float sg = bfr(gs / (1.f + __expf(-gs)));
                        sh[g * 448 + nt * 8 + t * 2 + e] = __float2bfloat16_rn(sg * us);
                    }
                }
            }
        }
        __syncthreads();
    }
    TL(2, 2);
    {
        const uint32_t* shw = reinterpret_cast<const uint32_t*>(sh);
        float a[4][4];
#pragma unroll
        for (int j = 0; j < 4; j++) a[j][0] = a[j][1] = a[j][2] = a[j][3] = 0.f;
#pragma unroll 1
        for (int it = 32; it < 46; it++) {
            const int slot = it % FS_N;
            uint32_t af[4];
#pragma unroll
            for (int q = 0; q < 4; q++) af[q] = g < 2 ? shw[g * 224 + (it - 32) * 16 + q * 4 + t] : 0u;
            mbar_wait(bars + 8 * slot, (it / FS_N) & 1);
            const uint32_t base = sbase + slot * FS_BYTES + (warp >> 1) * 4096 + lane * 128;
#pragma unroll
            for (int j = 0; j < 4; j++) {
                const int u = (warp & 1) * 4 + j;
                uint32_t b0, b1, b2, b3;
                ldsm4t(b0, b1, b2, b3, base + ((u ^ (lane & 7)) << 4));
                mma16816(a[j], af[0], af[1], b0, b1);
                mma16816(a[j], af[2], af[3], b2, b3);
            }
            __syncthreads();
            if (tid == 480 && it + FS_N < 46) issue(it + FS_N);
        }
        if (g < 2) {
#pragma unroll
            for (int j = 0; j < 4; j++)
                *reinterpret_cast<float2*>(&g_ypart[c * 1024 + g * 512 + (warp * 4 + j) * 8 + t * 2]) = make_float2(a[j][0], a[j][1]);
        }
    }
}

__global__ void __launch_bounds__(512, 1) attn_kernel(const __grid_constant__ CUtensorMap mapG, const __grid_constant__ CUtensorMap mapU,
                                                      const __grid_constant__ CUtensorMap mapD, float sc) {
    extern __shared__ uint8_t smem_raw[];
    const uint32_t sraw = smem_u32(smem_raw);
    const uint32_t sbase = (sraw + 1023u) & ~1023u;
    uint8_t* sptr = smem_raw + (sbase - sraw);
    TL(2, 0);
    if (blockIdx.x < 4) {
        pdl_launch();
        ffn_block(blockIdx.x, sptr, sbase, &mapG, &mapU, &mapD);
        TL(2, 3);
        return;
    }
    const uint32_t bars = sbase + 163840;
    const int head = (blockIdx.x - 4) >> 2, quarter = blockIdx.x & 3;
    const int wg = threadIdx.x >> 7, warp = (threadIdx.x >> 5) & 3, lane = threadIdx.x & 31;
    if (threadIdx.x == 0) {
        for (int c = 0; c < 8; c++) mbar_init(bars + 8 * c, 1);
        fence_barrier_init();
        for (int c = 0; c < 8; c++) mbar_expect_tx(bars + 8 * c, 16384);
    }
    {
        uint4* ones = reinterpret_cast<uint4*>(sptr + 131072);
        for (int i = threadIdx.x; i < 2048; i += 512) ones[i] = make_uint4(0x3f803f80u, 0x3f803f80u, 0x3f803f80u, 0x3f803f80u);
        fence_proxy_async();
    }
    __syncthreads();
    pdl_wait();
    pdl_launch();
    TL(2, 1);
    if ((threadIdx.x & 127) == 96) {
        const uint8_t* src = reinterpret_cast<const uint8_t*>((wg < 2 ? g_k : g_v) + head * 4096) + (wg & 1) * 32768;
#pragma unroll
        for (int c = 0; c < 8; c++) bulk_g2s(sbase + wg * 32768 + c * 4096, src + c * 4096, 4096, bars + 8 * c);
    }
    __syncwarp();
    const uint64_t kdesc0 = mkdesc(sbase, 32768, 128, 0);
    const uint64_t vdesc0 = mkdesc(sbase + 65536, 128, 32768, 0);
    uint32_t badmask = 0;
    uint32_t q[4];
    { const uint4 qq = g_q[(head * 128 + (quarter * 8 + wg) * 4 + warp) * 32 + lane]; q[0] = qq.x; q[1] = qq.y; q[2] = qq.z; q[3] = qq.w; }
#pragma unroll 1
    for (int mt = 0; mt < 2; mt++) {
        const int m64 = quarter * 8 + mt * 4 + wg;
        float s[32], s2[32], o[12];
#pragma unroll
        for (int i = 0; i < 12; i++) o[i] = 0.f;
        mbar_wait(bars, 0);
        if (mt == 0) TL(2, 2);
        WG_FENCE();
        qk64(s, q, kdesc0);
        WG_COMMIT(); WG_WAIT(0);
        float mx0 = -INFINITY, mx1 = -INFINITY;
#pragma unroll
        for (int i = 0; i < 8; i++) { mx0 = fmaxf(mx0, fmaxf(s[4 * i], s[4 * i + 1])); mx1 = fmaxf(mx1, fmaxf(s[4 * i + 2], s[4 * i + 3])); }
        mx0 = fmaxf(mx0, __shfl_xor_sync(~0u, mx0, 1)); mx0 = fmaxf(mx0, __shfl_xor_sync(~0u, mx0, 2));
        mx1 = fmaxf(mx1, __shfl_xor_sync(~0u, mx1, 1)); mx1 = fmaxf(mx1, __shfl_xor_sync(~0u, mx1, 2));
        float cm0 = -(ceilf(mx0 * QS) + SHIFT), cm1 = -(ceilf(mx1 * QS) + SHIFT);
        float cp0 = (cm0 + 127.f) * sc, cp1 = (cm1 + 127.f) * sc;
        asm volatile("" : "+f"(cm0), "+f"(cm1), "+f"(cp0), "+f"(cp1));
        uint64_t kd = kdesc0, vd = vdesc0;
        auto step = [&](float (&sc_)[32], float (&sn)[32]) {
            kd += 64;
            WG_FENCE();
            qk64(sn, q, kd);
            WG_COMMIT();
#pragma unroll
            for (int kk = 0; kk < 4; kk++) {
                const int i0 = kk * 2, i1 = kk * 2 + 1;
                const uint32_t p0 = packbf(ex2(fmaf(sc_[4 * i0], QS, cm0)), ex2(fmaf(sc_[4 * i0 + 1], QS, cm0)));
                const uint32_t p1 = packbf(ex2(fmaf(sc_[4 * i0 + 2], QS, cm1)), ex2(fmaf(sc_[4 * i0 + 3], QS, cm1)));
                const uint32_t p2 = polyexp(fmaf(sc_[4 * i1], scq, cp0), fmaf(sc_[4 * i1 + 1], scq, cp0));
                const uint32_t p3 = polyexp(fmaf(sc_[4 * i1 + 2], scq, cp1), fmaf(sc_[4 * i1 + 3], scq, cp1));
                WG_FENCE();
                pv24(o, p0, p1, p2, p3, vd);
                vd += 16;
            }
            WG_COMMIT();
            WG_WAIT(1);
        };
#pragma unroll 1
        for (int c = 0; c < 16; c++) {
            if (mt == 0 && (c & 1) == 0 && c < 14) mbar_wait(bars + 4 * c + 8, 0);
            step(s, s2); step(s2, s);
        }
        WG_WAIT(0);
        {
            const uint4 qq = g_q[(head * 128 + (quarter * 8 + 4 + wg) * 4 + warp) * 32 + lane]; q[0] = qq.x; q[1] = qq.y; q[2] = qq.z; q[3] = qq.w;
        }
        bool bad = !(o[8] > 0.f) || !(o[10] > 0.f);
#pragma unroll
        for (int i = 0; i < 12; i++) bad = bad || !(fabsf(o[i]) <= 3.0e38f);
        uint32_t anybad;
        asm volatile("{\n.reg .pred p, q;\nsetp.ne.u32 p, %1, 0;\nbarrier.cta.red.or.pred q, %2, 128, p;\nselp.u32 %0, 1, 0, q;\n}"
                     : "=r"(anybad) : "r"((uint32_t)bad), "r"(wg + 1) : "memory");
        badmask |= anybad << mt;
        attn_store(o, head, m64, warp, lane);
    }
#pragma unroll 1
    for (int mt = 0; mt < 2; mt++) {
        if (!((badmask >> mt) & 1)) continue;
        const int m64 = quarter * 8 + mt * 4 + wg;
        { const uint4 qq = g_q[(head * 128 + m64 * 4 + warp) * 32 + lane]; q[0] = qq.x; q[1] = qq.y; q[2] = qq.z; q[3] = qq.w; }
        float o[12];
        attn_safe(o, q, mkdesc(sbase, 32768, 128, 0), mkdesc(sbase + 65536, 128, 32768, 0));
        attn_store(o, head, m64, warp, lane);
    }
    TL(2, 3);
}

constexpr int K3_SMEM = 8 * 8192 + 8 * 16384 + 1024 + 128;

__device__ __forceinline__ void wgmma_n64(float (&d)[32], uint64_t da, uint64_t db, int scale_d) {
    asm volatile("{\n.reg .pred p;\nsetp.ne.b32 p, %34, 0;\n"
        "wgmma.mma_async.sync.aligned.m64n64k16.f32.bf16.bf16 "
        "{%0,%1,%2,%3,%4,%5,%6,%7,%8,%9,%10,%11,%12,%13,%14,%15,%16,%17,%18,%19,%20,%21,%22,%23,%24,%25,%26,%27,%28,%29,%30,%31}, "
        "%32, %33, p, 1, 1, 0, 1;\n}"
        : "+f"(d[0]), "+f"(d[1]), "+f"(d[2]), "+f"(d[3]), "+f"(d[4]), "+f"(d[5]), "+f"(d[6]), "+f"(d[7]),
          "+f"(d[8]), "+f"(d[9]), "+f"(d[10]), "+f"(d[11]), "+f"(d[12]), "+f"(d[13]), "+f"(d[14]), "+f"(d[15]),
          "+f"(d[16]), "+f"(d[17]), "+f"(d[18]), "+f"(d[19]), "+f"(d[20]), "+f"(d[21]), "+f"(d[22]), "+f"(d[23]),
          "+f"(d[24]), "+f"(d[25]), "+f"(d[26]), "+f"(d[27]), "+f"(d[28]), "+f"(d[29]), "+f"(d[30]), "+f"(d[31])
        : "l"(da), "l"(db), "r"(scale_d));
}

__global__ void __launch_bounds__(256, 1) oproj_kernel(const __grid_constant__ CUtensorMap mapA, const __grid_constant__ CUtensorMap mapB,
                                                       const __nv_bfloat16* __restrict__ x, __nv_bfloat16* __restrict__ out) {
    extern __shared__ uint8_t smem_raw[];
    const uint32_t sbase = (smem_u32(smem_raw) + 1023u) & ~1023u;
    const uint32_t sA = sbase, sB = sbase + 8 * 8192, bars = sbase + 8 * 8192 + 8 * 16384;
    const int warp = threadIdx.x >> 5, lane = threadIdx.x & 31, wg = warp >> 2;
    const int nb = blockIdx.x & 3, mb = blockIdx.x >> 2;
    TL(3, 0);
    if (threadIdx.x == 0) {
        for (int c = 0; c < 8; c++) mbar_init(bars + 8 * c, 1);
        fence_barrier_init();
        map_prefetch(&mapA);
        for (int h = 0; h < 2; h++) {
            mbar_expect_tx(bars + 8 * (4 + h), 65536);
            tma3d(sB + h * 65536, &mapB, bars + 8 * (4 + h), h * 256, nb * 2);
        }
    }
    const int g = lane >> 2, t = lane & 3;
    const int row0 = mb * 64 + (warp & 3) * 16 + g;
    const int col0 = nb * 128 + wg * 64 + t * 2;
    uint32_t xv[16], nv[16];
#pragma unroll
    for (int i = 0; i < 8; i++) {
        xv[2 * i] = *reinterpret_cast<const uint32_t*>(x + (size_t)row0 * DM + col0 + i * 8);
        xv[2 * i + 1] = *reinterpret_cast<const uint32_t*>(x + (size_t)(row0 + 8) * DM + col0 + i * 8);
        nv[2 * i] = *reinterpret_cast<const uint32_t*>(g_xn + (size_t)row0 * DM + col0 + i * 8);
        nv[2 * i + 1] = *reinterpret_cast<const uint32_t*>(g_xn + (size_t)(row0 + 8) * DM + col0 + i * 8);
    }
    __syncthreads();
    pdl_wait();
    TL(3, 1);
    if (threadIdx.x == 0) {
        for (int c = 0; c < 4; c++) {
            mbar_expect_tx(bars + 8 * c, 16384);
            tma3d(sA + c * 16384, &mapA, bars + 8 * c, mb * 64, c * 2);
        }
    }
    __shared__ float supd[2][128];
    const int sel0 = g_sel[0], sel1 = g_sel[1];
    {
        const int which = threadIdx.x >> 7, col = nb * 128 + (threadIdx.x & 127);
        const float y = g_ypart[which * 512 + col] + g_ypart[1024 + which * 512 + col] + g_ypart[2048 + which * 512 + col] + g_ypart[3072 + which * 512 + col];
        supd[which][threadIdx.x & 127] = bfr(bfr(y) * g_gate[which]);
    }
    __syncthreads();
    float acc[32];
#pragma unroll
    for (int i = 0; i < 32; i++) acc[i] = 0.f;
#pragma unroll 1
    for (int c = 0; c < 8; c++) {
        if ((c & 3) == 0) mbar_wait(bars + 8 * (4 + (c >> 2)), 0);
        if ((c & 1) == 0) mbar_wait(bars + 8 * (c >> 1), 0);
        const uint64_t da = mkdesc(sA + c * 8192, 16, 1024, 1);
        const uint64_t db = mkdesc(sB + (c >> 2) * 65536 + wg * 32768 + (c & 3) * 8192, 8192, 1024, 1);
        WG_FENCE();
#pragma unroll
        for (int k = 0; k < 4; k++) wgmma_n64(acc, da + k * 2, db + k * 128, (c | k) != 0);
        WG_COMMIT();
    }
    WG_WAIT(0);
    TL(3, 2);
#pragma unroll
    for (int h = 0; h < 2; h++) {
        const int row = row0 + h * 8;
        const int which = row == sel0 ? 0 : (row == sel1 ? 1 : -1);
#pragma unroll
        for (int i = 0; i < 8; i++) {
            const int col = col0 + i * 8;
            float b0 = bf_lo(nv[2 * i + h]), b1 = bf_hi(nv[2 * i + h]);
            if (which >= 0) {
                b0 = bfr(b0 + supd[which][col - nb * 128]); b1 = bfr(b1 + supd[which][col + 1 - nb * 128]);
            }
            const float t0 = bfr(bf_lo(xv[2 * i + h]) + bfr(acc[4 * i + 2 * h]));
            const float t1 = bfr(bf_hi(xv[2 * i + h]) + bfr(acc[4 * i + 2 * h + 1]));
            *reinterpret_cast<uint32_t*>(out + (size_t)row * DM + col) = packbf(t0 + b0, t1 + b1);
        }
    }
    TL(3, 3);
}

typedef CUresult (*EncodeFn)(CUtensorMap*, CUtensorMapDataType, cuuint32_t, void*, const cuuint64_t*, const cuuint64_t*,
                             const cuuint32_t*, const cuuint32_t*, CUtensorMapInterleave, CUtensorMapSwizzle,
                             CUtensorMapL2promotion, CUtensorMapFloatOOBfill);

void make_map(EncodeFn fn, CUtensorMap* m, const void* ptr, uint64_t cols, uint64_t rows, uint32_t box_rows, uint32_t box_chunks) {
    cuuint64_t dims[3] = {64, rows, cols / 64};
    cuuint64_t strides[2] = {cols * 2, 128};
    cuuint32_t box[3] = {64, box_rows, box_chunks};
    cuuint32_t es[3] = {1, 1, 1};
    fn(m, CU_TENSOR_MAP_DATA_TYPE_BFLOAT16, 3, const_cast<void*>(ptr), dims, strides, box, es, CU_TENSOR_MAP_INTERLEAVE_NONE,
       CU_TENSOR_MAP_SWIZZLE_128B, CU_TENSOR_MAP_L2_PROMOTION_L2_256B, CU_TENSOR_MAP_FLOAT_OOB_FILL_NONE);
}

template <typename... KArgs, typename... Args>
void launch(void (*kern)(KArgs...), int grid, int block, int smem, bool pdl, Args... args) {
    cudaLaunchConfig_t cfg = {};
    cfg.gridDim = dim3(grid); cfg.blockDim = dim3(block); cfg.dynamicSmemBytes = smem; cfg.stream = cudaStreamPerThread;
    cudaLaunchAttribute at[1];
    at[0].id = cudaLaunchAttributeProgrammaticStreamSerialization;
    at[0].val.programmaticStreamSerializationAllowed = 1;
    cfg.attrs = at; cfg.numAttrs = pdl ? 1 : 0;
    cudaLaunchKernelEx(&cfg, kern, KArgs(args)...);
}

}

extern "C" void kernel_launch(void* const* d_in, const int* in_sizes, int n_in, void* d_out, int out_size) {
    const __nv_bfloat16* x = (const __nv_bfloat16*)d_in[0];
    const __nv_bfloat16* wqkv = (const __nv_bfloat16*)d_in[1];
    const __nv_bfloat16* wo = (const __nv_bfloat16*)d_in[2];
    const __nv_bfloat16* wr = (const __nv_bfloat16*)d_in[4];
    const __nv_bfloat16* wgate = (const __nv_bfloat16*)d_in[5];
    const __nv_bfloat16* wup = (const __nv_bfloat16*)d_in[6];
    const __nv_bfloat16* wdown = (const __nv_bfloat16*)d_in[7];
    __nv_bfloat16* out = (__nv_bfloat16*)d_out;

    static EncodeFn enc = nullptr;
    static void* p_xn = nullptr; static void* p_o = nullptr;
    if (!enc) {
        void* fn = nullptr; cudaDriverEntryPointQueryResult qr;
        cudaGetDriverEntryPoint("cuTensorMapEncodeTiled", &fn, cudaEnableDefault, &qr);
        enc = (EncodeFn)fn;
        cudaGetSymbolAddress(&p_xn, g_xn);
        cudaGetSymbolAddress(&p_o, g_o);
        cudaFuncSetAttribute(qkv_kernel, cudaFuncAttributeMaxDynamicSharedMemorySize, K1_SMEM);
        cudaFuncSetAttribute(attn_kernel, cudaFuncAttributeMaxDynamicSharedMemorySize, K2_SMEM);
        cudaFuncSetAttribute(oproj_kernel, cudaFuncAttributeMaxDynamicSharedMemorySize, K3_SMEM);
    }
    CUtensorMap mXn, mWqkv, mO, mWo, mG, mU, mD;
    make_map(enc, &mG, wgate, FF, DM, 16, 7);
    make_map(enc, &mU, wup, FF, DM, 16, 7);
    make_map(enc, &mD, wdown, DM, FF, 32, 8);
    make_map(enc, &mXn, p_xn, DM, S_LEN, 128, 1);
    make_map(enc, &mWqkv, wqkv, 3 * DM, DM, 64, 3);
    make_map(enc, &mO, p_o, DM, S_LEN, 64, 2);
    make_map(enc, &mWo, wo, DM, DM, 256, 2);

    union { uint32_t u; float f; } scu; scu.u = 128u;

    launch(ln_kernel, S_LEN / 8, 256, 0, false, x, wr);
    launch(qkv_kernel, 128, 320, K1_SMEM, true, mXn, mWqkv, (const uint8_t*)wgate, (const uint8_t*)wup, (const uint8_t*)wdown, (const uint8_t*)wo);
    launch(attn_kernel, 132, 512, K2_SMEM, true, mG, mU, mD, scu.f);
    launch(oproj_kernel, 128, 256, K3_SMEM, true, mO, mWo, x, out);
}
```

```cpp
#include <cuda_runtime.h>
#include <cuda_bf16.h>
#include <cuda.h>
#include <stdint.h>
#include <type_traits>

#define COPYMODE 0
#define CTHREAD 0
#define PAT 0xCECC
#define ORDER 0
namespace {

constexpr int S_LEN = 2048;
constexpr int DM = 512;
constexpr int NH = 32;
constexpr int FF = 1792;

__device__ __align__(1024) __nv_bfloat16 g_xn[S_LEN * DM];
__device__ __align__(16) float g_r[S_LEN];
__device__ __align__(1024) uint4 g_q[NH * 128 * 32];
__device__ __align__(1024) uint4 g_k[NH * 4096];
__device__ __align__(1024) uint4 g_v[NH * 4096];
__device__ __align__(1024) __nv_bfloat16 g_o[S_LEN * DM];
__device__ __align__(16) float g_ypart[4 * 2 * DM];
__device__ int g_sel[2];
__device__ float g_gate[2];

#define TL(k, slot) do {} while (0)

__device__ __forceinline__ uint32_t smem_u32(const void* p) { return (uint32_t)__cvta_generic_to_shared(p); }
__device__ __forceinline__ void pdl_wait() { asm volatile("griddepcontrol.wait;" ::: "memory"); }
__device__ __forceinline__ void pdl_launch() { asm volatile("griddepcontrol.launch_dependents;" ::: "memory"); }
__device__ __forceinline__ void mbar_init(uint32_t bar, uint32_t cnt) {
    asm volatile("mbarrier.init.shared::cta.b64 [%0], %1;" :: "r"(bar), "r"(cnt) : "memory");
}
__device__ __forceinline__ void mbar_expect_tx(uint32_t bar, uint32_t bytes) {
    asm volatile("mbarrier.arrive.expect_tx.shared::cta.b64 _, [%0], %1;" :: "r"(bar), "r"(bytes) : "memory");
}
__device__ __forceinline__ void mbar_arrive(uint32_t bar) {
    asm volatile("mbarrier.arrive.shared::cta.b64 _, [%0];" :: "r"(bar) : "memory");
}
__device__ __forceinline__ void mbar_wait(uint32_t bar, uint32_t parity) {
    asm volatile("{\n.reg .pred p;\n.reg .u32 n;\nmov.u32 n, 0;\n"
                 "WAIT_%=:\n"
                 "mbarrier.try_wait.parity.shared::cta.b64 p, [%0], %1;\n"
                 "@p bra DONE_%=;\n"
                 "add.u32 n, n, 1;\n"
                 "setp.lt.u32 p, n, 4000000;\n"
                 "@p bra WAIT_%=;\n"
                 "trap;\n"
                 "DONE_%=:\n}"
                 :: "r"(bar), "r"(parity) : "memory");
}
__device__ __forceinline__ void fence_barrier_init() { asm volatile("fence.mbarrier_init.release.cluster;" ::: "memory"); }
__device__ __forceinline__ void fence_proxy_async() { asm volatile("fence.proxy.async.shared::cta;" ::: "memory"); }
__device__ __forceinline__ void tma3d(uint32_t dst, const CUtensorMap* map, uint32_t bar, int row, int chunk) {
    asm volatile("cp.async.bulk.tensor.3d.shared::cluster.global.mbarrier::complete_tx::bytes [%0], [%1, {%3, %4, %5}], [%2];"
                 :: "r"(dst), "l"((uint64_t)map), "r"(bar), "r"(0), "r"(row), "r"(chunk) : "memory");
}
__device__ __forceinline__ void bulk_g2s(uint32_t dst, const void* src, uint32_t bytes, uint32_t bar) {
    asm volatile("cp.async.bulk.shared::cluster.global.mbarrier::complete_tx::bytes [%0], [%1], %2, [%3];"
                 :: "r"(dst), "l"((uint64_t)src), "r"(bytes), "r"(bar) : "memory");
}
__device__ __forceinline__ void l2_prefetch(const void* src, uint32_t bytes) {
    asm volatile("cp.async.bulk.prefetch.L2.global [%0], %1;" :: "l"((uint64_t)src), "r"(bytes) : "memory");
}
__device__ __forceinline__ void map_prefetch(const CUtensorMap* m) {
    asm volatile("prefetch.tensormap [%0];" :: "l"((uint64_t)m) : "memory");
}
__device__ __forceinline__ uint64_t mkdesc(uint32_t addr, uint32_t lbo, uint32_t sbo, uint32_t swz) {
    return (uint64_t)((addr & 0x3FFFF) >> 4) | ((uint64_t)(lbo >> 4) << 16) | ((uint64_t)(sbo >> 4) << 32) | ((uint64_t)swz << 62);
}
#define WG_FENCE() asm volatile("wgmma.fence.sync.aligned;" ::: "memory")
#define WG_COMMIT() asm volatile("wgmma.commit_group.sync.aligned;" ::: "memory")
#define WG_WAIT(n) asm volatile("wgmma.wait_group.sync.aligned %0;" :: "n"(n) : "memory")

__device__ __forceinline__ float ex2(float x) { float y; asm("ex2.approx.ftz.f32 %0, %1;" : "=f"(y) : "f"(x)); return y; }
__device__ __forceinline__ uint32_t packbf(float lo, float hi) {
    uint32_t r; asm("cvt.rn.bf16x2.f32 %0, %1, %2;" : "=r"(r) : "f"(hi), "f"(lo)); return r;
}
__device__ __forceinline__ float bf_lo(uint32_t v) { return __uint_as_float(v << 16); }
__device__ __forceinline__ float bf_hi(uint32_t v) { return __uint_as_float(v & 0xffff0000u); }
__device__ __forceinline__ float bfr(float x) { return __bfloat162float(__float2bfloat16_rn(x)); }

__global__ void __launch_bounds__(256) ln_kernel(const __nv_bfloat16* __restrict__ x, const __nv_bfloat16* __restrict__ wr) {
    TL(0, 0);
    pdl_launch();
    const int warp = threadIdx.x >> 5, lane = threadIdx.x & 31;
    const int row = blockIdx.x * 8 + warp;
    const uint4* xr = reinterpret_cast<const uint4*>(x + (size_t)row * DM);
    uint4 a = xr[lane], b = xr[32 + lane];
    const uint4* wp = reinterpret_cast<const uint4*>(wr);
    uint4 wa = wp[lane], wb = wp[32 + lane];
    uint32_t u[8] = {a.x, a.y, a.z, a.w, b.x, b.y, b.z, b.w};
    uint32_t w[8] = {wa.x, wa.y, wa.z, wa.w, wb.x, wb.y, wb.z, wb.w};
    float f[16];
    float sum = 0.f;
#pragma unroll
    for (int i = 0; i < 8; i++) { f[2 * i] = bf_lo(u[i]); f[2 * i + 1] = bf_hi(u[i]); sum += f[2 * i] + f[2 * i + 1]; }
#pragma unroll
    for (int o = 16; o > 0; o >>= 1) sum += __shfl_xor_sync(~0u, sum, o);
    const float mean = sum * (1.f / DM);
    float sq = 0.f;
#pragma unroll
    for (int i = 0; i < 16; i++) { float d = f[i] - mean; sq = fmaf(d, d, sq); }
#pragma unroll
    for (int o = 16; o > 0; o >>= 1) sq += __shfl_xor_sync(~0u, sq, o);
    const float mb = bfr(mean);
    const float vb = bfr(sq * (1.f / DM));
    const float den = bfr(sqrtf(bfr(vb + 1e-5f)));
    const float rinv = 1.f / den;
    uint32_t o[8];
    float r = 0.f;
#pragma unroll
    for (int i = 0; i < 8; i++) {
        float d0 = bfr(f[2 * i] - mb), d1 = bfr(f[2 * i + 1] - mb);
        o[i] = packbf(d0 * rinv, d1 * rinv);
        r = fmaf(bf_lo(o[i]), bf_lo(w[i]), r);
        r = fmaf(bf_hi(o[i]), bf_hi(w[i]), r);
    }
#pragma unroll
    for (int of = 16; of > 0; of >>= 1) r += __shfl_xor_sync(~0u, r, of);
    uint4* xo = reinterpret_cast<uint4*>(g_xn + (size_t)row * DM);
    xo[lane] = make_uint4(o[0], o[1], o[2], o[3]);
    xo[32 + lane] = make_uint4(o[4], o[5], o[6], o[7]);
    if (lane == 0) g_r[row] = r;
    TL(0, 3);
}

constexpr int K1_ST = 5;
constexpr int K1_STAGE = 16384 + 24576;
constexpr int K1_SMEM = K1_ST * K1_STAGE + 1024 + 128;

__device__ __forceinline__ void wgmma_n192(float (&d)[96], uint64_t da, uint64_t db, int scale_d) {
    asm volatile("{\n.reg .pred p;\nsetp.ne.b32 p, %98, 0;\n"
        "wgmma.mma_async.sync.aligned.m64n192k16.f32.bf16.bf16 "
        "{%0,%1,%2,%3,%4,%5,%6,%7,%8,%9,%10,%11,%12,%13,%14,%15,%16,%17,%18,%19,%20,%21,%22,%23,"
        "%24,%25,%26,%27,%28,%29,%30,%31,%32,%33,%34,%35,%36,%37,%38,%39,%40,%41,%42,%43,%44,%45,%46,%47,"
        "%48,%49,%50,%51,%52,%53,%54,%55,%56,%57,%58,%59,%60,%61,%62,%63,%64,%65,%66,%67,%68,%69,%70,%71,"
        "%72,%73,%74,%75,%76,%77,%78,%79,%80,%81,%82,%83,%84,%85,%86,%87,%88,%89,%90,%91,%92,%93,%94,%95}, "
        "%96, %97, p, 1, 1, 0, 1;\n}"
        : "+f"(d[0]), "+f"(d[1]), "+f"(d[2]), "+f"(d[3]), "+f"(d[4]), "+f"(d[5]), "+f"(d[6]), "+f"(d[7]),
          "+f"(d[8]), "+f"(d[9]), "+f"(d[10]), "+f"(d[11]), "+f"(d[12]), "+f"(d[13]), "+f"(d[14]), "+f"(d[15]),
          "+f"(d[16]), "+f"(d[17]), "+f"(d[18]), "+f"(d[19]), "+f"(d[20]), "+f"(d[21]), "+f"(d[22]), "+f"(d[23]),
          "+f"(d[24]), "+f"(d[25]), "+f"(d[26]), "+f"(d[27]), "+f"(d[28]), "+f"(d[29]), "+f"(d[30]), "+f"(d[31]),
          "+f"(d[32]), "+f"(d[33]), "+f"(d[34]), "+f"(d[35]), "+f"(d[36]), "+f"(d[37]), "+f"(d[38]), "+f"(d[39]),
          "+f"(d[40]), "+f"(d[41]), "+f"(d[42]), "+f"(d[43]), "+f"(d[44]), "+f"(d[45]), "+f"(d[46]), "+f"(d[47]),
          "+f"(d[48]), "+f"(d[49]), "+f"(d[50]), "+f"(d[51]), "+f"(d[52]), "+f"(d[53]), "+f"(d[54]), "+f"(d[55]),
          "+f"(d[56]), "+f"(d[57]), "+f"(d[58]), "+f"(d[59]), "+f"(d[60]), "+f"(d[61]), "+f"(d[62]), "+f"(d[63]),
          "+f"(d[64]), "+f"(d[65]), "+f"(d[66]), "+f"(d[67]), "+f"(d[68]), "+f"(d[69]), "+f"(d[70]), "+f"(d[71]),
          "+f"(d[72]), "+f"(d[73]), "+f"(d[74]), "+f"(d[75]), "+f"(d[76]), "+f"(d[77]), "+f"(d[78]), "+f"(d[79]),
          "+f"(d[80]), "+f"(d[81]), "+f"(d[82]), "+f"(d[83]), "+f"(d[84]), "+f"(d[85]), "+f"(d[86]), "+f"(d[87]),
          "+f"(d[88]), "+f"(d[89]), "+f"(d[90]), "+f"(d[91]), "+f"(d[92]), "+f"(d[93]), "+f"(d[94]), "+f"(d[95])
        : "l"(da), "l"(db), "r"(scale_d));
}

__global__ void __launch_bounds__(320, 1) qkv_kernel(const __grid_constant__ CUtensorMap mapA, const __grid_constant__ CUtensorMap mapB,
                                                     const uint8_t* __restrict__ pwg, const uint8_t* __restrict__ pwu, const uint8_t* __restrict__ pwd,
                                                     const uint8_t* __restrict__ pwo) {
    extern __shared__ uint8_t smem_raw[];
    const uint32_t sbase = (smem_u32(smem_raw) + 1023u) & ~1023u;
    const uint32_t bars = sbase + K1_ST * K1_STAGE;
    const int warp = threadIdx.x >> 5, lane = threadIdx.x & 31;
    const int nb = blockIdx.x & 7, mb = blockIdx.x >> 3;
    TL(1, 0);
    if (threadIdx.x == 0) {
        for (int s = 0; s < K1_ST; s++) { mbar_init(bars + 8 * s, 2); mbar_init(bars + 8 * (K1_ST + s), 2); }
        fence_barrier_init();
    }
    __syncthreads();
    if (warp == 8) {
        if (lane == 0) {
            for (int c = 0; c < 8; c++) {
                const int s = c < K1_ST ? c : c - K1_ST;
                if (c >= K1_ST) mbar_wait(bars + 8 * (K1_ST + s), 0);
                mbar_expect_tx(bars + 8 * s, 24576);
                tma3d(sbase + s * K1_STAGE + 16384, &mapB, bars + 8 * s, c * 64, nb * 3);
            }
        }
        return;
    }
    if (warp == 9) {
        if (lane == 0) {
            map_prefetch(&mapA);
            pdl_wait();
            pdl_launch();
            for (int c = 0; c < 8; c++) {
                const int s = c < K1_ST ? c : c - K1_ST;
                if (c == K1_ST) {
                    l2_prefetch(pwg + blockIdx.x * 14336, 14336);
                    l2_prefetch(pwu + blockIdx.x * 14336, 14336);
                    l2_prefetch(pwd + blockIdx.x * 14336, 14336);
                    l2_prefetch(pwo + blockIdx.x * 4096, 4096);
                }
                if (c >= K1_ST) mbar_wait(bars + 8 * (K1_ST + s), 0);
                mbar_expect_tx(bars + 8 * s, 16384);
                tma3d(sbase + s * K1_STAGE, &mapA, bars + 8 * s, mb * 128, c);
            }
        }
        return;
    }
    const int wg = warp >> 2;
    float acc[96];
#pragma unroll
    for (int i = 0; i < 96; i++) acc[i] = 0.f;
#pragma unroll 1
    for (int c = 0; c < 8; c++) {
        const int s = c < K1_ST ? c : c - K1_ST;
        const uint32_t st = sbase + s * K1_STAGE;
        mbar_wait(bars + 8 * s, c < K1_ST ? 0 : 1);
        if (c == 0) TL(1, 1);
        const uint64_t da = mkdesc(st + wg * 8192, 16, 1024, 1);
        const uint64_t db = mkdesc(st + 16384, 8192, 1024, 1);
        WG_FENCE();
#pragma unroll
        for (int k = 0; k < 4; k++) wgmma_n192(acc, da + k * 2, db + k * 128, (c | k) != 0);
        WG_COMMIT();
        if (c + K1_ST < 8 + 1) {
            WG_WAIT(1);
            if (c >= 1 && (threadIdx.x & 127) == 0) mbar_arrive(bars + 8 * (K1_ST + c - 1));
        }
    }
    WG_WAIT(0);
    TL(1, 2);
    const int g = lane >> 2, t = lane & 3;
    const int mt = mb * 8 + warp;
#pragma unroll
    for (int hh = 0; hh < 12; hh++) {
        const int gh = nb * 12 + hh;
        const float* a = &acc[hh * 8];
        if (gh < 32) {
            uint4 v;
            v.x = packbf(a[0], a[1]); v.y = packbf(a[2], a[3]);
            v.z = packbf(a[4], a[5]); v.w = packbf(a[6], a[7]);
            g_q[(gh * 128 + mt) * 32 + lane] = v;
        } else {
            uint32_t* dst = reinterpret_cast<uint32_t*>(gh < 64 ? g_k + (gh - 32) * 4096 : g_v + (gh - 64) * 4096);
            const float ks = gh < 64 ? 5.421010862427522e-20f : 1.0f;
            const int off = (mt * 16 + g) * 4 + t;
            dst[off] = packbf(a[0] * ks, a[1] * ks);
            dst[off + 32] = packbf(a[2] * ks, a[3] * ks);
            dst[8192 + off] = packbf(a[4] * ks, a[5] * ks);
            dst[8192 + off + 32] = packbf(a[6] * ks, a[7] * ks);
        }
    }
    TL(1, 3);
}

constexpr float SHIFT = 90.0f;
constexpr float QS = 0.25f * 1.4426950408889634f * 18446744073709551616.0f;
constexpr float scq = 0.25f * 1.4426950408889634f * 3.3087224502121107e-24f;
constexpr int K2_SMEM = 163840 + 1024 + 128;

__device__ __forceinline__ uint32_t polyexp(float lo, float hi) {
    uint32_t w, g, q, h;
    asm("cvt.pack.sat.s16.s32 %0, %1, %2;" : "=r"(w) : "r"(__float_as_uint(hi)), "r"(__float_as_uint(lo)));
    g = w & 0x007F007Fu;
    asm("fma.rn.f16x2 %0, %1, %2, %3;" : "=r"(q) : "r"(g), "r"(0xf940f940u), "r"(0x35513551u));
    asm("mul.rn.f16x2 %0, %1, %2;" : "=r"(h) : "r"(q), "r"(g));
    return w - h;
}
__device__ __forceinline__ void qk64(float (&s)[32], const uint32_t (&q)[4], uint64_t db) {
    asm volatile("wgmma.mma_async.sync.aligned.m64n64k16.f32.bf16.bf16 "
        "{%0,%1,%2,%3,%4,%5,%6,%7,%8,%9,%10,%11,%12,%13,%14,%15,%16,%17,%18,%19,%20,%21,%22,%23,%24,%25,%26,%27,%28,%29,%30,%31}, "
        "{%32,%33,%34,%35}, %36, 0, 1, 1, 0;"
        : "=f"(s[0]), "=f"(s[1]), "=f"(s[2]), "=f"(s[3]), "=f"(s[4]), "=f"(s[5]), "=f"(s[6]), "=f"(s[7]),
          "=f"(s[8]), "=f"(s[9]), "=f"(s[10]), "=f"(s[11]), "=f"(s[12]), "=f"(s[13]), "=f"(s[14]), "=f"(s[15]),
          "=f"(s[16]), "=f"(s[17]), "=f"(s[18]), "=f"(s[19]), "=f"(s[20]), "=f"(s[21]), "=f"(s[22]), "=f"(s[23]),
          "=f"(s[24]), "=f"(s[25]), "=f"(s[26]), "=f"(s[27]), "=f"(s[28]), "=f"(s[29]), "=f"(s[30]), "=f"(s[31])
        : "r"(q[0]), "r"(q[1]), "r"(q[2]), "r"(q[3]), "l"(db));
}
__device__ __forceinline__ void pv24(float (&o)[12], uint32_t a0, uint32_t a1, uint32_t a2, uint32_t a3, uint64_t db) {
    asm volatile("wgmma.mma_async.sync.aligned.m64n24k16.f32.bf16.bf16 "
        "{%0,%1,%2,%3,%4,%5,%6,%7,%8,%9,%10,%11}, {%12,%13,%14,%15}, %16, 1, 1, 1, 1;"
        : "+f"(o[0]), "+f"(o[1]), "+f"(o[2]), "+f"(o[3]), "+f"(o[4]), "+f"(o[5]), "+f"(o[6]), "+f"(o[7]),
          "+f"(o[8]), "+f"(o[9]), "+f"(o[10]), "+f"(o[11])
        : "r"(a0), "r"(a1), "r"(a2), "r"(a3), "l"(db));
}

__device__ __forceinline__ void attn_safe(float (&o)[12], const uint32_t (&q)[4], uint64_t kdesc0, uint64_t vdesc0) {
    float s[32];
    float m0 = -INFINITY, m1 = -INFINITY;
#pragma unroll
    for (int i = 0; i < 12; i++) o[i] = 0.f;
#pragma unroll 1
    for (int j = 0; j < 32; j++) {
        WG_FENCE();
        qk64(s, q, kdesc0 + (uint64_t)(j * 64));
        WG_COMMIT(); WG_WAIT(0);
        float n0 = m0, n1 = m1;
#pragma unroll
        for (int i = 0; i < 8; i++) { n0 = fmaxf(n0, fmaxf(s[4 * i], s[4 * i + 1])); n1 = fmaxf(n1, fmaxf(s[4 * i + 2], s[4 * i + 3])); }
        n0 = fmaxf(n0, __shfl_xor_sync(~0u, n0, 1)); n0 = fmaxf(n0, __shfl_xor_sync(~0u, n0, 2));
        n1 = fmaxf(n1, __shfl_xor_sync(~0u, n1, 1)); n1 = fmaxf(n1, __shfl_xor_sync(~0u, n1, 2));
        const float c0 = ex2((m0 - n0) * QS), c1 = ex2((m1 - n1) * QS);
        m0 = n0; m1 = n1;
#pragma unroll
        for (int i = 0; i < 3; i++) { o[4 * i] *= c0; o[4 * i + 1] *= c0; o[4 * i + 2] *= c1; o[4 * i + 3] *= c1; }
        uint32_t p[16];
#pragma unroll
        for (int i = 0; i < 8; i++) {
            p[2 * i] = packbf(ex2((s[4 * i] - m0) * QS), ex2((s[4 * i + 1] - m0) * QS));
            p[2 * i + 1] = packbf(ex2((s[4 * i + 2] - m1) * QS), ex2((s[4 * i + 3] - m1) * QS));
        }
        WG_FENCE();
#pragma unroll
        for (int kk = 0; kk < 4; kk++) pv24(o, p[4 * kk], p[4 * kk + 1], p[4 * kk + 2], p[4 * kk + 3], vdesc0 + (uint64_t)(j * 64 + kk * 16));
        WG_COMMIT(); WG_WAIT(0);
    }
}

__device__ __forceinline__ void attn_store(const float (&o)[12], int head, int m64, int warp, int lane) {
    const int g = lane >> 2, t = lane & 3;
    const int row = m64 * 64 + warp * 16 + g;
    const float i0 = 1.f / o[8], i1 = 1.f / o[10];
    uint32_t* p0 = reinterpret_cast<uint32_t*>(g_o + (size_t)row * DM + head * 16 + t * 2);
    uint32_t* p1 = reinterpret_cast<uint32_t*>(g_o + (size_t)(row + 8) * DM + head * 16 + t * 2);
    p0[0] = packbf(o[0] * i0, o[1] * i0); p0[4] = packbf(o[4] * i0, o[5] * i0);
    p1[0] = packbf(o[2] * i1, o[3] * i1); p1[4] = packbf(o[6] * i1, o[7] * i1);
}

constexpr int FS_N = 4;
constexpr int FS_BYTES = 32768;
__device__ __forceinline__ void ldsm4t(uint32_t& r0, uint32_t& r1, uint32_t& r2, uint32_t& r3, uint32_t addr) {
    asm volatile("ldmatrix.sync.aligned.m8n8.x4.trans.shared.b16 {%0,%1,%2,%3}, [%4];" : "=r"(r0), "=r"(r1), "=r"(r2), "=r"(r3) : "r"(addr) : "memory");
}
__device__ __forceinline__ void mma16816(float (&d)[4], uint32_t a0, uint32_t a2, uint32_t b0, uint32_t b1) {
    asm volatile("mma.sync.aligned.m16n8k16.row.col.f32.bf16.bf16.f32 {%0,%1,%2,%3}, {%4,%5,%6,%5}, {%7,%8}, {%0,%1,%2,%3};"
                 : "+f"(d[0]), "+f"(d[1]), "+f"(d[2]), "+f"(d[3]) : "r"(a0), "r"(0u), "r"(a2), "r"(b0), "r"(b1));
}
__device__ void ffn_block(int c, uint8_t* smem, uint32_t sbase, const CUtensorMap* mapG, const CUtensorMap* mapU, const CUtensorMap* mapD) {
    const int tid = threadIdx.x, warp = tid >> 5, lane = tid & 31;
    uint32_t* sx = reinterpret_cast<uint32_t*>(smem + FS_N * FS_BYTES);
    __nv_bfloat16* sh = reinterpret_cast<__nv_bfloat16*>(sx + 512);
    const uint32_t bars = sbase + FS_N * FS_BYTES + 8192;
    __shared__ float tv[32]; __shared__ int ti[32];
    __shared__ int ssel[2];
    auto issue = [&](int item) {
        const int slot = item % FS_N;
        const uint32_t dst = sbase + slot * FS_BYTES, bar = bars + 8 * slot;
        mbar_expect_tx(bar, item < 32 ? 28672 : 32768);
        if (item < 32) {
            tma3d(dst, mapG, bar, item * 16, c * 7);
            tma3d(dst + 14336, mapU, bar, item * 16, c * 7);
        } else {
            tma3d(dst, mapD, bar, c * 448 + (item - 32) * 32, 0);
        }
    };
    if (tid == 0) {
        for (int i = 0; i < FS_N; i++) mbar_init(bars + 8 * i, 1);
        fence_barrier_init();
        for (int i = 0; i < FS_N; i++) issue(i);
    }
    float b1 = -INFINITY, b2 = -INFINITY; int i1 = 0x7fffffff, i2 = 0x7fffffff;
    auto push = [&](float v, int i) {
        if (v > b1 || (v == b1 && i < i1)) { b2 = b1; i2 = i1; b1 = v; i1 = i; }
        else if (v > b2 || (v == b2 && i < i2)) { b2 = v; i2 = i; }
    };
    {
        const float4 rv = reinterpret_cast<const float4*>(g_r)[tid];
        push(rv.x, 4 * tid); push(rv.y, 4 * tid + 1); push(rv.z, 4 * tid + 2); push(rv.w, 4 * tid + 3);
    }
#pragma unroll
    for (int o = 16; o > 0; o >>= 1) {
        float v1 = __shfl_xor_sync(~0u, b1, o), v2 = __shfl_xor_sync(~0u, b2, o);
        int j1 = __shfl_xor_sync(~0u, i1, o), j2 = __shfl_xor_sync(~0u, i2, o);
        push(v1, j1); push(v2, j2);
    }
    if (lane == 0) { tv[2 * warp] = b1; ti[2 * warp] = i1; tv[2 * warp + 1] = b2; ti[2 * warp + 1] = i2; }
    __syncthreads();
    if (warp == 1) {
        b1 = tv[lane]; i1 = ti[lane]; b2 = -INFINITY; i2 = 0x7fffffff;
#pragma unroll
        for (int o = 16; o > 0; o >>= 1) {
            float v1 = __shfl_xor_sync(~0u, b1, o), v2 = __shfl_xor_sync(~0u, b2, o);
            int j1 = __shfl_xor_sync(~0u, i1, o), j2 = __shfl_xor_sync(~0u, i2, o);
            push(v1, j1); push(v2, j2);
        }
        if (lane == 0) {
            i1 = min(max(i1, 0), S_LEN - 1); i2 = min(max(i2, 0), S_LEN - 1);
            ssel[0] = i1; ssel[1] = i2;
            if (c == 0) {
                g_sel[0] = i1; g_sel[1] = i2;
                g_gate[0] = bfr(1.f / (1.f + __expf(-bfr(b1))));
                g_gate[1] = bfr(1.f / (1.f + __expf(-bfr(b2))));
            }
        }
    }
    __syncthreads();
    sx[tid] = *reinterpret_cast<const uint32_t*>(g_xn + (size_t)ssel[tid >> 8] * DM + (tid & 255) * 2);
    __syncthreads();
    TL(2, 1);
    const int g = lane >> 2, t = lane & 3;
    const int lrow = lane & 15, lsel = lane >> 4;
    {
        float ag[4][4], au[4][4];
#pragma unroll
        for (int j = 0; j < 4; j++) { ag[j][0] = ag[j][1] = ag[j][2] = ag[j][3] = 0.f; au[j][0] = au[j][1] = au[j][2] = au[j][3] = 0.f; }
#pragma unroll 1
        for (int it = 0; it < 32; it++) {
            const int slot = it % FS_N;
            const uint32_t a0 = g < 2 ? sx[g * 256 + it * 8 + t] : 0u, a2 = g < 2 ? sx[g * 256 + it * 8 + 4 + t] : 0u;
            mbar_wait(bars + 8 * slot, (it / FS_N) & 1);
            const uint32_t base = sbase + slot * FS_BYTES + lsel * 14336 + lrow * 128;
#pragma unroll
            for (int j = 0; j < 4; j++) {
                const int nt = warp + j * 16;
                if (nt < 56) {
                    uint32_t b0, b1, b2, b3;
                    ldsm4t(b0, b1, b2, b3, base + (nt >> 3) * 2048 + (((nt & 7) ^ (lrow & 7)) << 4));
                    mma16816(ag[j], a0, a2, b0, b1);
                    mma16816(au[j], a0, a2, b2, b3);
                }
            }
            __syncthreads();
            if (tid == 480) issue(it + FS_N);
        }
        if (g < 2) {
#pragma unroll
            for (int j = 0; j < 4; j++) {
                const int nt = warp + j * 16;
                if (nt < 56) {
#pragma unroll
                    for (int e = 0; e < 2; e++) {
                        const float gs = bfr(ag[j][e]), us = bfr(au[j][e]);
                        const float sg = bfr(gs / (1.f + __expf(-gs)));
                        sh[g * 448 + nt * 8 + t * 2 + e] = __float2bfloat16_rn(sg * us);
                    }
                }
            }
        }
        __syncthreads();
    }
    TL(2, 2);
    {
        const uint32_t* shw = reinterpret_cast<const uint32_t*>(sh);
        float a[4][4];
#pragma unroll
        for (int j = 0; j < 4; j++) a[j][0] = a[j][1] = a[j][2] = a[j][3] = 0.f;
#pragma unroll 1
        for (int it = 32; it < 46; it++) {
            const int slot = it % FS_N;
            uint32_t af[4];
#pragma unroll
            for (int q = 0; q < 4; q++) af[q] = g < 2 ? shw[g * 224 + (it - 32) * 16 + q * 4 + t] : 0u;
            mbar_wait(bars + 8 * slot, (it / FS_N) & 1);
            const uint32_t base = sbase + slot * FS_BYTES + (warp >> 1) * 4096 + lane * 128;
#pragma unroll
            for (int j = 0; j < 4; j++) {
                const int u = (warp & 1) * 4 + j;
                uint32_t b0, b1, b2, b3;
                ldsm4t(b0, b1, b2, b3, base + ((u ^ (lane & 7)) << 4));
                mma16816(a[j], af[0], af[1], b0, b1);
                mma16816(a[j], af[2], af[3], b2, b3);
            }
            __syncthreads();
            if (tid == 480 && it + FS_N < 46) issue(it + FS_N);
        }
        if (g < 2) {
#pragma unroll
            for (int j = 0; j < 4; j++)
                *reinterpret_cast<float2*>(&g_ypart[c * 1024 + g * 512 + (warp * 4 + j) * 8 + t * 2]) = make_float2(a[j][0], a[j][1]);
        }
    }
}

__global__ void __launch_bounds__(512, 1) attn_kernel(const __grid_constant__ CUtensorMap mapG, const __grid_constant__ CUtensorMap mapU,
                                                      const __grid_constant__ CUtensorMap mapD, float sc) {
    extern __shared__ uint8_t smem_raw[];
    const uint32_t sraw = smem_u32(smem_raw);
    const uint32_t sbase = (sraw + 1023u) & ~1023u;
    uint8_t* sptr = smem_raw + (sbase - sraw);
    TL(2, 0);
    if (blockIdx.x < 4) {
        pdl_launch();
        ffn_block(blockIdx.x, sptr, sbase, &mapG, &mapU, &mapD);
        TL(2, 3);
        return;
    }
    const uint32_t bars = sbase + 163840;
    const int head = (blockIdx.x - 4) >> 2, quarter = blockIdx.x & 3;
    const int wg = threadIdx.x >> 7, warp = (threadIdx.x >> 5) & 3, lane = threadIdx.x & 31;
    if (threadIdx.x == 0) {
        for (int c = 0; c < 8; c++) mbar_init(bars + 8 * c, 1);
        fence_barrier_init();
        for (int c = 0; c < 8; c++) mbar_expect_tx(bars + 8 * c, 16384);
    }
    {
        uint4* ones = reinterpret_cast<uint4*>(sptr + 131072);
        for (int i = threadIdx.x; i < 2048; i += 512) ones[i] = make_uint4(0x3f803f80u, 0x3f803f80u, 0x3f803f80u, 0x3f803f80u);
        fence_proxy_async();
    }
    __syncthreads();
    pdl_wait();
    pdl_launch();
    TL(2, 1);
    if (threadIdx.x == CTHREAD) {
        const uint8_t* kp = reinterpret_cast<const uint8_t*>(g_k + head * 4096);
        const uint8_t* vp = reinterpret_cast<const uint8_t*>(g_v + head * 4096);
        for (int c = 0; c < 8; c++) {
            bulk_g2s(sbase + c * 4096, kp + c * 4096, 4096, bars + 8 * c);
            bulk_g2s(sbase + 32768 + c * 4096, kp + 32768 + c * 4096, 4096, bars + 8 * c);
            bulk_g2s(sbase + 65536 + c * 4096, vp + c * 4096, 4096, bars + 8 * c);
            bulk_g2s(sbase + 98304 + c * 4096, vp + 32768 + c * 4096, 4096, bars + 8 * c);
        }
    }
    const uint64_t kdesc0 = mkdesc(sbase, 32768, 128, 0);
    const uint64_t vdesc0 = mkdesc(sbase + 65536, 128, 32768, 0);
    uint32_t badmask = 0;
    uint32_t q[4];
    { const uint4 qq = g_q[(head * 128 + (quarter * 8 + wg) * 4 + warp) * 32 + lane]; q[0] = qq.x; q[1] = qq.y; q[2] = qq.z; q[3] = qq.w; }
#pragma unroll 1
    for (int mt = 0; mt < 2; mt++) {
        const int m64 = quarter * 8 + mt * 4 + wg;
        float s[32], s2[32], o[12];
#pragma unroll
        for (int i = 0; i < 12; i++) o[i] = 0.f;
        mbar_wait(bars, 0);
        if (mt == 0) TL(2, 2);
        WG_FENCE();
        qk64(s, q, kdesc0);
        WG_COMMIT(); WG_WAIT(0);
        float mx0 = -INFINITY, mx1 = -INFINITY;
#pragma unroll
        for (int i = 0; i < 8; i++) { mx0 = fmaxf(mx0, fmaxf(s[4 * i], s[4 * i + 1])); mx1 = fmaxf(mx1, fmaxf(s[4 * i + 2], s[4 * i + 3])); }
        mx0 = fmaxf(mx0, __shfl_xor_sync(~0u, mx0, 1)); mx0 = fmaxf(mx0, __shfl_xor_sync(~0u, mx0, 2));
        mx1 = fmaxf(mx1, __shfl_xor_sync(~0u, mx1, 1)); mx1 = fmaxf(mx1, __shfl_xor_sync(~0u, mx1, 2));
        float cm0 = -(ceilf(mx0 * QS) + SHIFT), cm1 = -(ceilf(mx1 * QS) + SHIFT);
        float cp0 = (cm0 + 127.f) * sc, cp1 = (cm1 + 127.f) * sc;
        asm volatile("" : "+f"(cm0), "+f"(cm1), "+f"(cp0), "+f"(cp1));
        uint64_t kd = kdesc0, vd = vdesc0;
        auto step = [&](float (&sc_)[32], float (&sn)[32]) {
            kd += 64;
            WG_FENCE();
            qk64(sn, q, kd);
            WG_COMMIT();
#pragma unroll
            for (int kk = 0; kk < 4; kk++) {
                uint32_t p[4];
#pragma unroll
                for (int ee = 0; ee < 4; ee++) {
                    const int e = ORDER == 0 ? ee : (ORDER == 1 ? 3 - ee : (ee ^ (ee >> 1)));
                    const int r = kk * 8 + e * 2;
                    const float cmx = (e & 1) ? cm1 : cm0, cpx = (e & 1) ? cp1 : cp0;
                    if ((PAT >> (kk * 4 + e)) & 1) p[e] = polyexp(fmaf(sc_[r], scq, cpx), fmaf(sc_[r + 1], scq, cpx));
                    else p[e] = packbf(ex2(fmaf(sc_[r], QS, cmx)), ex2(fmaf(sc_[r + 1], QS, cmx)));
                }
                WG_FENCE();
                pv24(o, p[0], p[1], p[2], p[3], vd);
                vd += 16;
            }
            WG_COMMIT();
            WG_WAIT(1);
        };
#pragma unroll 1
        for (int c = 0; c < 16; c++) {
            if (mt == 0 && (c & 1) == 0 && c < 14) mbar_wait(bars + 4 * c + 8, 0);
            step(s, s2); step(s2, s);
        }
        WG_WAIT(0);
        {
            const uint4 qq = g_q[(head * 128 + (quarter * 8 + 4 + wg) * 4 + warp) * 32 + lane]; q[0] = qq.x; q[1] = qq.y; q[2] = qq.z; q[3] = qq.w;
        }
        bool bad = !(o[8] > 0.f) || !(o[10] > 0.f);
#pragma unroll
        for (int i = 0; i < 12; i++) bad = bad || !(fabsf(o[i]) <= 3.0e38f);
        uint32_t anybad;
        asm volatile("{\n.reg .pred p, q;\nsetp.ne.u32 p, %1, 0;\nbarrier.cta.red.or.pred q, %2, 128, p;\nselp.u32 %0, 1, 0, q;\n}"
                     : "=r"(anybad) : "r"((uint32_t)bad), "r"(wg + 1) : "memory");
        badmask |= anybad << mt;
        attn_store(o, head, m64, warp, lane);
    }
#pragma unroll 1
    for (int mt = 0; mt < 2; mt++) {
        if (!((badmask >> mt) & 1)) continue;
        const int m64 = quarter * 8 + mt * 4 + wg;
        { const uint4 qq = g_q[(head * 128 + m64 * 4 + warp) * 32 + lane]; q[0] = qq.x; q[1] = qq.y; q[2] = qq.z; q[3] = qq.w; }
        float o[12];
        attn_safe(o, q, mkdesc(sbase, 32768, 128, 0), mkdesc(sbase + 65536, 128, 32768, 0));
        attn_store(o, head, m64, warp, lane);
    }
    TL(2, 3);
}

constexpr int K3_SMEM = 8 * 8192 + 8 * 16384 + 1024 + 128;

__device__ __forceinline__ void wgmma_n64(float (&d)[32], uint64_t da, uint64_t db, int scale_d) {
    asm volatile("{\n.reg .pred p;\nsetp.ne.b32 p, %34, 0;\n"
        "wgmma.mma_async.sync.aligned.m64n64k16.f32.bf16.bf16 "
        "{%0,%1,%2,%3,%4,%5,%6,%7,%8,%9,%10,%11,%12,%13,%14,%15,%16,%17,%18,%19,%20,%21,%22,%23,%24,%25,%26,%27,%28,%29,%30,%31}, "
        "%32, %33, p, 1, 1, 0, 1;\n}"
        : "+f"(d[0]), "+f"(d[1]), "+f"(d[2]), "+f"(d[3]), "+f"(d[4]), "+f"(d[5]), "+f"(d[6]), "+f"(d[7]),
          "+f"(d[8]), "+f"(d[9]), "+f"(d[10]), "+f"(d[11]), "+f"(d[12]), "+f"(d[13]), "+f"(d[14]), "+f"(d[15]),
          "+f"(d[16]), "+f"(d[17]), "+f"(d[18]), "+f"(d[19]), "+f"(d[20]), "+f"(d[21]), "+f"(d[22]), "+f"(d[23]),
          "+f"(d[24]), "+f"(d[25]), "+f"(d[26]), "+f"(d[27]), "+f"(d[28]), "+f"(d[29]), "+f"(d[30]), "+f"(d[31])
        : "l"(da), "l"(db), "r"(scale_d));
}

__global__ void __launch_bounds__(256, 1) oproj_kernel(const __grid_constant__ CUtensorMap mapA, const __grid_constant__ CUtensorMap mapB,
                                                       const __nv_bfloat16* __restrict__ x, __nv_bfloat16* __restrict__ out) {
    extern __shared__ uint8_t smem_raw[];
    const uint32_t sbase = (smem_u32(smem_raw) + 1023u) & ~1023u;
    const uint32_t sA = sbase, sB = sbase + 8 * 8192, bars = sbase + 8 * 8192 + 8 * 16384;
    const int warp = threadIdx.x >> 5, lane = threadIdx.x & 31, wg = warp >> 2;
    const int nb = blockIdx.x & 3, mb = blockIdx.x >> 2;
    TL(3, 0);
    if (threadIdx.x == 0) {
        for (int c = 0; c < 8; c++) mbar_init(bars + 8 * c, 1);
        fence_barrier_init();
        map_prefetch(&mapA);
        for (int h = 0; h < 2; h++) {
            mbar_expect_tx(bars + 8 * (4 + h), 65536);
            tma3d(sB + h * 65536, &mapB, bars + 8 * (4 + h), h * 256, nb * 2);
        }
    }
    const int g = lane >> 2, t = lane & 3;
    const int row0 = mb * 64 + (warp & 3) * 16 + g;
    const int col0 = nb * 128 + wg * 64 + t * 2;
    uint32_t xv[16], nv[16];
#pragma unroll
    for (int i = 0; i < 8; i++) {
        xv[2 * i] = *reinterpret_cast<const uint32_t*>(x + (size_t)row0 * DM + col0 + i * 8);
        xv[2 * i + 1] = *reinterpret_cast<const uint32_t*>(x + (size_t)(row0 + 8) * DM + col0 + i * 8);
        nv[2 * i] = *reinterpret_cast<const uint32_t*>(g_xn + (size_t)row0 * DM + col0 + i * 8);
        nv[2 * i + 1] = *reinterpret_cast<const uint32_t*>(g_xn + (size_t)(row0 + 8) * DM + col0 + i * 8);
    }
    __syncthreads();
    pdl_wait();
    TL(3, 1);
    if (threadIdx.x == 0) {
        for (int c = 0; c < 4; c++) {
            mbar_expect_tx(bars + 8 * c, 16384);
            tma3d(sA + c * 16384, &mapA, bars + 8 * c, mb * 64, c * 2);
        }
    }
    __shared__ float supd[2][128];
    const int sel0 = g_sel[0], sel1 = g_sel[1];
    {
        const int which = threadIdx.x >> 7, col = nb * 128 + (threadIdx.x & 127);
        const float y = g_ypart[which * 512 + col] + g_ypart[1024 + which * 512 + col] + g_ypart[2048 + which * 512 + col] + g_ypart[3072 + which * 512 + col];
        supd[which][threadIdx.x & 127] = bfr(bfr(y) * g_gate[which]);
    }
    __syncthreads();
    float acc[32];
#pragma unroll
    for (int i = 0; i < 32; i++) acc[i] = 0.f;
#pragma unroll 1
    for (int c = 0; c < 8; c++) {
        if ((c & 3) == 0) mbar_wait(bars + 8 * (4 + (c >> 2)), 0);
        if ((c & 1) == 0) mbar_wait(bars + 8 * (c >> 1), 0);
        const uint64_t da = mkdesc(sA + c * 8192, 16, 1024, 1);
        const uint64_t db = mkdesc(sB + (c >> 2) * 65536 + wg * 32768 + (c & 3) * 8192, 8192, 1024, 1);
        WG_FENCE();
#pragma unroll
        for (int k = 0; k < 4; k++) wgmma_n64(acc, da + k * 2, db + k * 128, (c | k) != 0);
        WG_COMMIT();
    }
    WG_WAIT(0);
    TL(3, 2);
#pragma unroll
    for (int h = 0; h < 2; h++) {
        const int row = row0 + h * 8;
        const int which = row == sel0 ? 0 : (row == sel1 ? 1 : -1);
#pragma unroll
        for (int i = 0; i < 8; i++) {
            const int col = col0 + i * 8;
            float b0 = bf_lo(nv[2 * i + h]), b1 = bf_hi(nv[2 * i + h]);
            if (which >= 0) {
                b0 = bfr(b0 + supd[which][col - nb * 128]); b1 = bfr(b1 + supd[which][col + 1 - nb * 128]);
            }
            const float t0 = bfr(bf_lo(xv[2 * i + h]) + bfr(acc[4 * i + 2 * h]));
            const float t1 = bfr(bf_hi(xv[2 * i + h]) + bfr(acc[4 * i + 2 * h + 1]));
            *reinterpret_cast<uint32_t*>(out + (size_t)row * DM + col) = packbf(t0 + b0, t1 + b1);
        }
    }
    TL(3, 3);
}

typedef CUresult (*EncodeFn)(CUtensorMap*, CUtensorMapDataType, cuuint32_t, void*, const cuuint64_t*, const cuuint64_t*,
                             const cuuint32_t*, const cuuint32_t*, CUtensorMapInterleave, CUtensorMapSwizzle,
                             CUtensorMapL2promotion, CUtensorMapFloatOOBfill);

void make_map(EncodeFn fn, CUtensorMap* m, const void* ptr, uint64_t cols, uint64_t rows, uint32_t box_rows, uint32_t box_chunks) {
    cuuint64_t dims[3] = {64, rows, cols / 64};
    cuuint64_t strides[2] = {cols * 2, 128};
    cuuint32_t box[3] = {64, box_rows, box_chunks};
    cuuint32_t es[3] = {1, 1, 1};
    fn(m, CU_TENSOR_MAP_DATA_TYPE_BFLOAT16, 3, const_cast<void*>(ptr), dims, strides, box, es, CU_TENSOR_MAP_INTERLEAVE_NONE,
       CU_TENSOR_MAP_SWIZZLE_128B, CU_TENSOR_MAP_L2_PROMOTION_L2_256B, CU_TENSOR_MAP_FLOAT_OOB_FILL_NONE);
}

template <typename... KArgs, typename... Args>
void launch(void (*kern)(KArgs...), int grid, int block, int smem, bool pdl, Args... args) {
    cudaLaunchConfig_t cfg = {};
    cfg.gridDim = dim3(grid); cfg.blockDim = dim3(block); cfg.dynamicSmemBytes = smem; cfg.stream = cudaStreamPerThread;
    cudaLaunchAttribute at[1];
    at[0].id = cudaLaunchAttributeProgrammaticStreamSerialization;
    at[0].val.programmaticStreamSerializationAllowed = 1;
    cfg.attrs = at; cfg.numAttrs = pdl ? 1 : 0;
    cudaLaunchKernelEx(&cfg, kern, KArgs(args)...);
}

}

extern "C" void kernel_launch(void* const* d_in, const int* in_sizes, int n_in, void* d_out, int out_size) {
    const __nv_bfloat16* x = (const __nv_bfloat16*)d_in[0];
    const __nv_bfloat16* wqkv = (const __nv_bfloat16*)d_in[1];
    const __nv_bfloat16* wo = (const __nv_bfloat16*)d_in[2];
    const __nv_bfloat16* wr = (const __nv_bfloat16*)d_in[4];
    const __nv_bfloat16* wgate = (const __nv_bfloat16*)d_in[5];
    const __nv_bfloat16* wup = (const __nv_bfloat16*)d_in[6];
    const __nv_bfloat16* wdown = (const __nv_bfloat16*)d_in[7];
    __nv_bfloat16* out = (__nv_bfloat16*)d_out;

    static EncodeFn enc = nullptr;
    static void* p_xn = nullptr; static void* p_o = nullptr;
    if (!enc) {
        void* fn = nullptr; cudaDriverEntryPointQueryResult qr;
        cudaGetDriverEntryPoint("cuTensorMapEncodeTiled", &fn, cudaEnableDefault, &qr);
        enc = (EncodeFn)fn;
        cudaGetSymbolAddress(&p_xn, g_xn);
        cudaGetSymbolAddress(&p_o, g_o);
        cudaFuncSetAttribute(qkv_kernel, cudaFuncAttributeMaxDynamicSharedMemorySize, K1_SMEM);
        cudaFuncSetAttribute(attn_kernel, cudaFuncAttributeMaxDynamicSharedMemorySize, K2_SMEM);
        cudaFuncSetAttribute(oproj_kernel, cudaFuncAttributeMaxDynamicSharedMemorySize, K3_SMEM);
    }
    CUtensorMap mXn, mWqkv, mO, mWo, mG, mU, mD;
    make_map(enc, &mG, wgate, FF, DM, 16, 7);
    make_map(enc, &mU, wup, FF, DM, 16, 7);
    make_map(enc, &mD, wdown, DM, FF, 32, 8);
    make_map(enc, &mXn, p_xn, DM, S_LEN, 128, 1);
    make_map(enc, &mWqkv, wqkv, 3 * DM, DM, 64, 3);
    make_map(enc, &mO, p_o, DM, S_LEN, 64, 2);
    make_map(enc, &mWo, wo, DM, DM, 256, 2);

    union { uint32_t u; float f; } scu; scu.u = 128u;

    launch(ln_kernel, S_LEN / 8, 256, 0, false, x, wr);
    launch(qkv_kernel, 128, 320, K1_SMEM, true, mXn, mWqkv, (const uint8_t*)wgate, (const uint8_t*)wup, (const uint8_t*)wdown, (const uint8_t*)wo);
    launch(attn_kernel, 132, 512, K2_SMEM, true, mG, mU, mD, scu.f);
    launch(oproj_kernel, 128, 256, K3_SMEM, true, mO, mWo, x, out);
}
```

```cpp
#include <cuda_runtime.h>
#include <cuda_bf16.h>
#include <cuda.h>
#include <stdint.h>
#include <type_traits>

#define COPYMODE 0
#define CTHREAD 0
#define WPRE 5
#define PAT 0xCECC
#define ORDER 0
namespace {

constexpr int S_LEN = 2048;
constexpr int DM = 512;
constexpr int NH = 32;
constexpr int FF = 1792;

__device__ __align__(1024) __nv_bfloat16 g_xn[S_LEN * DM];
__device__ __align__(16) float g_r[S_LEN];
__device__ __align__(1024) uint4 g_q[NH * 128 * 32];
__device__ __align__(1024) uint4 g_k[NH * 4096];
__device__ __align__(1024) uint4 g_v[NH * 4096];
__device__ __align__(1024) __nv_bfloat16 g_o[S_LEN * DM];
__device__ __align__(16) float g_ypart[4 * 2 * DM];
__device__ int g_sel[2];
__device__ float g_gate[2];
__device__ unsigned g_cnt[16 * 32];

#define TL(k, slot) do {} while (0)

__device__ __forceinline__ uint32_t smem_u32(const void* p) { return (uint32_t)__cvta_generic_to_shared(p); }
__device__ __forceinline__ void pdl_wait() { asm volatile("griddepcontrol.wait;" ::: "memory"); }
__device__ __forceinline__ void pdl_launch() { asm volatile("griddepcontrol.launch_dependents;" ::: "memory"); }
__device__ __forceinline__ void mbar_init(uint32_t bar, uint32_t cnt) {
    asm volatile("mbarrier.init.shared::cta.b64 [%0], %1;" :: "r"(bar), "r"(cnt) : "memory");
}
__device__ __forceinline__ void mbar_expect_tx(uint32_t bar, uint32_t bytes) {
    asm volatile("mbarrier.arrive.expect_tx.shared::cta.b64 _, [%0], %1;" :: "r"(bar), "r"(bytes) : "memory");
}
__device__ __forceinline__ void mbar_arrive(uint32_t bar) {
    asm volatile("mbarrier.arrive.shared::cta.b64 _, [%0];" :: "r"(bar) : "memory");
}
__device__ __forceinline__ void mbar_wait(uint32_t bar, uint32_t parity) {
    asm volatile("{\n.reg .pred p;\n.reg .u32 n;\nmov.u32 n, 0;\n"
                 "WAIT_%=:\n"
                 "mbarrier.try_wait.parity.shared::cta.b64 p, [%0], %1;\n"
                 "@p bra DONE_%=;\n"
                 "add.u32 n, n, 1;\n"
                 "setp.lt.u32 p, n, 4000000;\n"
                 "@p bra WAIT_%=;\n"
                 "trap;\n"
                 "DONE_%=:\n}"
                 :: "r"(bar), "r"(parity) : "memory");
}
__device__ __forceinline__ void flag_wait(int idx, unsigned target) {
    asm volatile("{\n.reg .pred p;\n.reg .u32 n, v;\nmov.u32 n, 0;\n"
                 "FW_%=:\n"
                 "ld.acquire.gpu.global.u32 v, [%0];\n"
                 "setp.ge.u32 p, v, %1;\n"
                 "@p bra FD_%=;\n"
                 "add.u32 n, n, 1;\n"
                 "setp.lt.u32 p, n, 16000000;\n"
                 "@p bra FW_%=;\n"
                 "trap;\n"
                 "FD_%=:\n}"
                 :: "l"(g_cnt + idx * 32), "r"(target) : "memory");
}
__device__ __forceinline__ void fence_barrier_init() { asm volatile("fence.mbarrier_init.release.cluster;" ::: "memory"); }
__device__ __forceinline__ void fence_proxy_async() { asm volatile("fence.proxy.async.shared::cta;" ::: "memory"); }
__device__ __forceinline__ void tma3d(uint32_t dst, const CUtensorMap* map, uint32_t bar, int row, int chunk) {
    asm volatile("cp.async.bulk.tensor.3d.shared::cluster.global.mbarrier::complete_tx::bytes [%0], [%1, {%3, %4, %5}], [%2];"
                 :: "r"(dst), "l"((uint64_t)map), "r"(bar), "r"(0), "r"(row), "r"(chunk) : "memory");
}
__device__ __forceinline__ void bulk_g2s(uint32_t dst, const void* src, uint32_t bytes, uint32_t bar) {
    asm volatile("cp.async.bulk.shared::cluster.global.mbarrier::complete_tx::bytes [%0], [%1], %2, [%3];"
                 :: "r"(dst), "l"((uint64_t)src), "r"(bytes), "r"(bar) : "memory");
}
__device__ __forceinline__ void l2_prefetch(const void* src, uint32_t bytes) {
    asm volatile("cp.async.bulk.prefetch.L2.global [%0], %1;" :: "l"((uint64_t)src), "r"(bytes) : "memory");
}
__device__ __forceinline__ void map_prefetch(const CUtensorMap* m) {
    asm volatile("prefetch.tensormap [%0];" :: "l"((uint64_t)m) : "memory");
}
__device__ __forceinline__ uint64_t mkdesc(uint32_t addr, uint32_t lbo, uint32_t sbo, uint32_t swz) {
    return (uint64_t)((addr & 0x3FFFF) >> 4) | ((uint64_t)(lbo >> 4) << 16) | ((uint64_t)(sbo >> 4) << 32) | ((uint64_t)swz << 62);
}
#define WG_FENCE() asm volatile("wgmma.fence.sync.aligned;" ::: "memory")
#define WG_COMMIT() asm volatile("wgmma.commit_group.sync.aligned;" ::: "memory")
#define WG_WAIT(n) asm volatile("wgmma.wait_group.sync.aligned %0;" :: "n"(n) : "memory")

__device__ __forceinline__ float ex2(float x) { float y; asm("ex2.approx.ftz.f32 %0, %1;" : "=f"(y) : "f"(x)); return y; }
__device__ __forceinline__ uint32_t packbf(float lo, float hi) {
    uint32_t r; asm("cvt.rn.bf16x2.f32 %0, %1, %2;" : "=r"(r) : "f"(hi), "f"(lo)); return r;
}
__device__ __forceinline__ float bf_lo(uint32_t v) { return __uint_as_float(v << 16); }
__device__ __forceinline__ float bf_hi(uint32_t v) { return __uint_as_float(v & 0xffff0000u); }
__device__ __forceinline__ float bfr(float x) { return __bfloat162float(__float2bfloat16_rn(x)); }

__device__ __forceinline__ void ln_row(const uint4 a, const uint4 b, const uint4 wa, const uint4 wb, int row, int lane) {
    const uint32_t u[8] = {a.x, a.y, a.z, a.w, b.x, b.y, b.z, b.w};
    const uint32_t w[8] = {wa.x, wa.y, wa.z, wa.w, wb.x, wb.y, wb.z, wb.w};
    float f[16];
    float sum = 0.f;
#pragma unroll
    for (int i = 0; i < 8; i++) { f[2 * i] = bf_lo(u[i]); f[2 * i + 1] = bf_hi(u[i]); sum += f[2 * i] + f[2 * i + 1]; }
#pragma unroll
    for (int o = 16; o > 0; o >>= 1) sum += __shfl_xor_sync(~0u, sum, o);
    const float mean = sum * (1.f / DM);
    float sq = 0.f;
#pragma unroll
    for (int i = 0; i < 16; i++) { const float d = f[i] - mean; sq = fmaf(d, d, sq); }
#pragma unroll
    for (int o = 16; o > 0; o >>= 1) sq += __shfl_xor_sync(~0u, sq, o);
    const float mb = bfr(mean);
    const float vb = bfr(sq * (1.f / DM));
    const float rinv = 1.f / bfr(sqrtf(bfr(vb + 1e-5f)));
    uint32_t o[8];
    float r = 0.f;
#pragma unroll
    for (int i = 0; i < 8; i++) {
        const float d0 = bfr(f[2 * i] - mb), d1 = bfr(f[2 * i + 1] - mb);
        o[i] = packbf(d0 * rinv, d1 * rinv);
        r = fmaf(bf_lo(o[i]), bf_lo(w[i]), r);
        r = fmaf(bf_hi(o[i]), bf_hi(w[i]), r);
    }
    uint4* xo = reinterpret_cast<uint4*>(g_xn + (size_t)row * DM);
    xo[lane] = make_uint4(o[0], o[1], o[2], o[3]);
    xo[32 + lane] = make_uint4(o[4], o[5], o[6], o[7]);
#pragma unroll
    for (int of = 16; of > 0; of >>= 1) r += __shfl_xor_sync(~0u, r, of);
    if (lane == 0) g_r[row] = r;
}

constexpr int K1_ST = 5;
constexpr int K1_STAGE = 16384 + 24576;
constexpr int K1_SMEM = K1_ST * K1_STAGE + 1024 + 128;

__device__ __forceinline__ void wgmma_n192(float (&d)[96], uint64_t da, uint64_t db, int scale_d) {
    asm volatile("{\n.reg .pred p;\nsetp.ne.b32 p, %98, 0;\n"
        "wgmma.mma_async.sync.aligned.m64n192k16.f32.bf16.bf16 "
        "{%0,%1,%2,%3,%4,%5,%6,%7,%8,%9,%10,%11,%12,%13,%14,%15,%16,%17,%18,%19,%20,%21,%22,%23,"
        "%24,%25,%26,%27,%28,%29,%30,%31,%32,%33,%34,%35,%36,%37,%38,%39,%40,%41,%42,%43,%44,%45,%46,%47,"
        "%48,%49,%50,%51,%52,%53,%54,%55,%56,%57,%58,%59,%60,%61,%62,%63,%64,%65,%66,%67,%68,%69,%70,%71,"
        "%72,%73,%74,%75,%76,%77,%78,%79,%80,%81,%82,%83,%84,%85,%86,%87,%88,%89,%90,%91,%92,%93,%94,%95}, "
        "%96, %97, p, 1, 1, 0, 1;\n}"
        : "+f"(d[0]), "+f"(d[1]), "+f"(d[2]), "+f"(d[3]), "+f"(d[4]), "+f"(d[5]), "+f"(d[6]), "+f"(d[7]),
          "+f"(d[8]), "+f"(d[9]), "+f"(d[10]), "+f"(d[11]), "+f"(d[12]), "+f"(d[13]), "+f"(d[14]), "+f"(d[15]),
          "+f"(d[16]), "+f"(d[17]), "+f"(d[18]), "+f"(d[19]), "+f"(d[20]), "+f"(d[21]), "+f"(d[22]), "+f"(d[23]),
          "+f"(d[24]), "+f"(d[25]), "+f"(d[26]), "+f"(d[27]), "+f"(d[28]), "+f"(d[29]), "+f"(d[30]), "+f"(d[31]),
          "+f"(d[32]), "+f"(d[33]), "+f"(d[34]), "+f"(d[35]), "+f"(d[36]), "+f"(d[37]), "+f"(d[38]), "+f"(d[39]),
          "+f"(d[40]), "+f"(d[41]), "+f"(d[42]), "+f"(d[43]), "+f"(d[44]), "+f"(d[45]), "+f"(d[46]), "+f"(d[47]),
          "+f"(d[48]), "+f"(d[49]), "+f"(d[50]), "+f"(d[51]), "+f"(d[52]), "+f"(d[53]), "+f"(d[54]), "+f"(d[55]),
          "+f"(d[56]), "+f"(d[57]), "+f"(d[58]), "+f"(d[59]), "+f"(d[60]), "+f"(d[61]), "+f"(d[62]), "+f"(d[63]),
          "+f"(d[64]), "+f"(d[65]), "+f"(d[66]), "+f"(d[67]), "+f"(d[68]), "+f"(d[69]), "+f"(d[70]), "+f"(d[71]),
          "+f"(d[72]), "+f"(d[73]), "+f"(d[74]), "+f"(d[75]), "+f"(d[76]), "+f"(d[77]), "+f"(d[78]), "+f"(d[79]),
          "+f"(d[80]), "+f"(d[81]), "+f"(d[82]), "+f"(d[83]), "+f"(d[84]), "+f"(d[85]), "+f"(d[86]), "+f"(d[87]),
          "+f"(d[88]), "+f"(d[89]), "+f"(d[90]), "+f"(d[91]), "+f"(d[92]), "+f"(d[93]), "+f"(d[94]), "+f"(d[95])
        : "l"(da), "l"(db), "r"(scale_d));
}

__global__ void __launch_bounds__(320, 1) qkv_kernel(const __grid_constant__ CUtensorMap mapA, const __grid_constant__ CUtensorMap mapB,
                                                     const uint8_t* __restrict__ pwg, const uint8_t* __restrict__ pwu, const uint8_t* __restrict__ pwd,
                                                     const uint8_t* __restrict__ pwo, const __nv_bfloat16* __restrict__ x,
                                                     const __nv_bfloat16* __restrict__ wr) {
    extern __shared__ uint8_t smem_raw[];
    const uint32_t sbase = (smem_u32(smem_raw) + 1023u) & ~1023u;
    const uint32_t bars = sbase + K1_ST * K1_STAGE;
    const int warp = threadIdx.x >> 5, lane = threadIdx.x & 31;
    const int nb = blockIdx.x & 7, mb = blockIdx.x >> 3;
    TL(1, 0);
    uint4 xa[2], xb[2], wa, wb;
    if (warp < 8) {
#pragma unroll
        for (int h = 0; h < 2; h++) {
            const uint4* xr = reinterpret_cast<const uint4*>(x + (size_t)(blockIdx.x * 16 + warp * 2 + h) * DM);
            xa[h] = xr[lane]; xb[h] = xr[32 + lane];
        }
        wa = reinterpret_cast<const uint4*>(wr)[lane]; wb = reinterpret_cast<const uint4*>(wr)[32 + lane];
    }
    if (threadIdx.x == 256) {
        for (int s = 0; s < K1_ST; s++) { mbar_init(bars + 8 * s, 2); mbar_init(bars + 8 * (K1_ST + s), 2); }
        fence_barrier_init();
    }
    __syncthreads();
    if (warp == 8) {
        if (lane == 0) {
            for (int c = 0; c < 8; c++) {
                const int s = c < K1_ST ? c : c - K1_ST;
                if (c >= K1_ST) mbar_wait(bars + 8 * (K1_ST + s), 0);
                mbar_expect_tx(bars + 8 * s, 24576);
                tma3d(sbase + s * K1_STAGE + 16384, &mapB, bars + 8 * s, c * 64, nb * 3);
            }
        }
        return;
    }
    if (warp == 9) {
        asm volatile("bar.sync 1, 288;" ::: "memory");
        if (lane == 0) {
            asm volatile("red.release.gpu.global.add.u32 [%0], 1;" :: "l"(g_cnt + mb * 32) : "memory");
            pdl_launch();
            map_prefetch(&mapA);
            flag_wait(mb, 8);
            asm volatile("fence.proxy.async.global;" ::: "memory");
            for (int c = 0; c < 8; c++) {
                const int s = c < K1_ST ? c : c - K1_ST;
                if (c == K1_ST) {
                    l2_prefetch(pwg + blockIdx.x * 14336, 14336);
                    l2_prefetch(pwu + blockIdx.x * 14336, 14336);
                    l2_prefetch(pwd + blockIdx.x * 14336, 14336);
                    l2_prefetch(pwo + blockIdx.x * 4096, 4096);
                }
                if (c >= K1_ST) mbar_wait(bars + 8 * (K1_ST + s), 0);
                mbar_expect_tx(bars + 8 * s, 16384);
                tma3d(sbase + s * K1_STAGE, &mapA, bars + 8 * s, mb * 128, c);
            }
        }
        return;
    }
    ln_row(xa[0], xb[0], wa, wb, blockIdx.x * 16 + warp * 2, lane);
    ln_row(xa[1], xb[1], wa, wb, blockIdx.x * 16 + warp * 2 + 1, lane);
    asm volatile("bar.arrive 1, 288;" ::: "memory");
    const int wg = warp >> 2;
    float acc[96];
#pragma unroll
    for (int i = 0; i < 96; i++) acc[i] = 0.f;
#pragma unroll 1
    for (int c = 0; c < 8; c++) {
        const int s = c < K1_ST ? c : c - K1_ST;
        const uint32_t st = sbase + s * K1_STAGE;
        mbar_wait(bars + 8 * s, c < K1_ST ? 0 : 1);
        if (c == 0) TL(1, 1);
        const uint64_t da = mkdesc(st + wg * 8192, 16, 1024, 1);
        const uint64_t db = mkdesc(st + 16384, 8192, 1024, 1);
        WG_FENCE();
#pragma unroll
        for (int k = 0; k < 4; k++) wgmma_n192(acc, da + k * 2, db + k * 128, (c | k) != 0);
        WG_COMMIT();
        if (c + K1_ST < 8 + 1) {
            WG_WAIT(1);
            if (c >= 1 && (threadIdx.x & 127) == 0) mbar_arrive(bars + 8 * (K1_ST + c - 1));
        }
    }
    WG_WAIT(0);
    TL(1, 2);
    const int g = lane >> 2, t = lane & 3;
    const int mt = mb * 8 + warp;
#pragma unroll
    for (int hh = 0; hh < 12; hh++) {
        const int gh = nb * 12 + hh;
        const float* a = &acc[hh * 8];
        if (gh < 32) {
            uint4 v;
            v.x = packbf(a[0], a[1]); v.y = packbf(a[2], a[3]);
            v.z = packbf(a[4], a[5]); v.w = packbf(a[6], a[7]);
            g_q[(gh * 128 + mt) * 32 + lane] = v;
        } else {
            uint32_t* dst = reinterpret_cast<uint32_t*>(gh < 64 ? g_k + (gh - 32) * 4096 : g_v + (gh - 64) * 4096);
            const float ks = gh < 64 ? 5.421010862427522e-20f : 1.0f;
            const int off = (mt * 16 + g) * 4 + t;
            dst[off] = packbf(a[0] * ks, a[1] * ks);
            dst[off + 32] = packbf(a[2] * ks, a[3] * ks);
            dst[8192 + off] = packbf(a[4] * ks, a[5] * ks);
            dst[8192 + off + 32] = packbf(a[6] * ks, a[7] * ks);
        }
    }
    TL(1, 3);
}

constexpr float SHIFT = 90.0f;
constexpr float QS = 0.25f * 1.4426950408889634f * 18446744073709551616.0f;
constexpr float scq = 0.25f * 1.4426950408889634f * 3.3087224502121107e-24f;
constexpr int K2_SMEM = 163840 + 1024 + 128;

__device__ __forceinline__ uint32_t polyexp(float lo, float hi) {
    uint32_t w, g, q, h;
    asm("cvt.pack.sat.s16.s32 %0, %1, %2;" : "=r"(w) : "r"(__float_as_uint(hi)), "r"(__float_as_uint(lo)));
    g = w & 0x007F007Fu;
    asm("fma.rn.f16x2 %0, %1, %2, %3;" : "=r"(q) : "r"(g), "r"(0xf940f940u), "r"(0x35513551u));
    asm("mul.rn.f16x2 %0, %1, %2;" : "=r"(h) : "r"(q), "r"(g));
    return w - h;
}
__device__ __forceinline__ void qk64(float (&s)[32], const uint32_t (&q)[4], uint64_t db) {
    asm volatile("wgmma.mma_async.sync.aligned.m64n64k16.f32.bf16.bf16 "
        "{%0,%1,%2,%3,%4,%5,%6,%7,%8,%9,%10,%11,%12,%13,%14,%15,%16,%17,%18,%19,%20,%21,%22,%23,%24,%25,%26,%27,%28,%29,%30,%31}, "
        "{%32,%33,%34,%35}, %36, 0, 1, 1, 0;"
        : "=f"(s[0]), "=f"(s[1]), "=f"(s[2]), "=f"(s[3]), "=f"(s[4]), "=f"(s[5]), "=f"(s[6]), "=f"(s[7]),
          "=f"(s[8]), "=f"(s[9]), "=f"(s[10]), "=f"(s[11]), "=f"(s[12]), "=f"(s[13]), "=f"(s[14]), "=f"(s[15]),
          "=f"(s[16]), "=f"(s[17]), "=f"(s[18]), "=f"(s[19]), "=f"(s[20]), "=f"(s[21]), "=f"(s[22]), "=f"(s[23]),
          "=f"(s[24]), "=f"(s[25]), "=f"(s[26]), "=f"(s[27]), "=f"(s[28]), "=f"(s[29]), "=f"(s[30]), "=f"(s[31])
        : "r"(q[0]), "r"(q[1]), "r"(q[2]), "r"(q[3]), "l"(db));
}
__device__ __forceinline__ void pv24(float (&o)[12], uint32_t a0, uint32_t a1, uint32_t a2, uint32_t a3, uint64_t db) {
    asm volatile("wgmma.mma_async.sync.aligned.m64n24k16.f32.bf16.bf16 "
        "{%0,%1,%2,%3,%4,%5,%6,%7,%8,%9,%10,%11}, {%12,%13,%14,%15}, %16, 1, 1, 1, 1;"
        : "+f"(o[0]), "+f"(o[1]), "+f"(o[2]), "+f"(o[3]), "+f"(o[4]), "+f"(o[5]), "+f"(o[6]), "+f"(o[7]),
          "+f"(o[8]), "+f"(o[9]), "+f"(o[10]), "+f"(o[11])
        : "r"(a0), "r"(a1), "r"(a2), "r"(a3), "l"(db));
}

__device__ __forceinline__ void attn_safe(float (&o)[12], const uint32_t (&q)[4], uint64_t kdesc0, uint64_t vdesc0) {
    float s[32];
    float m0 = -INFINITY, m1 = -INFINITY;
#pragma unroll
    for (int i = 0; i < 12; i++) o[i] = 0.f;
#pragma unroll 1
    for (int j = 0; j < 32; j++) {
        WG_FENCE();
        qk64(s, q, kdesc0 + (uint64_t)(j * 64));
        WG_COMMIT(); WG_WAIT(0);
        float n0 = m0, n1 = m1;
#pragma unroll
        for (int i = 0; i < 8; i++) { n0 = fmaxf(n0, fmaxf(s[4 * i], s[4 * i + 1])); n1 = fmaxf(n1, fmaxf(s[4 * i + 2], s[4 * i + 3])); }
        n0 = fmaxf(n0, __shfl_xor_sync(~0u, n0, 1)); n0 = fmaxf(n0, __shfl_xor_sync(~0u, n0, 2));
        n1 = fmaxf(n1, __shfl_xor_sync(~0u, n1, 1)); n1 = fmaxf(n1, __shfl_xor_sync(~0u, n1, 2));
        const float c0 = ex2((m0 - n0) * QS), c1 = ex2((m1 - n1) * QS);
        m0 = n0; m1 = n1;
#pragma unroll
        for (int i = 0; i < 3; i++) { o[4 * i] *= c0; o[4 * i + 1] *= c0; o[4 * i + 2] *= c1; o[4 * i + 3] *= c1; }
        uint32_t p[16];
#pragma unroll
        for (int i = 0; i < 8; i++) {
            p[2 * i] = packbf(ex2((s[4 * i] - m0) * QS), ex2((s[4 * i + 1] - m0) * QS));
            p[2 * i + 1] = packbf(ex2((s[4 * i + 2] - m1) * QS), ex2((s[4 * i + 3] - m1) * QS));
        }
        WG_FENCE();
#pragma unroll
        for (int kk = 0; kk < 4; kk++) pv24(o, p[4 * kk], p[4 * kk + 1], p[4 * kk + 2], p[4 * kk + 3], vdesc0 + (uint64_t)(j * 64 + kk * 16));
        WG_COMMIT(); WG_WAIT(0);
    }
}

__device__ __forceinline__ void attn_store(const float (&o)[12], int head, int m64, int warp, int lane) {
    const int g = lane >> 2, t = lane & 3;
    const int row = m64 * 64 + warp * 16 + g;
    const float i0 = 1.f / o[8], i1 = 1.f / o[10];
    uint32_t* p0 = reinterpret_cast<uint32_t*>(g_o + (size_t)row * DM + head * 16 + t * 2);
    uint32_t* p1 = reinterpret_cast<uint32_t*>(g_o + (size_t)(row + 8) * DM + head * 16 + t * 2);
    p0[0] = packbf(o[0] * i0, o[1] * i0); p0[4] = packbf(o[4] * i0, o[5] * i0);
    p1[0] = packbf(o[2] * i1, o[3] * i1); p1[4] = packbf(o[6] * i1, o[7] * i1);
}

constexpr int FS_N = 4;
constexpr int FS_BYTES = 32768;
__device__ __forceinline__ void ldsm4t(uint32_t& r0, uint32_t& r1, uint32_t& r2, uint32_t& r3, uint32_t addr) {
    asm volatile("ldmatrix.sync.aligned.m8n8.x4.trans.shared.b16 {%0,%1,%2,%3}, [%4];" : "=r"(r0), "=r"(r1), "=r"(r2), "=r"(r3) : "r"(addr) : "memory");
}
__device__ __forceinline__ void mma16816(float (&d)[4], uint32_t a0, uint32_t a2, uint32_t b0, uint32_t b1) {
    asm volatile("mma.sync.aligned.m16n8k16.row.col.f32.bf16.bf16.f32 {%0,%1,%2,%3}, {%4,%5,%6,%5}, {%7,%8}, {%0,%1,%2,%3};"
                 : "+f"(d[0]), "+f"(d[1]), "+f"(d[2]), "+f"(d[3]) : "r"(a0), "r"(0u), "r"(a2), "r"(b0), "r"(b1));
}
__device__ void ffn_block(int c, uint8_t* smem, uint32_t sbase, const CUtensorMap* mapG, const CUtensorMap* mapU, const CUtensorMap* mapD) {
    const int tid = threadIdx.x, warp = tid >> 5, lane = tid & 31;
    uint32_t* sx = reinterpret_cast<uint32_t*>(smem + FS_N * FS_BYTES);
    __nv_bfloat16* sh = reinterpret_cast<__nv_bfloat16*>(sx + 512);
    const uint32_t bars = sbase + FS_N * FS_BYTES + 8192;
    __shared__ float tv[32]; __shared__ int ti[32];
    __shared__ int ssel[2];
    auto issue = [&](int item) {
        const int slot = item % FS_N;
        const uint32_t dst = sbase + slot * FS_BYTES, bar = bars + 8 * slot;
        mbar_expect_tx(bar, item < 32 ? 28672 : 32768);
        if (item < 32) {
            tma3d(dst, mapG, bar, item * 16, c * 7);
            tma3d(dst + 14336, mapU, bar, item * 16, c * 7);
        } else {
            tma3d(dst, mapD, bar, c * 448 + (item - 32) * 32, 0);
        }
    };
    if (tid == 0) {
        for (int i = 0; i < FS_N; i++) mbar_init(bars + 8 * i, 1);
        fence_barrier_init();
        for (int i = 0; i < FS_N; i++) issue(i);
    }
    float b1 = -INFINITY, b2 = -INFINITY; int i1 = 0x7fffffff, i2 = 0x7fffffff;
    auto push = [&](float v, int i) {
        if (v > b1 || (v == b1 && i < i1)) { b2 = b1; i2 = i1; b1 = v; i1 = i; }
        else if (v > b2 || (v == b2 && i < i2)) { b2 = v; i2 = i; }
    };
    {
        const float4 rv = __ldcg(reinterpret_cast<const float4*>(g_r) + tid);
        push(rv.x, 4 * tid); push(rv.y, 4 * tid + 1); push(rv.z, 4 * tid + 2); push(rv.w, 4 * tid + 3);
    }
#pragma unroll
    for (int o = 16; o > 0; o >>= 1) {
        float v1 = __shfl_xor_sync(~0u, b1, o), v2 = __shfl_xor_sync(~0u, b2, o);
        int j1 = __shfl_xor_sync(~0u, i1, o), j2 = __shfl_xor_sync(~0u, i2, o);
        push(v1, j1); push(v2, j2);
    }
    if (lane == 0) { tv[2 * warp] = b1; ti[2 * warp] = i1; tv[2 * warp + 1] = b2; ti[2 * warp + 1] = i2; }
    __syncthreads();
    if (warp == 1) {
        b1 = tv[lane]; i1 = ti[lane]; b2 = -INFINITY; i2 = 0x7fffffff;
#pragma unroll
        for (int o = 16; o > 0; o >>= 1) {
            float v1 = __shfl_xor_sync(~0u, b1, o), v2 = __shfl_xor_sync(~0u, b2, o);
            int j1 = __shfl_xor_sync(~0u, i1, o), j2 = __shfl_xor_sync(~0u, i2, o);
            push(v1, j1); push(v2, j2);
        }
        if (lane == 0) {
            i1 = min(max(i1, 0), S_LEN - 1); i2 = min(max(i2, 0), S_LEN - 1);
            ssel[0] = i1; ssel[1] = i2;
            if (c == 0) {
                g_sel[0] = i1; g_sel[1] = i2;
                g_gate[0] = bfr(1.f / (1.f + __expf(-bfr(b1))));
                g_gate[1] = bfr(1.f / (1.f + __expf(-bfr(b2))));
            }
        }
    }
    __syncthreads();
    sx[tid] = __ldcg(reinterpret_cast<const uint32_t*>(g_xn + (size_t)ssel[tid >> 8] * DM + (tid & 255) * 2));
    __syncthreads();
    TL(2, 1);
    const int g = lane >> 2, t = lane & 3;
    const int lrow = lane & 15, lsel = lane >> 4;
    {
        float ag[4][4], au[4][4];
#pragma unroll
        for (int j = 0; j < 4; j++) { ag[j][0] = ag[j][1] = ag[j][2] = ag[j][3] = 0.f; au[j][0] = au[j][1] = au[j][2] = au[j][3] = 0.f; }
#pragma unroll 1
        for (int it = 0; it < 32; it++) {
            const int slot = it % FS_N;
            const uint32_t a0 = g < 2 ? sx[g * 256 + it * 8 + t] : 0u, a2 = g < 2 ? sx[g * 256 + it * 8 + 4 + t] : 0u;
            mbar_wait(bars + 8 * slot, (it / FS_N) & 1);
            const uint32_t base = sbase + slot * FS_BYTES + lsel * 14336 + lrow * 128;
#pragma unroll
            for (int j = 0; j < 4; j++) {
                const int nt = warp + j * 16;
                if (nt < 56) {
                    uint32_t b0, b1, b2, b3;
                    ldsm4t(b0, b1, b2, b3, base + (nt >> 3) * 2048 + (((nt & 7) ^ (lrow & 7)) << 4));
                    mma16816(ag[j], a0, a2, b0, b1);
                    mma16816(au[j], a0, a2, b2, b3);
                }
            }
            __syncthreads();
            if (tid == 480) issue(it + FS_N);
        }
        if (g < 2) {
#pragma unroll
            for (int j = 0; j < 4; j++) {
                const int nt = warp + j * 16;
                if (nt < 56) {
#pragma unroll
                    for (int e = 0; e < 2; e++) {
                        const float gs = bfr(ag[j][e]), us = bfr(au[j][e]);
                        const float sg = bfr(gs / (1.f + __expf(-gs)));
                        sh[g * 448 + nt * 8 + t * 2 + e] = __float2bfloat16_rn(sg * us);
                    }
                }
            }
        }
        __syncthreads();
    }
    TL(2, 2);
    {
        const uint32_t* shw = reinterpret_cast<const uint32_t*>(sh);
        float a[4][4];
#pragma unroll
        for (int j = 0; j < 4; j++) a[j][0] = a[j][1] = a[j][2] = a[j][3] = 0.f;
#pragma unroll 1
        for (int it = 32; it < 46; it++) {
            const int slot = it % FS_N;
            uint32_t af[4];
#pragma unroll
            for (int q = 0; q < 4; q++) af[q] = g < 2 ? shw[g * 224 + (it - 32) * 16 + q * 4 + t] : 0u;
            mbar_wait(bars + 8 * slot, (it / FS_N) & 1);
            const uint32_t base = sbase + slot * FS_BYTES + (warp >> 1) * 4096 + lane * 128;
#pragma unroll
            for (int j = 0; j < 4; j++) {
                const int u = (warp & 1) * 4 + j;
                uint32_t b0, b1, b2, b3;
                ldsm4t(b0, b1, b2, b3, base + ((u ^ (lane & 7)) << 4));
                mma16816(a[j], af[0], af[1], b0, b1);
                mma16816(a[j], af[2], af[3], b2, b3);
            }
            __syncthreads();
            if (tid == 480 && it + FS_N < 46) issue(it + FS_N);
        }
        if (g < 2) {
#pragma unroll
            for (int j = 0; j < 4; j++)
                *reinterpret_cast<float2*>(&g_ypart[c * 1024 + g * 512 + (warp * 4 + j) * 8 + t * 2]) = make_float2(a[j][0], a[j][1]);
        }
    }
}

__global__ void __launch_bounds__(512, 1) attn_kernel(const __grid_constant__ CUtensorMap mapG, const __grid_constant__ CUtensorMap mapU,
                                                      const __grid_constant__ CUtensorMap mapD, float sc) {
    extern __shared__ uint8_t smem_raw[];
    const uint32_t sraw = smem_u32(smem_raw);
    const uint32_t sbase = (sraw + 1023u) & ~1023u;
    uint8_t* sptr = smem_raw + (sbase - sraw);
    TL(2, 0);
    if (blockIdx.x < 4) {
        pdl_launch();
        ffn_block(blockIdx.x, sptr, sbase, &mapG, &mapU, &mapD);
        TL(2, 3);
        return;
    }
    const uint32_t bars = sbase + 163840;
    const int head = (blockIdx.x - 4) >> 2, quarter = blockIdx.x & 3;
    const int wg = threadIdx.x >> 7, warp = (threadIdx.x >> 5) & 3, lane = threadIdx.x & 31;
    if (threadIdx.x == 0) {
        for (int c = 0; c < 8; c++) mbar_init(bars + 8 * c, 1);
        fence_barrier_init();
        for (int c = 0; c < 8; c++) mbar_expect_tx(bars + 8 * c, 16384);
    }
    {
        uint4* ones = reinterpret_cast<uint4*>(sptr + 131072);
        for (int i = threadIdx.x; i < 2048; i += 512) ones[i] = make_uint4(0x3f803f80u, 0x3f803f80u, 0x3f803f80u, 0x3f803f80u);
        fence_proxy_async();
    }
    __syncthreads();
    pdl_wait();
    pdl_launch();
    TL(2, 1);
    if (threadIdx.x == CTHREAD) {
        const uint8_t* kp = reinterpret_cast<const uint8_t*>(g_k + head * 4096);
        const uint8_t* vp = reinterpret_cast<const uint8_t*>(g_v + head * 4096);
        for (int c = 0; c < 8; c++) {
            bulk_g2s(sbase + c * 4096, kp + c * 4096, 4096, bars + 8 * c);
            bulk_g2s(sbase + 32768 + c * 4096, kp + 32768 + c * 4096, 4096, bars + 8 * c);
            bulk_g2s(sbase + 65536 + c * 4096, vp + c * 4096, 4096, bars + 8 * c);
            bulk_g2s(sbase + 98304 + c * 4096, vp + 32768 + c * 4096, 4096, bars + 8 * c);
        }
    }
    const uint64_t kdesc0 = mkdesc(sbase, 32768, 128, 0);
    const uint64_t vdesc0 = mkdesc(sbase + 65536, 128, 32768, 0);
    uint32_t badmask = 0;
    uint32_t q[4];
    { const uint4 qq = g_q[(head * 128 + (quarter * 8 + wg) * 4 + warp) * 32 + lane]; q[0] = qq.x; q[1] = qq.y; q[2] = qq.z; q[3] = qq.w; }
#pragma unroll 1
    for (int mt = 0; mt < 2; mt++) {
        const int m64 = quarter * 8 + mt * 4 + wg;
        float s[32], s2[32], o[12];
#pragma unroll
        for (int i = 0; i < 12; i++) o[i] = 0.f;
        mbar_wait(bars, 0);
        if (mt == 0) TL(2, 2);
        WG_FENCE();
        qk64(s, q, kdesc0);
        WG_COMMIT(); WG_WAIT(0);
        float mx0 = -INFINITY, mx1 = -INFINITY;
#pragma unroll
        for (int i = 0; i < 8; i++) { mx0 = fmaxf(mx0, fmaxf(s[4 * i], s[4 * i + 1])); mx1 = fmaxf(mx1, fmaxf(s[4 * i + 2], s[4 * i + 3])); }
        mx0 = fmaxf(mx0, __shfl_xor_sync(~0u, mx0, 1)); mx0 = fmaxf(mx0, __shfl_xor_sync(~0u, mx0, 2));
        mx1 = fmaxf(mx1, __shfl_xor_sync(~0u, mx1, 1)); mx1 = fmaxf(mx1, __shfl_xor_sync(~0u, mx1, 2));
        float cm0 = -(ceilf(mx0 * QS) + SHIFT), cm1 = -(ceilf(mx1 * QS) + SHIFT);
        float cp0 = (cm0 + 127.f) * sc, cp1 = (cm1 + 127.f) * sc;
        asm volatile("" : "+f"(cm0), "+f"(cm1), "+f"(cp0), "+f"(cp1));
        uint64_t kd = kdesc0, vd = vdesc0;
        auto step = [&](float (&sc_)[32], float (&sn)[32]) {
            kd += 64;
            WG_FENCE();
            qk64(sn, q, kd);
            WG_COMMIT();
#pragma unroll
            for (int kk = 0; kk < 4; kk++) {
                uint32_t p[4];
#pragma unroll
                for (int ee = 0; ee < 4; ee++) {
                    const int e = ORDER == 0 ? ee : (ORDER == 1 ? 3 - ee : (ee ^ (ee >> 1)));
                    const int r = kk * 8 + e * 2;
                    const float cmx = (e & 1) ? cm1 : cm0, cpx = (e & 1) ? cp1 : cp0;
                    if ((PAT >> (kk * 4 + e)) & 1) p[e] = polyexp(fmaf(sc_[r], scq, cpx), fmaf(sc_[r + 1], scq, cpx));
                    else p[e] = packbf(ex2(fmaf(sc_[r], QS, cmx)), ex2(fmaf(sc_[r + 1], QS, cmx)));
                }
                WG_FENCE();
                pv24(o, p[0], p[1], p[2], p[3], vd);
                vd += 16;
            }
            WG_COMMIT();
            WG_WAIT(1);
        };
#pragma unroll 1
        for (int c = 0; c < 16; c++) {
            if (mt == 0 && (c & 1) == 0 && c < 14) mbar_wait(bars + 4 * c + 8, 0);
            step(s, s2); step(s2, s);
        }
        WG_WAIT(0);
        {
            const uint4 qq = g_q[(head * 128 + (quarter * 8 + 4 + wg) * 4 + warp) * 32 + lane]; q[0] = qq.x; q[1] = qq.y; q[2] = qq.z; q[3] = qq.w;
        }
        bool bad = !(o[8] > 0.f) || !(o[10] > 0.f);
#pragma unroll
        for (int i = 0; i < 12; i++) bad = bad || !(fabsf(o[i]) <= 3.0e38f);
        uint32_t anybad;
        asm volatile("{\n.reg .pred p, q;\nsetp.ne.u32 p, %1, 0;\nbarrier.cta.red.or.pred q, %2, 128, p;\nselp.u32 %0, 1, 0, q;\n}"
                     : "=r"(anybad) : "r"((uint32_t)bad), "r"(wg + 1) : "memory");
        badmask |= anybad << mt;
        attn_store(o, head, m64, warp, lane);
    }
#pragma unroll 1
    for (int mt = 0; mt < 2; mt++) {
        if (!((badmask >> mt) & 1)) continue;
        const int m64 = quarter * 8 + mt * 4 + wg;
        { const uint4 qq = g_q[(head * 128 + m64 * 4 + warp) * 32 + lane]; q[0] = qq.x; q[1] = qq.y; q[2] = qq.z; q[3] = qq.w; }
        float o[12];
        attn_safe(o, q, mkdesc(sbase, 32768, 128, 0), mkdesc(sbase + 65536, 128, 32768, 0));
        attn_store(o, head, m64, warp, lane);
    }
    TL(2, 3);
}

constexpr int K3_SMEM = 8 * 8192 + 8 * 16384 + 1024 + 128;

__device__ __forceinline__ void wgmma_n64(float (&d)[32], uint64_t da, uint64_t db, int scale_d) {
    asm volatile("{\n.reg .pred p;\nsetp.ne.b32 p, %34, 0;\n"
        "wgmma.mma_async.sync.aligned.m64n64k16.f32.bf16.bf16 "
        "{%0,%1,%2,%3,%4,%5,%6,%7,%8,%9,%10,%11,%12,%13,%14,%15,%16,%17,%18,%19,%20,%21,%22,%23,%24,%25,%26,%27,%28,%29,%30,%31}, "
        "%32, %33, p, 1, 1, 0, 1;\n}"
        : "+f"(d[0]), "+f"(d[1]), "+f"(d[2]), "+f"(d[3]), "+f"(d[4]), "+f"(d[5]), "+f"(d[6]), "+f"(d[7]),
          "+f"(d[8]), "+f"(d[9]), "+f"(d[10]), "+f"(d[11]), "+f"(d[12]), "+f"(d[13]), "+f"(d[14]), "+f"(d[15]),
          "+f"(d[16]), "+f"(d[17]), "+f"(d[18]), "+f"(d[19]), "+f"(d[20]), "+f"(d[21]), "+f"(d[22]), "+f"(d[23]),
          "+f"(d[24]), "+f"(d[25]), "+f"(d[26]), "+f"(d[27]), "+f"(d[28]), "+f"(d[29]), "+f"(d[30]), "+f"(d[31])
        : "l"(da), "l"(db), "r"(scale_d));
}

__global__ void __launch_bounds__(256, 1) oproj_kernel(const __grid_constant__ CUtensorMap mapA, const __grid_constant__ CUtensorMap mapB,
                                                       const __nv_bfloat16* __restrict__ x, __nv_bfloat16* __restrict__ out) {
    extern __shared__ uint8_t smem_raw[];
    const uint32_t sbase = (smem_u32(smem_raw) + 1023u) & ~1023u;
    const uint32_t sA = sbase, sB = sbase + 8 * 8192, bars = sbase + 8 * 8192 + 8 * 16384;
    const int warp = threadIdx.x >> 5, lane = threadIdx.x & 31, wg = warp >> 2;
    const int nb = blockIdx.x & 3, mb = blockIdx.x >> 2;
    TL(3, 0);
    if (threadIdx.x == 0) {
        for (int c = 0; c < 8; c++) mbar_init(bars + 8 * c, 1);
        fence_barrier_init();
        map_prefetch(&mapA);
        for (int h = 0; h < 2; h++) {
            mbar_expect_tx(bars + 8 * (4 + h), 65536);
            tma3d(sB + h * 65536, &mapB, bars + 8 * (4 + h), h * 256, nb * 2);
        }
    }
    const int g = lane >> 2, t = lane & 3;
    const int row0 = mb * 64 + (warp & 3) * 16 + g;
    const int col0 = nb * 128 + wg * 64 + t * 2;
    uint32_t xv[16], nv[16];
#pragma unroll
    for (int i = 0; i < 8; i++) {
        xv[2 * i] = *reinterpret_cast<const uint32_t*>(x + (size_t)row0 * DM + col0 + i * 8);
        xv[2 * i + 1] = *reinterpret_cast<const uint32_t*>(x + (size_t)(row0 + 8) * DM + col0 + i * 8);
        nv[2 * i] = *reinterpret_cast<const uint32_t*>(g_xn + (size_t)row0 * DM + col0 + i * 8);
        nv[2 * i + 1] = *reinterpret_cast<const uint32_t*>(g_xn + (size_t)(row0 + 8) * DM + col0 + i * 8);
    }
    __syncthreads();
    pdl_wait();
    if (blockIdx.x == 0 && threadIdx.x < 16) g_cnt[threadIdx.x * 32] = 0u;
    TL(3, 1);
    if (threadIdx.x == 0) {
        for (int c = 0; c < 4; c++) {
            mbar_expect_tx(bars + 8 * c, 16384);
            tma3d(sA + c * 16384, &mapA, bars + 8 * c, mb * 64, c * 2);
        }
    }
    __shared__ float supd[2][128];
    const int sel0 = g_sel[0], sel1 = g_sel[1];
    {
        const int which = threadIdx.x >> 7, col = nb * 128 + (threadIdx.x & 127);
        const float y = g_ypart[which * 512 + col] + g_ypart[1024 + which * 512 + col] + g_ypart[2048 + which * 512 + col] + g_ypart[3072 + which * 512 + col];
        supd[which][threadIdx.x & 127] = bfr(bfr(y) * g_gate[which]);
    }
    __syncthreads();
    float acc[32];
#pragma unroll
    for (int i = 0; i < 32; i++) acc[i] = 0.f;
#pragma unroll 1
    for (int c = 0; c < 8; c++) {
        if ((c & 3) == 0) mbar_wait(bars + 8 * (4 + (c >> 2)), 0);
        if ((c & 1) == 0) mbar_wait(bars + 8 * (c >> 1), 0);
        const uint64_t da = mkdesc(sA + c * 8192, 16, 1024, 1);
        const uint64_t db = mkdesc(sB + (c >> 2) * 65536 + wg * 32768 + (c & 3) * 8192, 8192, 1024, 1);
        WG_FENCE();
#pragma unroll
        for (int k = 0; k < 4; k++) wgmma_n64(acc, da + k * 2, db + k * 128, (c | k) != 0);
        WG_COMMIT();
    }
    WG_WAIT(0);
    TL(3, 2);
#pragma unroll
    for (int h = 0; h < 2; h++) {
        const int row = row0 + h * 8;
        const int which = row == sel0 ? 0 : (row == sel1 ? 1 : -1);
#pragma unroll
        for (int i = 0; i < 8; i++) {
            const int col = col0 + i * 8;
            float b0 = bf_lo(nv[2 * i + h]), b1 = bf_hi(nv[2 * i + h]);
            if (which >= 0) {
                b0 = bfr(b0 + supd[which][col - nb * 128]); b1 = bfr(b1 + supd[which][col + 1 - nb * 128]);
            }
            const float t0 = bfr(bf_lo(xv[2 * i + h]) + bfr(acc[4 * i + 2 * h]));
            const float t1 = bfr(bf_hi(xv[2 * i + h]) + bfr(acc[4 * i + 2 * h + 1]));
            *reinterpret_cast<uint32_t*>(out + (size_t)row * DM + col) = packbf(t0 + b0, t1 + b1);
        }
    }
    TL(3, 3);
}

typedef CUresult (*EncodeFn)(CUtensorMap*, CUtensorMapDataType, cuuint32_t, void*, const cuuint64_t*, const cuuint64_t*,
                             const cuuint32_t*, const cuuint32_t*, CUtensorMapInterleave, CUtensorMapSwizzle,
                             CUtensorMapL2promotion, CUtensorMapFloatOOBfill);

void make_map(EncodeFn fn, CUtensorMap* m, const void* ptr, uint64_t cols, uint64_t rows, uint32_t box_rows, uint32_t box_chunks) {
    cuuint64_t dims[3] = {64, rows, cols / 64};
    cuuint64_t strides[2] = {cols * 2, 128};
    cuuint32_t box[3] = {64, box_rows, box_chunks};
    cuuint32_t es[3] = {1, 1, 1};
    fn(m, CU_TENSOR_MAP_DATA_TYPE_BFLOAT16, 3, const_cast<void*>(ptr), dims, strides, box, es, CU_TENSOR_MAP_INTERLEAVE_NONE,
       CU_TENSOR_MAP_SWIZZLE_128B, CU_TENSOR_MAP_L2_PROMOTION_L2_256B, CU_TENSOR_MAP_FLOAT_OOB_FILL_NONE);
}

template <typename... KArgs, typename... Args>
void launch(void (*kern)(KArgs...), int grid, int block, int smem, bool pdl, Args... args) {
    cudaLaunchConfig_t cfg = {};
    cfg.gridDim = dim3(grid); cfg.blockDim = dim3(block); cfg.dynamicSmemBytes = smem; cfg.stream = cudaStreamPerThread;
    cudaLaunchAttribute at[1];
    at[0].id = cudaLaunchAttributeProgrammaticStreamSerialization;
    at[0].val.programmaticStreamSerializationAllowed = 1;
    cfg.attrs = at; cfg.numAttrs = pdl ? 1 : 0;
    cudaLaunchKernelEx(&cfg, kern, KArgs(args)...);
}

}

extern "C" void kernel_launch(void* const* d_in, const int* in_sizes, int n_in, void* d_out, int out_size) {
    const __nv_bfloat16* x = (const __nv_bfloat16*)d_in[0];
    const __nv_bfloat16* wqkv = (const __nv_bfloat16*)d_in[1];
    const __nv_bfloat16* wo = (const __nv_bfloat16*)d_in[2];
    const __nv_bfloat16* wr = (const __nv_bfloat16*)d_in[4];
    const __nv_bfloat16* wgate = (const __nv_bfloat16*)d_in[5];
    const __nv_bfloat16* wup = (const __nv_bfloat16*)d_in[6];
    const __nv_bfloat16* wdown = (const __nv_bfloat16*)d_in[7];
    __nv_bfloat16* out = (__nv_bfloat16*)d_out;

    static EncodeFn enc = nullptr;
    static void* p_xn = nullptr; static void* p_o = nullptr;
    if (!enc) {
        void* fn = nullptr; cudaDriverEntryPointQueryResult qr;
        cudaGetDriverEntryPoint("cuTensorMapEncodeTiled", &fn, cudaEnableDefault, &qr);
        enc = (EncodeFn)fn;
        cudaGetSymbolAddress(&p_xn, g_xn);
        cudaGetSymbolAddress(&p_o, g_o);
        cudaFuncSetAttribute(qkv_kernel, cudaFuncAttributeMaxDynamicSharedMemorySize, K1_SMEM);
        cudaFuncSetAttribute(attn_kernel, cudaFuncAttributeMaxDynamicSharedMemorySize, K2_SMEM);
        cudaFuncSetAttribute(oproj_kernel, cudaFuncAttributeMaxDynamicSharedMemorySize, K3_SMEM);
    }
    CUtensorMap mXn, mWqkv, mO, mWo, mG, mU, mD;
    make_map(enc, &mG, wgate, FF, DM, 16, 7);
    make_map(enc, &mU, wup, FF, DM, 16, 7);
    make_map(enc, &mD, wdown, DM, FF, 32, 8);
    make_map(enc, &mXn, p_xn, DM, S_LEN, 128, 1);
    make_map(enc, &mWqkv, wqkv, 3 * DM, DM, 64, 3);
    make_map(enc, &mO, p_o, DM, S_LEN, 64, 2);
    make_map(enc, &mWo, wo, DM, DM, 256, 2);

    union { uint32_t u; float f; } scu; scu.u = 128u;

    launch(qkv_kernel, 128, 320, K1_SMEM, false, mXn, mWqkv, (const uint8_t*)wgate, (const uint8_t*)wup, (const uint8_t*)wdown, (const uint8_t*)wo, x, wr);
    launch(attn_kernel, 132, 512, K2_SMEM, true, mG, mU, mD, scu.f);
    launch(oproj_kernel, 128, 256, K3_SMEM, true, mO, mWo, x, out);
}
```

```cpp
#include <cuda_runtime.h>
#include <cuda_bf16.h>
#include <cuda.h>
#include <stdint.h>

namespace {

constexpr int S_LEN = 2048;
constexpr int DM = 512;
constexpr int NH = 32;
constexpr int FF = 1792;

__device__ __align__(1024) __nv_bfloat16 g_xn[S_LEN * DM];
__device__ __align__(16) float g_r[S_LEN];
__device__ __align__(1024) uint4 g_q[NH * 128 * 32];
__device__ __align__(1024) uint4 g_k[NH * 4096];
__device__ __align__(1024) uint4 g_v[NH * 4096];
__device__ __align__(1024) __nv_bfloat16 g_o[S_LEN * DM];
__device__ __align__(16) float g_ypart[4 * 2 * DM];
__device__ int g_sel[2];
__device__ float g_gate[2];
__device__ float2 g_stat[S_LEN];


__device__ __forceinline__ uint32_t smem_u32(const void* p) { return (uint32_t)__cvta_generic_to_shared(p); }
__device__ __forceinline__ void pdl_wait() { asm volatile("griddepcontrol.wait;" ::: "memory"); }
__device__ __forceinline__ void pdl_launch() { asm volatile("griddepcontrol.launch_dependents;" ::: "memory"); }
__device__ __forceinline__ void mbar_init(uint32_t bar, uint32_t cnt) {
    asm volatile("mbarrier.init.shared::cta.b64 [%0], %1;" :: "r"(bar), "r"(cnt) : "memory");
}
__device__ __forceinline__ void mbar_expect_tx(uint32_t bar, uint32_t bytes) {
    asm volatile("mbarrier.arrive.expect_tx.shared::cta.b64 _, [%0], %1;" :: "r"(bar), "r"(bytes) : "memory");
}
__device__ __forceinline__ void mbar_arrive(uint32_t bar) {
    asm volatile("mbarrier.arrive.shared::cta.b64 _, [%0];" :: "r"(bar) : "memory");
}
__device__ __forceinline__ void mbar_wait(uint32_t bar, uint32_t parity) {
    asm volatile("{\n.reg .pred p;\n.reg .u32 n;\nmov.u32 n, 0;\n"
                 "WAIT_%=:\n"
                 "mbarrier.try_wait.parity.shared::cta.b64 p, [%0], %1;\n"
                 "@p bra DONE_%=;\n"
                 "add.u32 n, n, 1;\n"
                 "setp.lt.u32 p, n, 4000000;\n"
                 "@p bra WAIT_%=;\n"
                 "trap;\n"
                 "DONE_%=:\n}"
                 :: "r"(bar), "r"(parity) : "memory");
}
__device__ __forceinline__ void fence_barrier_init() { asm volatile("fence.mbarrier_init.release.cluster;" ::: "memory"); }
__device__ __forceinline__ void fence_proxy_async() { asm volatile("fence.proxy.async.shared::cta;" ::: "memory"); }
__device__ __forceinline__ void tma3d(uint32_t dst, const CUtensorMap* map, uint32_t bar, int row, int chunk) {
    asm volatile("cp.async.bulk.tensor.3d.shared::cluster.global.mbarrier::complete_tx::bytes [%0], [%1, {%3, %4, %5}], [%2];"
                 :: "r"(dst), "l"((uint64_t)map), "r"(bar), "r"(0), "r"(row), "r"(chunk) : "memory");
}
__device__ __forceinline__ void bulk_g2s(uint32_t dst, const void* src, uint32_t bytes, uint32_t bar) {
    asm volatile("cp.async.bulk.shared::cluster.global.mbarrier::complete_tx::bytes [%0], [%1], %2, [%3];"
                 :: "r"(dst), "l"((uint64_t)src), "r"(bytes), "r"(bar) : "memory");
}
__device__ __forceinline__ void l2_prefetch(const void* src, uint32_t bytes) {
    asm volatile("cp.async.bulk.prefetch.L2.global [%0], %1;" :: "l"((uint64_t)src), "r"(bytes) : "memory");
}
__device__ __forceinline__ void map_prefetch(const CUtensorMap* m) {
    asm volatile("prefetch.tensormap [%0];" :: "l"((uint64_t)m) : "memory");
}
__device__ __forceinline__ uint64_t mkdesc(uint32_t addr, uint32_t lbo, uint32_t sbo, uint32_t swz) {
    return (uint64_t)((addr & 0x3FFFF) >> 4) | ((uint64_t)(lbo >> 4) << 16) | ((uint64_t)(sbo >> 4) << 32) | ((uint64_t)swz << 62);
}
#define WG_FENCE() asm volatile("wgmma.fence.sync.aligned;" ::: "memory")
#define WG_COMMIT() asm volatile("wgmma.commit_group.sync.aligned;" ::: "memory")
#define WG_WAIT(n) asm volatile("wgmma.wait_group.sync.aligned %0;" :: "n"(n) : "memory")

__device__ __forceinline__ float ex2(float x) { float y; asm("ex2.approx.ftz.f32 %0, %1;" : "=f"(y) : "f"(x)); return y; }
__device__ __forceinline__ uint32_t packbf(float lo, float hi) {
    uint32_t r; asm("cvt.rn.bf16x2.f32 %0, %1, %2;" : "=r"(r) : "f"(hi), "f"(lo)); return r;
}
__device__ __forceinline__ float bf_lo(uint32_t v) { return __uint_as_float(v << 16); }
__device__ __forceinline__ float bf_hi(uint32_t v) { return __uint_as_float(v & 0xffff0000u); }
__device__ __forceinline__ float bfr(float x) { return __bfloat162float(__float2bfloat16_rn(x)); }

__global__ void __launch_bounds__(256) ln_kernel(const __nv_bfloat16* __restrict__ x, const __nv_bfloat16* __restrict__ wr,
                                                 const uint8_t* __restrict__ wqkv) {
    pdl_launch();
    const int warp = threadIdx.x >> 5, lane = threadIdx.x & 31;
    const int row = blockIdx.x * 8 + warp;
    const uint4* xr = reinterpret_cast<const uint4*>(x + (size_t)row * DM);
    uint4 a = xr[lane], b = xr[32 + lane];
    const uint4* wp = reinterpret_cast<const uint4*>(wr);
    uint4 wa = wp[lane], wb = wp[32 + lane];
    if (threadIdx.x == 0) l2_prefetch(wqkv + blockIdx.x * 6144, 6144);
    uint32_t u[8] = {a.x, a.y, a.z, a.w, b.x, b.y, b.z, b.w};
    uint32_t w[8] = {wa.x, wa.y, wa.z, wa.w, wb.x, wb.y, wb.z, wb.w};
    float f[16];
    float sum = 0.f;
#pragma unroll
    for (int i = 0; i < 8; i++) { f[2 * i] = bf_lo(u[i]); f[2 * i + 1] = bf_hi(u[i]); sum += f[2 * i] + f[2 * i + 1]; }
#pragma unroll
    for (int o = 16; o > 0; o >>= 1) sum += __shfl_xor_sync(~0u, sum, o);
    const float mean = sum * (1.f / DM);
    float sq = 0.f;
#pragma unroll
    for (int i = 0; i < 16; i++) { float d = f[i] - mean; sq = fmaf(d, d, sq); }
#pragma unroll
    for (int o = 16; o > 0; o >>= 1) sq += __shfl_xor_sync(~0u, sq, o);
    const float mb = bfr(mean);
    const float vb = bfr(sq * (1.f / DM));
    const float den = bfr(sqrtf(bfr(vb + 1e-5f)));
    const float rinv = 1.f / den;
    uint32_t o[8];
    float r = 0.f;
#pragma unroll
    for (int i = 0; i < 8; i++) {
        float d0 = bfr(f[2 * i] - mb), d1 = bfr(f[2 * i + 1] - mb);
        o[i] = packbf(d0 * rinv, d1 * rinv);
        r = fmaf(bf_lo(o[i]), bf_lo(w[i]), r);
        r = fmaf(bf_hi(o[i]), bf_hi(w[i]), r);
    }
#pragma unroll
    for (int of = 16; of > 0; of >>= 1) r += __shfl_xor_sync(~0u, r, of);
    uint4* xo = reinterpret_cast<uint4*>(g_xn + (size_t)row * DM);
    xo[lane] = make_uint4(o[0], o[1], o[2], o[3]);
    xo[32 + lane] = make_uint4(o[4], o[5], o[6], o[7]);
    if (lane == 0) { g_r[row] = r; g_stat[row] = make_float2(mb, rinv); }
}

constexpr int K1_ST = 5;
constexpr int K1_STAGE = 16384 + 24576;
constexpr int K1_SMEM = K1_ST * K1_STAGE + 1024 + 128;

__device__ __forceinline__ void wgmma_n192(float (&d)[96], uint64_t da, uint64_t db, int scale_d) {
    asm volatile("{\n.reg .pred p;\nsetp.ne.b32 p, %98, 0;\n"
        "wgmma.mma_async.sync.aligned.m64n192k16.f32.bf16.bf16 "
        "{%0,%1,%2,%3,%4,%5,%6,%7,%8,%9,%10,%11,%12,%13,%14,%15,%16,%17,%18,%19,%20,%21,%22,%23,"
        "%24,%25,%26,%27,%28,%29,%30,%31,%32,%33,%34,%35,%36,%37,%38,%39,%40,%41,%42,%43,%44,%45,%46,%47,"
        "%48,%49,%50,%51,%52,%53,%54,%55,%56,%57,%58,%59,%60,%61,%62,%63,%64,%65,%66,%67,%68,%69,%70,%71,"
        "%72,%73,%74,%75,%76,%77,%78,%79,%80,%81,%82,%83,%84,%85,%86,%87,%88,%89,%90,%91,%92,%93,%94,%95}, "
        "%96, %97, p, 1, 1, 0, 1;\n}"
        : "+f"(d[0]), "+f"(d[1]), "+f"(d[2]), "+f"(d[3]), "+f"(d[4]), "+f"(d[5]), "+f"(d[6]), "+f"(d[7]),
          "+f"(d[8]), "+f"(d[9]), "+f"(d[10]), "+f"(d[11]), "+f"(d[12]), "+f"(d[13]), "+f"(d[14]), "+f"(d[15]),
          "+f"(d[16]), "+f"(d[17]), "+f"(d[18]), "+f"(d[19]), "+f"(d[20]), "+f"(d[21]), "+f"(d[22]), "+f"(d[23]),
          "+f"(d[24]), "+f"(d[25]), "+f"(d[26]), "+f"(d[27]), "+f"(d[28]), "+f"(d[29]), "+f"(d[30]), "+f"(d[31]),
          "+f"(d[32]), "+f"(d[33]), "+f"(d[34]), "+f"(d[35]), "+f"(d[36]), "+f"(d[37]), "+f"(d[38]), "+f"(d[39]),
          "+f"(d[40]), "+f"(d[41]), "+f"(d[42]), "+f"(d[43]), "+f"(d[44]), "+f"(d[45]), "+f"(d[46]), "+f"(d[47]),
          "+f"(d[48]), "+f"(d[49]), "+f"(d[50]), "+f"(d[51]), "+f"(d[52]), "+f"(d[53]), "+f"(d[54]), "+f"(d[55]),
          "+f"(d[56]), "+f"(d[57]), "+f"(d[58]), "+f"(d[59]), "+f"(d[60]), "+f"(d[61]), "+f"(d[62]), "+f"(d[63]),
          "+f"(d[64]), "+f"(d[65]), "+f"(d[66]), "+f"(d[67]), "+f"(d[68]), "+f"(d[69]), "+f"(d[70]), "+f"(d[71]),
          "+f"(d[72]), "+f"(d[73]), "+f"(d[74]), "+f"(d[75]), "+f"(d[76]), "+f"(d[77]), "+f"(d[78]), "+f"(d[79]),
          "+f"(d[80]), "+f"(d[81]), "+f"(d[82]), "+f"(d[83]), "+f"(d[84]), "+f"(d[85]), "+f"(d[86]), "+f"(d[87]),
          "+f"(d[88]), "+f"(d[89]), "+f"(d[90]), "+f"(d[91]), "+f"(d[92]), "+f"(d[93]), "+f"(d[94]), "+f"(d[95])
        : "l"(da), "l"(db), "r"(scale_d));
}

__global__ void __launch_bounds__(320, 1) qkv_kernel(const __grid_constant__ CUtensorMap mapA, const __grid_constant__ CUtensorMap mapB,
                                                     const uint8_t* __restrict__ pwg, const uint8_t* __restrict__ pwu, const uint8_t* __restrict__ pwd,
                                                     const uint8_t* __restrict__ pwo) {
    extern __shared__ uint8_t smem_raw[];
    const uint32_t sbase = (smem_u32(smem_raw) + 1023u) & ~1023u;
    const uint32_t bars = sbase + K1_ST * K1_STAGE;
    const int warp = threadIdx.x >> 5, lane = threadIdx.x & 31;
    const int nb = blockIdx.x & 7, mb = blockIdx.x >> 3;
    if (threadIdx.x == 0) {
        for (int s = 0; s < K1_ST; s++) { mbar_init(bars + 8 * s, 2); mbar_init(bars + 8 * (K1_ST + s), 2); }
        fence_barrier_init();
    }
    __syncthreads();
    if (warp == 8) {
        if (lane == 0) {
            for (int c = 0; c < 8; c++) {
                const int s = c < K1_ST ? c : c - K1_ST;
                if (c >= K1_ST) mbar_wait(bars + 8 * (K1_ST + s), 0);
                mbar_expect_tx(bars + 8 * s, 24576);
                tma3d(sbase + s * K1_STAGE + 16384, &mapB, bars + 8 * s, c * 64, nb * 3);
            }
        }
        return;
    }
    if (warp == 9) {
        if (lane == 0) {
            map_prefetch(&mapA);
            pdl_wait();
            pdl_launch();
            for (int c = 0; c < 8; c++) {
                const int s = c < K1_ST ? c : c - K1_ST;
                if (c == K1_ST) {
                    l2_prefetch(pwg + blockIdx.x * 14336, 14336);
                    l2_prefetch(pwu + blockIdx.x * 14336, 14336);
                    l2_prefetch(pwd + blockIdx.x * 14336, 14336);
                    l2_prefetch(pwo + blockIdx.x * 4096, 4096);
                }
                if (c >= K1_ST) mbar_wait(bars + 8 * (K1_ST + s), 0);
                mbar_expect_tx(bars + 8 * s, 16384);
                tma3d(sbase + s * K1_STAGE, &mapA, bars + 8 * s, mb * 128, c);
            }
        }
        return;
    }
    const int wg = warp >> 2;
    float acc[96];
#pragma unroll
    for (int i = 0; i < 96; i++) acc[i] = 0.f;
#pragma unroll 1
    for (int c = 0; c < 8; c++) {
        const int s = c < K1_ST ? c : c - K1_ST;
        const uint32_t st = sbase + s * K1_STAGE;
        mbar_wait(bars + 8 * s, c < K1_ST ? 0 : 1);
        const uint64_t da = mkdesc(st + wg * 8192, 16, 1024, 1);
        const uint64_t db = mkdesc(st + 16384, 8192, 1024, 1);
        WG_FENCE();
#pragma unroll
        for (int k = 0; k < 4; k++) wgmma_n192(acc, da + k * 2, db + k * 128, (c | k) != 0);
        WG_COMMIT();
        if (c + K1_ST < 8 + 1) {
            WG_WAIT(1);
            if (c >= 1 && (threadIdx.x & 127) == 0) mbar_arrive(bars + 8 * (K1_ST + c - 1));
        }
    }
    WG_WAIT(0);
    const int g = lane >> 2, t = lane & 3;
    const int mt = mb * 8 + warp;
#pragma unroll
    for (int hh = 0; hh < 12; hh++) {
        const int gh = nb * 12 + hh;
        const float* a = &acc[hh * 8];
        if (gh < 32) {
            uint4 v;
            v.x = packbf(a[0], a[1]); v.y = packbf(a[2], a[3]);
            v.z = packbf(a[4], a[5]); v.w = packbf(a[6], a[7]);
            g_q[(gh * 128 + mt) * 32 + lane] = v;
        } else {
            uint32_t* dst = reinterpret_cast<uint32_t*>(gh < 64 ? g_k + (gh - 32) * 4096 : g_v + (gh - 64) * 4096);
            const float ks = gh < 64 ? 5.421010862427522e-20f : 1.0f;
            const int off = (mt * 16 + g) * 4 + t;
            dst[off] = packbf(a[0] * ks, a[1] * ks);
            dst[off + 32] = packbf(a[2] * ks, a[3] * ks);
            dst[8192 + off] = packbf(a[4] * ks, a[5] * ks);
            dst[8192 + off + 32] = packbf(a[6] * ks, a[7] * ks);
        }
    }
}

constexpr float SHIFT = 90.0f;
constexpr int PAT = 0xCECC;
constexpr float QS = 0.25f * 1.4426950408889634f * 18446744073709551616.0f;
constexpr float scq = 0.25f * 1.4426950408889634f * 3.3087224502121107e-24f;
constexpr int K2_SMEM = 163840 + 1024 + 128;

__device__ __forceinline__ uint32_t polyexp(float lo, float hi) {
    uint32_t w, g, q, h;
    asm("cvt.pack.sat.s16.s32 %0, %1, %2;" : "=r"(w) : "r"(__float_as_uint(hi)), "r"(__float_as_uint(lo)));
    g = w & 0x007F007Fu;
    asm("fma.rn.f16x2 %0, %1, %2, %3;" : "=r"(q) : "r"(g), "r"(0xf940f940u), "r"(0x35513551u));
    asm("mul.rn.f16x2 %0, %1, %2;" : "=r"(h) : "r"(q), "r"(g));
    return w - h;
}
__device__ __forceinline__ void qk64(float (&s)[32], const uint32_t (&q)[4], uint64_t db) {
    asm volatile("wgmma.mma_async.sync.aligned.m64n64k16.f32.bf16.bf16 "
        "{%0,%1,%2,%3,%4,%5,%6,%7,%8,%9,%10,%11,%12,%13,%14,%15,%16,%17,%18,%19,%20,%21,%22,%23,%24,%25,%26,%27,%28,%29,%30,%31}, "
        "{%32,%33,%34,%35}, %36, 0, 1, 1, 0;"
        : "=f"(s[0]), "=f"(s[1]), "=f"(s[2]), "=f"(s[3]), "=f"(s[4]), "=f"(s[5]), "=f"(s[6]), "=f"(s[7]),
          "=f"(s[8]), "=f"(s[9]), "=f"(s[10]), "=f"(s[11]), "=f"(s[12]), "=f"(s[13]), "=f"(s[14]), "=f"(s[15]),
          "=f"(s[16]), "=f"(s[17]), "=f"(s[18]), "=f"(s[19]), "=f"(s[20]), "=f"(s[21]), "=f"(s[22]), "=f"(s[23]),
          "=f"(s[24]), "=f"(s[25]), "=f"(s[26]), "=f"(s[27]), "=f"(s[28]), "=f"(s[29]), "=f"(s[30]), "=f"(s[31])
        : "r"(q[0]), "r"(q[1]), "r"(q[2]), "r"(q[3]), "l"(db));
}
__device__ __forceinline__ void pv24(float (&o)[12], uint32_t a0, uint32_t a1, uint32_t a2, uint32_t a3, uint64_t db) {
    asm volatile("wgmma.mma_async.sync.aligned.m64n24k16.f32.bf16.bf16 "
        "{%0,%1,%2,%3,%4,%5,%6,%7,%8,%9,%10,%11}, {%12,%13,%14,%15}, %16, 1, 1, 1, 1;"
        : "+f"(o[0]), "+f"(o[1]), "+f"(o[2]), "+f"(o[3]), "+f"(o[4]), "+f"(o[5]), "+f"(o[6]), "+f"(o[7]),
          "+f"(o[8]), "+f"(o[9]), "+f"(o[10]), "+f"(o[11])
        : "r"(a0), "r"(a1), "r"(a2), "r"(a3), "l"(db));
}

__device__ __forceinline__ void attn_safe(float (&o)[12], const uint32_t (&q)[4], uint64_t kdesc0, uint64_t vdesc0) {
    float s[32];
    float m0 = -INFINITY, m1 = -INFINITY;
#pragma unroll
    for (int i = 0; i < 12; i++) o[i] = 0.f;
#pragma unroll 1
    for (int j = 0; j < 32; j++) {
        WG_FENCE();
        qk64(s, q, kdesc0 + (uint64_t)(j * 64));
        WG_COMMIT(); WG_WAIT(0);
        float n0 = m0, n1 = m1;
#pragma unroll
        for (int i = 0; i < 8; i++) { n0 = fmaxf(n0, fmaxf(s[4 * i], s[4 * i + 1])); n1 = fmaxf(n1, fmaxf(s[4 * i + 2], s[4 * i + 3])); }
        n0 = fmaxf(n0, __shfl_xor_sync(~0u, n0, 1)); n0 = fmaxf(n0, __shfl_xor_sync(~0u, n0, 2));
        n1 = fmaxf(n1, __shfl_xor_sync(~0u, n1, 1)); n1 = fmaxf(n1, __shfl_xor_sync(~0u, n1, 2));
        const float c0 = ex2((m0 - n0) * QS), c1 = ex2((m1 - n1) * QS);
        m0 = n0; m1 = n1;
#pragma unroll
        for (int i = 0; i < 3; i++) { o[4 * i] *= c0; o[4 * i + 1] *= c0; o[4 * i + 2] *= c1; o[4 * i + 3] *= c1; }
        uint32_t p[16];
#pragma unroll
        for (int i = 0; i < 8; i++) {
            p[2 * i] = packbf(ex2((s[4 * i] - m0) * QS), ex2((s[4 * i + 1] - m0) * QS));
            p[2 * i + 1] = packbf(ex2((s[4 * i + 2] - m1) * QS), ex2((s[4 * i + 3] - m1) * QS));
        }
        WG_FENCE();
#pragma unroll
        for (int kk = 0; kk < 4; kk++) pv24(o, p[4 * kk], p[4 * kk + 1], p[4 * kk + 2], p[4 * kk + 3], vdesc0 + (uint64_t)(j * 64 + kk * 16));
        WG_COMMIT(); WG_WAIT(0);
    }
}

__device__ __forceinline__ void attn_store(const float (&o)[12], int head, int m64, int warp, int lane) {
    const int g = lane >> 2, t = lane & 3;
    const int row = m64 * 64 + warp * 16 + g;
    const float i0 = 1.f / o[8], i1 = 1.f / o[10];
    uint32_t* p0 = reinterpret_cast<uint32_t*>(g_o + (size_t)row * DM + head * 16 + t * 2);
    uint32_t* p1 = reinterpret_cast<uint32_t*>(g_o + (size_t)(row + 8) * DM + head * 16 + t * 2);
    p0[0] = packbf(o[0] * i0, o[1] * i0); p0[4] = packbf(o[4] * i0, o[5] * i0);
    p1[0] = packbf(o[2] * i1, o[3] * i1); p1[4] = packbf(o[6] * i1, o[7] * i1);
}

constexpr int FS_N = 4;
constexpr int FS_BYTES = 32768;
__device__ __forceinline__ void ldsm4t(uint32_t& r0, uint32_t& r1, uint32_t& r2, uint32_t& r3, uint32_t addr) {
    asm volatile("ldmatrix.sync.aligned.m8n8.x4.trans.shared.b16 {%0,%1,%2,%3}, [%4];" : "=r"(r0), "=r"(r1), "=r"(r2), "=r"(r3) : "r"(addr) : "memory");
}
__device__ __forceinline__ void mma16816(float (&d)[4], uint32_t a0, uint32_t a2, uint32_t b0, uint32_t b1) {
    asm volatile("mma.sync.aligned.m16n8k16.row.col.f32.bf16.bf16.f32 {%0,%1,%2,%3}, {%4,%5,%6,%5}, {%7,%8}, {%0,%1,%2,%3};"
                 : "+f"(d[0]), "+f"(d[1]), "+f"(d[2]), "+f"(d[3]) : "r"(a0), "r"(0u), "r"(a2), "r"(b0), "r"(b1));
}
__device__ void ffn_block(int c, uint8_t* smem, uint32_t sbase, const CUtensorMap* mapG, const CUtensorMap* mapU, const CUtensorMap* mapD) {
    const int tid = threadIdx.x, warp = tid >> 5, lane = tid & 31;
    uint32_t* sx = reinterpret_cast<uint32_t*>(smem + FS_N * FS_BYTES);
    __nv_bfloat16* sh = reinterpret_cast<__nv_bfloat16*>(sx + 512);
    const uint32_t bars = sbase + FS_N * FS_BYTES + 8192;
    __shared__ float tv[32]; __shared__ int ti[32];
    __shared__ int ssel[2];
    auto issue = [&](int item) {
        const int slot = item % FS_N;
        const uint32_t dst = sbase + slot * FS_BYTES, bar = bars + 8 * slot;
        mbar_expect_tx(bar, item < 32 ? 28672 : 32768);
        if (item < 32) {
            tma3d(dst, mapG, bar, item * 16, c * 7);
            tma3d(dst + 14336, mapU, bar, item * 16, c * 7);
        } else {
            tma3d(dst, mapD, bar, c * 448 + (item - 32) * 32, 0);
        }
    };
    if (tid == 0) {
        for (int i = 0; i < FS_N; i++) mbar_init(bars + 8 * i, 1);
        fence_barrier_init();
        for (int i = 0; i < FS_N; i++) issue(i);
    }
    float b1 = -INFINITY, b2 = -INFINITY; int i1 = 0x7fffffff, i2 = 0x7fffffff;
    auto push = [&](float v, int i) {
        if (v > b1 || (v == b1 && i < i1)) { b2 = b1; i2 = i1; b1 = v; i1 = i; }
        else if (v > b2 || (v == b2 && i < i2)) { b2 = v; i2 = i; }
    };
    {
        const float4 rv = reinterpret_cast<const float4*>(g_r)[tid];
        push(rv.x, 4 * tid); push(rv.y, 4 * tid + 1); push(rv.z, 4 * tid + 2); push(rv.w, 4 * tid + 3);
    }
#pragma unroll
    for (int o = 16; o > 0; o >>= 1) {
        float v1 = __shfl_xor_sync(~0u, b1, o), v2 = __shfl_xor_sync(~0u, b2, o);
        int j1 = __shfl_xor_sync(~0u, i1, o), j2 = __shfl_xor_sync(~0u, i2, o);
        push(v1, j1); push(v2, j2);
    }
    if (lane == 0) { tv[2 * warp] = b1; ti[2 * warp] = i1; tv[2 * warp + 1] = b2; ti[2 * warp + 1] = i2; }
    __syncthreads();
    if (warp == 1) {
        b1 = tv[lane]; i1 = ti[lane]; b2 = -INFINITY; i2 = 0x7fffffff;
#pragma unroll
        for (int o = 16; o > 0; o >>= 1) {
            float v1 = __shfl_xor_sync(~0u, b1, o), v2 = __shfl_xor_sync(~0u, b2, o);
            int j1 = __shfl_xor_sync(~0u, i1, o), j2 = __shfl_xor_sync(~0u, i2, o);
            push(v1, j1); push(v2, j2);
        }
        if (lane == 0) {
            i1 = min(max(i1, 0), S_LEN - 1); i2 = min(max(i2, 0), S_LEN - 1);
            ssel[0] = i1; ssel[1] = i2;
            if (c == 0) {
                g_sel[0] = i1; g_sel[1] = i2;
                g_gate[0] = bfr(1.f / (1.f + __expf(-bfr(b1))));
                g_gate[1] = bfr(1.f / (1.f + __expf(-bfr(b2))));
            }
        }
    }
    __syncthreads();
    sx[tid] = *reinterpret_cast<const uint32_t*>(g_xn + (size_t)ssel[tid >> 8] * DM + (tid & 255) * 2);
    __syncthreads();
    const int g = lane >> 2, t = lane & 3;
    const int lrow = lane & 15, lsel = lane >> 4;
    {
        float ag[4][4], au[4][4];
#pragma unroll
        for (int j = 0; j < 4; j++) { ag[j][0] = ag[j][1] = ag[j][2] = ag[j][3] = 0.f; au[j][0] = au[j][1] = au[j][2] = au[j][3] = 0.f; }
#pragma unroll 1
        for (int it = 0; it < 32; it++) {
            const int slot = it % FS_N;
            const uint32_t a0 = g < 2 ? sx[g * 256 + it * 8 + t] : 0u, a2 = g < 2 ? sx[g * 256 + it * 8 + 4 + t] : 0u;
            mbar_wait(bars + 8 * slot, (it / FS_N) & 1);
            const uint32_t base = sbase + slot * FS_BYTES + lsel * 14336 + lrow * 128;
#pragma unroll
            for (int j = 0; j < 4; j++) {
                const int nt = warp + j * 16;
                if (nt < 56) {
                    uint32_t b0, b1, b2, b3;
                    ldsm4t(b0, b1, b2, b3, base + (nt >> 3) * 2048 + (((nt & 7) ^ (lrow & 7)) << 4));
                    mma16816(ag[j], a0, a2, b0, b1);
                    mma16816(au[j], a0, a2, b2, b3);
                }
            }
            __syncthreads();
            if (tid == 480) issue(it + FS_N);
        }
        if (g < 2) {
#pragma unroll
            for (int j = 0; j < 4; j++) {
                const int nt = warp + j * 16;
                if (nt < 56) {
#pragma unroll
                    for (int e = 0; e < 2; e++) {
                        const float gs = bfr(ag[j][e]), us = bfr(au[j][e]);
                        const float sg = bfr(gs / (1.f + __expf(-gs)));
                        sh[g * 448 + nt * 8 + t * 2 + e] = __float2bfloat16_rn(sg * us);
                    }
                }
            }
        }
        __syncthreads();
    }
    {
        const uint32_t* shw = reinterpret_cast<const uint32_t*>(sh);
        float a[4][4];
#pragma unroll
        for (int j = 0; j < 4; j++) a[j][0] = a[j][1] = a[j][2] = a[j][3] = 0.f;
#pragma unroll 1
        for (int it = 32; it < 46; it++) {
            const int slot = it % FS_N;
            uint32_t af[4];
#pragma unroll
            for (int q = 0; q < 4; q++) af[q] = g < 2 ? shw[g * 224 + (it - 32) * 16 + q * 4 + t] : 0u;
            mbar_wait(bars + 8 * slot, (it / FS_N) & 1);
            const uint32_t base = sbase + slot * FS_BYTES + (warp >> 1) * 4096 + lane * 128;
#pragma unroll
            for (int j = 0; j < 4; j++) {
                const int u = (warp & 1) * 4 + j;
                uint32_t b0, b1, b2, b3;
                ldsm4t(b0, b1, b2, b3, base + ((u ^ (lane & 7)) << 4));
                mma16816(a[j], af[0], af[1], b0, b1);
                mma16816(a[j], af[2], af[3], b2, b3);
            }
            __syncthreads();
            if (tid == 480 && it + FS_N < 46) issue(it + FS_N);
        }
        if (g < 2) {
#pragma unroll
            for (int j = 0; j < 4; j++)
                *reinterpret_cast<float2*>(&g_ypart[c * 1024 + g * 512 + (warp * 4 + j) * 8 + t * 2]) = make_float2(a[j][0], a[j][1]);
        }
    }
}

__global__ void __launch_bounds__(512, 1) attn_kernel(const __grid_constant__ CUtensorMap mapG, const __grid_constant__ CUtensorMap mapU,
                                                      const __grid_constant__ CUtensorMap mapD, float sc) {
    extern __shared__ uint8_t smem_raw[];
    const uint32_t sraw = smem_u32(smem_raw);
    const uint32_t sbase = (sraw + 1023u) & ~1023u;
    uint8_t* sptr = smem_raw + (sbase - sraw);
    if (blockIdx.x < 4) {
        pdl_launch();
        ffn_block(blockIdx.x, sptr, sbase, &mapG, &mapU, &mapD);
        return;
    }
    const uint32_t bars = sbase + 163840;
    const int head = (blockIdx.x - 4) >> 2, quarter = blockIdx.x & 3;
    const int wg = threadIdx.x >> 7, warp = (threadIdx.x >> 5) & 3, lane = threadIdx.x & 31;
    if (threadIdx.x == 0) {
        for (int c = 0; c < 8; c++) mbar_init(bars + 8 * c, 1);
        fence_barrier_init();
        for (int c = 0; c < 8; c++) mbar_expect_tx(bars + 8 * c, 16384);
    }
    {
        uint4* ones = reinterpret_cast<uint4*>(sptr + 131072);
        for (int i = threadIdx.x; i < 2048; i += 512) ones[i] = make_uint4(0x3f803f80u, 0x3f803f80u, 0x3f803f80u, 0x3f803f80u);
        fence_proxy_async();
    }
    __syncthreads();
    pdl_wait();
    pdl_launch();
    if (threadIdx.x == 0) {
        const uint8_t* kp = reinterpret_cast<const uint8_t*>(g_k + head * 4096);
        const uint8_t* vp = reinterpret_cast<const uint8_t*>(g_v + head * 4096);
        for (int c = 0; c < 8; c++) {
            bulk_g2s(sbase + c * 4096, kp + c * 4096, 4096, bars + 8 * c);
            bulk_g2s(sbase + 32768 + c * 4096, kp + 32768 + c * 4096, 4096, bars + 8 * c);
            bulk_g2s(sbase + 65536 + c * 4096, vp + c * 4096, 4096, bars + 8 * c);
            bulk_g2s(sbase + 98304 + c * 4096, vp + 32768 + c * 4096, 4096, bars + 8 * c);
        }
    }
    const uint64_t kdesc0 = mkdesc(sbase, 32768, 128, 0);
    const uint64_t vdesc0 = mkdesc(sbase + 65536, 128, 32768, 0);
    uint32_t badmask = 0;
    uint32_t q[4];
    { const uint4 qq = g_q[(head * 128 + (quarter * 8 + wg) * 4 + warp) * 32 + lane]; q[0] = qq.x; q[1] = qq.y; q[2] = qq.z; q[3] = qq.w; }
#pragma unroll 1
    for (int mt = 0; mt < 2; mt++) {
        const int m64 = quarter * 8 + mt * 4 + wg;
        float s[32], s2[32], o[12];
#pragma unroll
        for (int i = 0; i < 12; i++) o[i] = 0.f;
        mbar_wait(bars, 0);
        WG_FENCE();
        qk64(s, q, kdesc0);
        WG_COMMIT(); WG_WAIT(0);
        float mx0 = -INFINITY, mx1 = -INFINITY;
#pragma unroll
        for (int i = 0; i < 8; i++) { mx0 = fmaxf(mx0, fmaxf(s[4 * i], s[4 * i + 1])); mx1 = fmaxf(mx1, fmaxf(s[4 * i + 2], s[4 * i + 3])); }
        mx0 = fmaxf(mx0, __shfl_xor_sync(~0u, mx0, 1)); mx0 = fmaxf(mx0, __shfl_xor_sync(~0u, mx0, 2));
        mx1 = fmaxf(mx1, __shfl_xor_sync(~0u, mx1, 1)); mx1 = fmaxf(mx1, __shfl_xor_sync(~0u, mx1, 2));
        float cm0 = -(ceilf(mx0 * QS) + SHIFT), cm1 = -(ceilf(mx1 * QS) + SHIFT);
        float cp0 = (cm0 + 127.f) * sc, cp1 = (cm1 + 127.f) * sc;
        asm volatile("" : "+f"(cm0), "+f"(cm1), "+f"(cp0), "+f"(cp1));
        uint64_t kd = kdesc0, vd = vdesc0;
        auto step = [&](float (&sc_)[32], float (&sn)[32]) {
            kd += 64;
            WG_FENCE();
            qk64(sn, q, kd);
            WG_COMMIT();
#pragma unroll
            for (int kk = 0; kk < 4; kk++) {
                uint32_t p[4];
#pragma unroll
                for (int e = 0; e < 4; e++) {
                    const int r = kk * 8 + e * 2;
                    const float cmx = (e & 1) ? cm1 : cm0, cpx = (e & 1) ? cp1 : cp0;
                    if ((PAT >> (kk * 4 + e)) & 1) p[e] = polyexp(fmaf(sc_[r], scq, cpx), fmaf(sc_[r + 1], scq, cpx));
                    else p[e] = packbf(ex2(fmaf(sc_[r], QS, cmx)), ex2(fmaf(sc_[r + 1], QS, cmx)));
                }
                WG_FENCE();
                pv24(o, p[0], p[1], p[2], p[3], vd);
                vd += 16;
            }
            WG_COMMIT();
            WG_WAIT(1);
        };
#pragma unroll 1
        for (int c = 0; c < 16; c++) {
            if (mt == 0 && (c & 1) == 0 && c < 14) mbar_wait(bars + 4 * c + 8, 0);
            step(s, s2); step(s2, s);
        }
        WG_WAIT(0);
        {
            const uint4 qq = g_q[(head * 128 + (quarter * 8 + 4 + wg) * 4 + warp) * 32 + lane]; q[0] = qq.x; q[1] = qq.y; q[2] = qq.z; q[3] = qq.w;
        }
        bool bad = !(o[8] > 0.f) || !(o[10] > 0.f);
#pragma unroll
        for (int i = 0; i < 12; i++) bad = bad || !(fabsf(o[i]) <= 3.0e38f);
        uint32_t anybad;
        asm volatile("{\n.reg .pred p, q;\nsetp.ne.u32 p, %1, 0;\nbarrier.cta.red.or.pred q, %2, 128, p;\nselp.u32 %0, 1, 0, q;\n}"
                     : "=r"(anybad) : "r"((uint32_t)bad), "r"(wg + 1) : "memory");
        badmask |= anybad << mt;
        attn_store(o, head, m64, warp, lane);
    }
#pragma unroll 1
    for (int mt = 0; mt < 2; mt++) {
        if (!((badmask >> mt) & 1)) continue;
        const int m64 = quarter * 8 + mt * 4 + wg;
        { const uint4 qq = g_q[(head * 128 + m64 * 4 + warp) * 32 + lane]; q[0] = qq.x; q[1] = qq.y; q[2] = qq.z; q[3] = qq.w; }
        float o[12];
        attn_safe(o, q, mkdesc(sbase, 32768, 128, 0), mkdesc(sbase + 65536, 128, 32768, 0));
        attn_store(o, head, m64, warp, lane);
    }
}

constexpr int K3_SMEM = 8 * 8192 + 8 * 16384 + 1024 + 128;

__device__ __forceinline__ void wgmma_n64(float (&d)[32], uint64_t da, uint64_t db, int scale_d) {
    asm volatile("{\n.reg .pred p;\nsetp.ne.b32 p, %34, 0;\n"
        "wgmma.mma_async.sync.aligned.m64n64k16.f32.bf16.bf16 "
        "{%0,%1,%2,%3,%4,%5,%6,%7,%8,%9,%10,%11,%12,%13,%14,%15,%16,%17,%18,%19,%20,%21,%22,%23,%24,%25,%26,%27,%28,%29,%30,%31}, "
        "%32, %33, p, 1, 1, 0, 1;\n}"
        : "+f"(d[0]), "+f"(d[1]), "+f"(d[2]), "+f"(d[3]), "+f"(d[4]), "+f"(d[5]), "+f"(d[6]), "+f"(d[7]),
          "+f"(d[8]), "+f"(d[9]), "+f"(d[10]), "+f"(d[11]), "+f"(d[12]), "+f"(d[13]), "+f"(d[14]), "+f"(d[15]),
          "+f"(d[16]), "+f"(d[17]), "+f"(d[18]), "+f"(d[19]), "+f"(d[20]), "+f"(d[21]), "+f"(d[22]), "+f"(d[23]),
          "+f"(d[24]), "+f"(d[25]), "+f"(d[26]), "+f"(d[27]), "+f"(d[28]), "+f"(d[29]), "+f"(d[30]), "+f"(d[31])
        : "l"(da), "l"(db), "r"(scale_d));
}

__global__ void __launch_bounds__(256, 1) oproj_kernel(const __grid_constant__ CUtensorMap mapA, const __grid_constant__ CUtensorMap mapB,
                                                       const __nv_bfloat16* __restrict__ x, __nv_bfloat16* __restrict__ out) {
    extern __shared__ uint8_t smem_raw[];
    const uint32_t sbase = (smem_u32(smem_raw) + 1023u) & ~1023u;
    const uint32_t sA = sbase, sB = sbase + 8 * 8192, bars = sbase + 8 * 8192 + 8 * 16384;
    const int warp = threadIdx.x >> 5, lane = threadIdx.x & 31, wg = warp >> 2;
    const int nb = blockIdx.x & 3, mb = blockIdx.x >> 2;
    if (threadIdx.x == 0) {
        for (int c = 0; c < 8; c++) mbar_init(bars + 8 * c, 1);
        fence_barrier_init();
        map_prefetch(&mapA);
        for (int h = 0; h < 2; h++) {
            mbar_expect_tx(bars + 8 * (4 + h), 65536);
            tma3d(sB + h * 65536, &mapB, bars + 8 * (4 + h), h * 256, nb * 2);
        }
    }
    const int g = lane >> 2, t = lane & 3;
    const int row0 = mb * 64 + (warp & 3) * 16 + g;
    const int col0 = nb * 128 + wg * 64 + t * 2;
    uint32_t xv[16];
#pragma unroll
    for (int i = 0; i < 8; i++) {
        xv[2 * i] = *reinterpret_cast<const uint32_t*>(x + (size_t)row0 * DM + col0 + i * 8);
        xv[2 * i + 1] = *reinterpret_cast<const uint32_t*>(x + (size_t)(row0 + 8) * DM + col0 + i * 8);
    }
    const float2 st[2] = {g_stat[row0], g_stat[row0 + 8]};
    __syncthreads();
    pdl_wait();
    if (threadIdx.x == 0) {
        for (int c = 0; c < 4; c++) {
            mbar_expect_tx(bars + 8 * c, 16384);
            tma3d(sA + c * 16384, &mapA, bars + 8 * c, mb * 64, c * 2);
        }
    }
    __shared__ float supd[2][128];
    const int sel0 = g_sel[0], sel1 = g_sel[1];
    {
        const int which = threadIdx.x >> 7, col = nb * 128 + (threadIdx.x & 127);
        const float y = g_ypart[which * 512 + col] + g_ypart[1024 + which * 512 + col] + g_ypart[2048 + which * 512 + col] + g_ypart[3072 + which * 512 + col];
        supd[which][threadIdx.x & 127] = bfr(bfr(y) * g_gate[which]);
    }
    __syncthreads();
    float acc[32];
#pragma unroll
    for (int i = 0; i < 32; i++) acc[i] = 0.f;
#pragma unroll 1
    for (int c = 0; c < 8; c++) {
        if ((c & 3) == 0) mbar_wait(bars + 8 * (4 + (c >> 2)), 0);
        if ((c & 1) == 0) mbar_wait(bars + 8 * (c >> 1), 0);
        const uint64_t da = mkdesc(sA + c * 8192, 16, 1024, 1);
        const uint64_t db = mkdesc(sB + (c >> 2) * 65536 + wg * 32768 + (c & 3) * 8192, 8192, 1024, 1);
        WG_FENCE();
#pragma unroll
        for (int k = 0; k < 4; k++) wgmma_n64(acc, da + k * 2, db + k * 128, (c | k) != 0);
        WG_COMMIT();
    }
    WG_WAIT(0);
#pragma unroll
    for (int h = 0; h < 2; h++) {
        const int row = row0 + h * 8;
        const int which = row == sel0 ? 0 : (row == sel1 ? 1 : -1);
#pragma unroll
        for (int i = 0; i < 8; i++) {
            const int col = col0 + i * 8;
            float b0 = bfr(bfr(bf_lo(xv[2 * i + h]) - st[h].x) * st[h].y), b1 = bfr(bfr(bf_hi(xv[2 * i + h]) - st[h].x) * st[h].y);
            if (which >= 0) {
                b0 = bfr(b0 + supd[which][col - nb * 128]); b1 = bfr(b1 + supd[which][col + 1 - nb * 128]);
            }
            const float t0 = bfr(bf_lo(xv[2 * i + h]) + bfr(acc[4 * i + 2 * h]));
            const float t1 = bfr(bf_hi(xv[2 * i + h]) + bfr(acc[4 * i + 2 * h + 1]));
            *reinterpret_cast<uint32_t*>(out + (size_t)row * DM + col) = packbf(t0 + b0, t1 + b1);
        }
    }
}

typedef CUresult (*EncodeFn)(CUtensorMap*, CUtensorMapDataType, cuuint32_t, void*, const cuuint64_t*, const cuuint64_t*,
                             const cuuint32_t*, const cuuint32_t*, CUtensorMapInterleave, CUtensorMapSwizzle,
                             CUtensorMapL2promotion, CUtensorMapFloatOOBfill);

void make_map(EncodeFn fn, CUtensorMap* m, const void* ptr, uint64_t cols, uint64_t rows, uint32_t box_rows, uint32_t box_chunks) {
    cuuint64_t dims[3] = {64, rows, cols / 64};
    cuuint64_t strides[2] = {cols * 2, 128};
    cuuint32_t box[3] = {64, box_rows, box_chunks};
    cuuint32_t es[3] = {1, 1, 1};
    fn(m, CU_TENSOR_MAP_DATA_TYPE_BFLOAT16, 3, const_cast<void*>(ptr), dims, strides, box, es, CU_TENSOR_MAP_INTERLEAVE_NONE,
       CU_TENSOR_MAP_SWIZZLE_128B, CU_TENSOR_MAP_L2_PROMOTION_L2_256B, CU_TENSOR_MAP_FLOAT_OOB_FILL_NONE);
}

template <typename... KArgs, typename... Args>
void launch(void (*kern)(KArgs...), int grid, int block, int smem, bool pdl, Args... args) {
    cudaLaunchConfig_t cfg = {};
    cfg.gridDim = dim3(grid); cfg.blockDim = dim3(block); cfg.dynamicSmemBytes = smem; cfg.stream = cudaStreamPerThread;
    cudaLaunchAttribute at[1];
    at[0].id = cudaLaunchAttributeProgrammaticStreamSerialization;
    at[0].val.programmaticStreamSerializationAllowed = 1;
    cfg.attrs = at; cfg.numAttrs = pdl ? 1 : 0;
    cudaLaunchKernelEx(&cfg, kern, KArgs(args)...);
}

}

extern "C" void kernel_launch(void* const* d_in, const int* in_sizes, int n_in, void* d_out, int out_size) {
    const __nv_bfloat16* x = (const __nv_bfloat16*)d_in[0];
    const __nv_bfloat16* wqkv = (const __nv_bfloat16*)d_in[1];
    const __nv_bfloat16* wo = (const __nv_bfloat16*)d_in[2];
    const __nv_bfloat16* wr = (const __nv_bfloat16*)d_in[4];
    const __nv_bfloat16* wgate = (const __nv_bfloat16*)d_in[5];
    const __nv_bfloat16* wup = (const __nv_bfloat16*)d_in[6];
    const __nv_bfloat16* wdown = (const __nv_bfloat16*)d_in[7];
    __nv_bfloat16* out = (__nv_bfloat16*)d_out;

    static EncodeFn enc = nullptr;
    static void* p_xn = nullptr; static void* p_o = nullptr;
    if (!enc) {
        void* fn = nullptr; cudaDriverEntryPointQueryResult qr;
        cudaGetDriverEntryPoint("cuTensorMapEncodeTiled", &fn, cudaEnableDefault, &qr);
        enc = (EncodeFn)fn;
        cudaGetSymbolAddress(&p_xn, g_xn);
        cudaGetSymbolAddress(&p_o, g_o);
        cudaFuncSetAttribute(qkv_kernel, cudaFuncAttributeMaxDynamicSharedMemorySize, K1_SMEM);
        cudaFuncSetAttribute(attn_kernel, cudaFuncAttributeMaxDynamicSharedMemorySize, K2_SMEM);
        cudaFuncSetAttribute(oproj_kernel, cudaFuncAttributeMaxDynamicSharedMemorySize, K3_SMEM);
    }
    CUtensorMap mXn, mWqkv, mO, mWo, mG, mU, mD;
    make_map(enc, &mG, wgate, FF, DM, 16, 7);
    make_map(enc, &mU, wup, FF, DM, 16, 7);
    make_map(enc, &mD, wdown, DM, FF, 32, 8);
    make_map(enc, &mXn, p_xn, DM, S_LEN, 128, 1);
    make_map(enc, &mWqkv, wqkv, 3 * DM, DM, 64, 3);
    make_map(enc, &mO, p_o, DM, S_LEN, 64, 2);
    make_map(enc, &mWo, wo, DM, DM, 256, 2);

    union { uint32_t u; float f; } scu; scu.u = 128u;

    launch(ln_kernel, S_LEN / 8, 256, 0, false, x, wr, (const uint8_t*)wqkv);
    launch(qkv_kernel, 128, 320, K1_SMEM, true, mXn, mWqkv, (const uint8_t*)wgate, (const uint8_t*)wup, (const uint8_t*)wdown, (const uint8_t*)wo);
    launch(attn_kernel, 132, 512, K2_SMEM, true, mG, mU, mD, scu.f);
    launch(oproj_kernel, 128, 256, K3_SMEM, true, mO, mWo, x, out);
}
```

```cpp
#include <cuda_runtime.h>
#include <cuda_bf16.h>
#include <cuda.h>
#include <stdint.h>

namespace {

constexpr int S_LEN = 2048;
constexpr int DM = 512;
constexpr int NH = 32;
constexpr int FF = 1792;

__device__ __align__(1024) __nv_bfloat16 g_xn[S_LEN * DM];
__device__ __align__(16) float g_r[S_LEN];
__device__ __align__(1024) uint4 g_q[NH * 128 * 32];
__device__ __align__(1024) uint4 g_k[NH * 4096];
__device__ __align__(1024) uint4 g_v[NH * 4096];
__device__ __align__(1024) __nv_bfloat16 g_o[S_LEN * DM];
__device__ __align__(16) float g_ypart[4 * 2 * DM];
__device__ int g_sel[2];
__device__ float g_gate[2];


__device__ __forceinline__ uint32_t smem_u32(const void* p) { return (uint32_t)__cvta_generic_to_shared(p); }
__device__ __forceinline__ void pdl_wait() { asm volatile("griddepcontrol.wait;" ::: "memory"); }
__device__ __forceinline__ void pdl_launch() { asm volatile("griddepcontrol.launch_dependents;" ::: "memory"); }
__device__ __forceinline__ void mbar_init(uint32_t bar, uint32_t cnt) {
    asm volatile("mbarrier.init.shared::cta.b64 [%0], %1;" :: "r"(bar), "r"(cnt) : "memory");
}
__device__ __forceinline__ void mbar_expect_tx(uint32_t bar, uint32_t bytes) {
    asm volatile("mbarrier.arrive.expect_tx.shared::cta.b64 _, [%0], %1;" :: "r"(bar), "r"(bytes) : "memory");
}
__device__ __forceinline__ void mbar_arrive(uint32_t bar) {
    asm volatile("mbarrier.arrive.shared::cta.b64 _, [%0];" :: "r"(bar) : "memory");
}
__device__ __forceinline__ void mbar_wait(uint32_t bar, uint32_t parity) {
    asm volatile("{\n.reg .pred p;\n.reg .u32 n;\nmov.u32 n, 0;\n"
                 "WAIT_%=:\n"
                 "mbarrier.try_wait.parity.shared::cta.b64 p, [%0], %1;\n"
                 "@p bra DONE_%=;\n"
                 "add.u32 n, n, 1;\n"
                 "setp.lt.u32 p, n, 4000000;\n"
                 "@p bra WAIT_%=;\n"
                 "trap;\n"
                 "DONE_%=:\n}"
                 :: "r"(bar), "r"(parity) : "memory");
}
__device__ __forceinline__ void fence_barrier_init() { asm volatile("fence.mbarrier_init.release.cluster;" ::: "memory"); }
__device__ __forceinline__ void fence_proxy_async() { asm volatile("fence.proxy.async.shared::cta;" ::: "memory"); }
__device__ __forceinline__ void tma3d(uint32_t dst, const CUtensorMap* map, uint32_t bar, int row, int chunk) {
    asm volatile("cp.async.bulk.tensor.3d.shared::cluster.global.mbarrier::complete_tx::bytes [%0], [%1, {%3, %4, %5}], [%2];"
                 :: "r"(dst), "l"((uint64_t)map), "r"(bar), "r"(0), "r"(row), "r"(chunk) : "memory");
}
__device__ __forceinline__ void bulk_g2s(uint32_t dst, const void* src, uint32_t bytes, uint32_t bar) {
    asm volatile("cp.async.bulk.shared::cluster.global.mbarrier::complete_tx::bytes [%0], [%1], %2, [%3];"
                 :: "r"(dst), "l"((uint64_t)src), "r"(bytes), "r"(bar) : "memory");
}
__device__ __forceinline__ void l2_prefetch(const void* src, uint32_t bytes) {
    asm volatile("cp.async.bulk.prefetch.L2.global [%0], %1;" :: "l"((uint64_t)src), "r"(bytes) : "memory");
}
__device__ __forceinline__ void map_prefetch(const CUtensorMap* m) {
    asm volatile("prefetch.tensormap [%0];" :: "l"((uint64_t)m) : "memory");
}
__device__ __forceinline__ uint64_t mkdesc(uint32_t addr, uint32_t lbo, uint32_t sbo, uint32_t swz) {
    return (uint64_t)((addr & 0x3FFFF) >> 4) | ((uint64_t)(lbo >> 4) << 16) | ((uint64_t)(sbo >> 4) << 32) | ((uint64_t)swz << 62);
}
#define WG_FENCE() asm volatile("wgmma.fence.sync.aligned;" ::: "memory")
#define WG_COMMIT() asm volatile("wgmma.commit_group.sync.aligned;" ::: "memory")
#define WG_WAIT(n) asm volatile("wgmma.wait_group.sync.aligned %0;" :: "n"(n) : "memory")

__device__ __forceinline__ float ex2(float x) { float y; asm("ex2.approx.ftz.f32 %0, %1;" : "=f"(y) : "f"(x)); return y; }
__device__ __forceinline__ uint32_t packbf(float lo, float hi) {
    uint32_t r; asm("cvt.rn.bf16x2.f32 %0, %1, %2;" : "=r"(r) : "f"(hi), "f"(lo)); return r;
}
__device__ __forceinline__ float bf_lo(uint32_t v) { return __uint_as_float(v << 16); }
__device__ __forceinline__ float bf_hi(uint32_t v) { return __uint_as_float(v & 0xffff0000u); }
__device__ __forceinline__ float bfr(float x) { return __bfloat162float(__float2bfloat16_rn(x)); }

__global__ void __launch_bounds__(256) ln_kernel(const __nv_bfloat16* __restrict__ x, const __nv_bfloat16* __restrict__ wr,
                                                 const uint8_t* __restrict__ wqkv) {
    pdl_launch();
    const int warp = threadIdx.x >> 5, lane = threadIdx.x & 31;
    const int row = blockIdx.x * 8 + warp;
    const uint4* xr = reinterpret_cast<const uint4*>(x + (size_t)row * DM);
    uint4 a = xr[lane], b = xr[32 + lane];
    const uint4* wp = reinterpret_cast<const uint4*>(wr);
    uint4 wa = wp[lane], wb = wp[32 + lane];
    if (threadIdx.x == 0) l2_prefetch(wqkv + blockIdx.x * 6144, 6144);
    uint32_t u[8] = {a.x, a.y, a.z, a.w, b.x, b.y, b.z, b.w};
    uint32_t w[8] = {wa.x, wa.y, wa.z, wa.w, wb.x, wb.y, wb.z, wb.w};
    float f[16];
    float sum = 0.f;
#pragma unroll
    for (int i = 0; i < 8; i++) { f[2 * i] = bf_lo(u[i]); f[2 * i + 1] = bf_hi(u[i]); sum += f[2 * i] + f[2 * i + 1]; }
#pragma unroll
    for (int o = 16; o > 0; o >>= 1) sum += __shfl_xor_sync(~0u, sum, o);
    const float mean = sum * (1.f / DM);
    float sq = 0.f;
#pragma unroll
    for (int i = 0; i < 16; i++) { float d = f[i] - mean; sq = fmaf(d, d, sq); }
#pragma unroll
    for (int o = 16; o > 0; o >>= 1) sq += __shfl_xor_sync(~0u, sq, o);
    const float mb = bfr(mean);
    const float vb = bfr(sq * (1.f / DM));
    const float den = bfr(sqrtf(bfr(vb + 1e-5f)));
    const float rinv = 1.f / den;
    uint32_t o[8];
    float r = 0.f;
#pragma unroll
    for (int i = 0; i < 8; i++) {
        float d0 = bfr(f[2 * i] - mb), d1 = bfr(f[2 * i + 1] - mb);
        o[i] = packbf(d0 * rinv, d1 * rinv);
        r = fmaf(bf_lo(o[i]), bf_lo(w[i]), r);
        r = fmaf(bf_hi(o[i]), bf_hi(w[i]), r);
    }
#pragma unroll
    for (int of = 16; of > 0; of >>= 1) r += __shfl_xor_sync(~0u, r, of);
    uint4* xo = reinterpret_cast<uint4*>(g_xn + (size_t)row * DM);
    xo[lane] = make_uint4(o[0], o[1], o[2], o[3]);
    xo[32 + lane] = make_uint4(o[4], o[5], o[6], o[7]);
    if (lane == 0) g_r[row] = r;
}

constexpr int K1_ST = 5;
constexpr int K1_STAGE = 16384 + 24576;
constexpr int K1_SMEM = K1_ST * K1_STAGE + 1024 + 128;

__device__ __forceinline__ void wgmma_n192(float (&d)[96], uint64_t da, uint64_t db, int scale_d) {
    asm volatile("{\n.reg .pred p;\nsetp.ne.b32 p, %98, 0;\n"
        "wgmma.mma_async.sync.aligned.m64n192k16.f32.bf16.bf16 "
        "{%0,%1,%2,%3,%4,%5,%6,%7,%8,%9,%10,%11,%12,%13,%14,%15,%16,%17,%18,%19,%20,%21,%22,%23,"
        "%24,%25,%26,%27,%28,%29,%30,%31,%32,%33,%34,%35,%36,%37,%38,%39,%40,%41,%42,%43,%44,%45,%46,%47,"
        "%48,%49,%50,%51,%52,%53,%54,%55,%56,%57,%58,%59,%60,%61,%62,%63,%64,%65,%66,%67,%68,%69,%70,%71,"
        "%72,%73,%74,%75,%76,%77,%78,%79,%80,%81,%82,%83,%84,%85,%86,%87,%88,%89,%90,%91,%92,%93,%94,%95}, "
        "%96, %97, p, 1, 1, 0, 1;\n}"
        : "+f"(d[0]), "+f"(d[1]), "+f"(d[2]), "+f"(d[3]), "+f"(d[4]), "+f"(d[5]), "+f"(d[6]), "+f"(d[7]),
          "+f"(d[8]), "+f"(d[9]), "+f"(d[10]), "+f"(d[11]), "+f"(d[12]), "+f"(d[13]), "+f"(d[14]), "+f"(d[15]),
          "+f"(d[16]), "+f"(d[17]), "+f"(d[18]), "+f"(d[19]), "+f"(d[20]), "+f"(d[21]), "+f"(d[22]), "+f"(d[23]),
          "+f"(d[24]), "+f"(d[25]), "+f"(d[26]), "+f"(d[27]), "+f"(d[28]), "+f"(d[29]), "+f"(d[30]), "+f"(d[31]),
          "+f"(d[32]), "+f"(d[33]), "+f"(d[34]), "+f"(d[35]), "+f"(d[36]), "+f"(d[37]), "+f"(d[38]), "+f"(d[39]),
          "+f"(d[40]), "+f"(d[41]), "+f"(d[42]), "+f"(d[43]), "+f"(d[44]), "+f"(d[45]), "+f"(d[46]), "+f"(d[47]),
          "+f"(d[48]), "+f"(d[49]), "+f"(d[50]), "+f"(d[51]), "+f"(d[52]), "+f"(d[53]), "+f"(d[54]), "+f"(d[55]),
          "+f"(d[56]), "+f"(d[57]), "+f"(d[58]), "+f"(d[59]), "+f"(d[60]), "+f"(d[61]), "+f"(d[62]), "+f"(d[63]),
          "+f"(d[64]), "+f"(d[65]), "+f"(d[66]), "+f"(d[67]), "+f"(d[68]), "+f"(d[69]), "+f"(d[70]), "+f"(d[71]),
          "+f"(d[72]), "+f"(d[73]), "+f"(d[74]), "+f"(d[75]), "+f"(d[76]), "+f"(d[77]), "+f"(d[78]), "+f"(d[79]),
          "+f"(d[80]), "+f"(d[81]), "+f"(d[82]), "+f"(d[83]), "+f"(d[84]), "+f"(d[85]), "+f"(d[86]), "+f"(d[87]),
          "+f"(d[88]), "+f"(d[89]), "+f"(d[90]), "+f"(d[91]), "+f"(d[92]), "+f"(d[93]), "+f"(d[94]), "+f"(d[95])
        : "l"(da), "l"(db), "r"(scale_d));
}

__global__ void __launch_bounds__(320, 1) qkv_kernel(const __grid_constant__ CUtensorMap mapA, const __grid_constant__ CUtensorMap mapB,
                                                     const uint8_t* __restrict__ pwg, const uint8_t* __restrict__ pwu, const uint8_t* __restrict__ pwd,
                                                     const uint8_t* __restrict__ pwo) {
    extern __shared__ uint8_t smem_raw[];
    const uint32_t sbase = (smem_u32(smem_raw) + 1023u) & ~1023u;
    const uint32_t bars = sbase + K1_ST * K1_STAGE;
    const int warp = threadIdx.x >> 5, lane = threadIdx.x & 31;
    const int nb = blockIdx.x & 7, mb = blockIdx.x >> 3;
    if (threadIdx.x == 0) {
        for (int s = 0; s < K1_ST; s++) { mbar_init(bars + 8 * s, 2); mbar_init(bars + 8 * (K1_ST + s), 2); }
        fence_barrier_init();
    }
    __syncthreads();
    if (warp == 8) {
        if (lane == 0) {
            for (int c = 0; c < 8; c++) {
                const int s = c < K1_ST ? c : c - K1_ST;
                if (c >= K1_ST) mbar_wait(bars + 8 * (K1_ST + s), 0);
                mbar_expect_tx(bars + 8 * s, 24576);
                tma3d(sbase + s * K1_STAGE + 16384, &mapB, bars + 8 * s, c * 64, nb * 3);
            }
        }
        return;
    }
    if (warp == 9) {
        if (lane == 0) {
            map_prefetch(&mapA);
            pdl_wait();
            pdl_launch();
            for (int c = 0; c < 8; c++) {
                const int s = c < K1_ST ? c : c - K1_ST;
                if (c == K1_ST) {
                    l2_prefetch(pwg + blockIdx.x * 14336, 14336);
                    l2_prefetch(pwu + blockIdx.x * 14336, 14336);
                    l2_prefetch(pwd + blockIdx.x * 14336, 14336);
                    l2_prefetch(pwo + blockIdx.x * 4096, 4096);
                }
                if (c >= K1_ST) mbar_wait(bars + 8 * (K1_ST + s), 0);
                mbar_expect_tx(bars + 8 * s, 16384);
                tma3d(sbase + s * K1_STAGE, &mapA, bars + 8 * s, mb * 128, c);
            }
        }
        return;
    }
    const int wg = warp >> 2;
    float acc[96];
#pragma unroll
    for (int i = 0; i < 96; i++) acc[i] = 0.f;
#pragma unroll 1
    for (int c = 0; c < 8; c++) {
        const int s = c < K1_ST ? c : c - K1_ST;
        const uint32_t st = sbase + s * K1_STAGE;
        mbar_wait(bars + 8 * s, c < K1_ST ? 0 : 1);
        const uint64_t da = mkdesc(st + wg * 8192, 16, 1024, 1);
        const uint64_t db = mkdesc(st + 16384, 8192, 1024, 1);
        WG_FENCE();
#pragma unroll
        for (int k = 0; k < 4; k++) wgmma_n192(acc, da + k * 2, db + k * 128, (c | k) != 0);
        WG_COMMIT();
        if (c + K1_ST < 8 + 1) {
            WG_WAIT(1);
            if (c >= 1 && (threadIdx.x & 127) == 0) mbar_arrive(bars + 8 * (K1_ST + c - 1));
        }
    }
    WG_WAIT(0);
    const int g = lane >> 2, t = lane & 3;
    const int mt = mb * 8 + warp;
#pragma unroll
    for (int hh = 0; hh < 12; hh++) {
        const int gh = nb * 12 + hh;
        const float* a = &acc[hh * 8];
        if (gh < 32) {
            uint4 v;
            v.x = packbf(a[0], a[1]); v.y = packbf(a[2], a[3]);
            v.z = packbf(a[4], a[5]); v.w = packbf(a[6], a[7]);
            g_q[(gh * 128 + mt) * 32 + lane] = v;
        } else {
            uint32_t* dst = reinterpret_cast<uint32_t*>(gh < 64 ? g_k + (gh - 32) * 4096 : g_v + (gh - 64) * 4096);
            const float ks = gh < 64 ? 5.421010862427522e-20f : 1.0f;
            const int off = (mt * 16 + g) * 4 + t;
            dst[off] = packbf(a[0] * ks, a[1] * ks);
            dst[off + 32] = packbf(a[2] * ks, a[3] * ks);
            dst[8192 + off] = packbf(a[4] * ks, a[5] * ks);
            dst[8192 + off + 32] = packbf(a[6] * ks, a[7] * ks);
        }
    }
}

constexpr float SHIFT = 90.0f;
constexpr int PAT = 0xCECC;
constexpr float QS = 0.25f * 1.4426950408889634f * 18446744073709551616.0f;
constexpr float scq = 0.25f * 1.4426950408889634f * 3.3087224502121107e-24f;
constexpr int K2_SMEM = 163840 + 1024 + 128;

__device__ __forceinline__ uint32_t polyexp(float lo, float hi) {
    uint32_t w, g, q, h;
    asm("cvt.pack.sat.s16.s32 %0, %1, %2;" : "=r"(w) : "r"(__float_as_uint(hi)), "r"(__float_as_uint(lo)));
    g = w & 0x007F007Fu;
    asm("fma.rn.f16x2 %0, %1, %2, %3;" : "=r"(q) : "r"(g), "r"(0xf940f940u), "r"(0x35513551u));
    asm("mul.rn.f16x2 %0, %1, %2;" : "=r"(h) : "r"(q), "r"(g));
    return w - h;
}
__device__ __forceinline__ void qk64(float (&s)[32], const uint32_t (&q)[4], uint64_t db) {
    asm volatile("wgmma.mma_async.sync.aligned.m64n64k16.f32.bf16.bf16 "
        "{%0,%1,%2,%3,%4,%5,%6,%7,%8,%9,%10,%11,%12,%13,%14,%15,%16,%17,%18,%19,%20,%21,%22,%23,%24,%25,%26,%27,%28,%29,%30,%31}, "
        "{%32,%33,%34,%35}, %36, 0, 1, 1, 0;"
        : "=f"(s[0]), "=f"(s[1]), "=f"(s[2]), "=f"(s[3]), "=f"(s[4]), "=f"(s[5]), "=f"(s[6]), "=f"(s[7]),
          "=f"(s[8]), "=f"(s[9]), "=f"(s[10]), "=f"(s[11]), "=f"(s[12]), "=f"(s[13]), "=f"(s[14]), "=f"(s[15]),
          "=f"(s[16]), "=f"(s[17]), "=f"(s[18]), "=f"(s[19]), "=f"(s[20]), "=f"(s[21]), "=f"(s[22]), "=f"(s[23]),
          "=f"(s[24]), "=f"(s[25]), "=f"(s[26]), "=f"(s[27]), "=f"(s[28]), "=f"(s[29]), "=f"(s[30]), "=f"(s[31])
        : "r"(q[0]), "r"(q[1]), "r"(q[2]), "r"(q[3]), "l"(db));
}
__device__ __forceinline__ void pv24(float (&o)[12], uint32_t a0, uint32_t a1, uint32_t a2, uint32_t a3, uint64_t db) {
    asm volatile("wgmma.mma_async.sync.aligned.m64n24k16.f32.bf16.bf16 "
        "{%0,%1,%2,%3,%4,%5,%6,%7,%8,%9,%10,%11}, {%12,%13,%14,%15}, %16, 1, 1, 1, 1;"
        : "+f"(o[0]), "+f"(o[1]), "+f"(o[2]), "+f"(o[3]), "+f"(o[4]), "+f"(o[5]), "+f"(o[6]), "+f"(o[7]),
          "+f"(o[8]), "+f"(o[9]), "+f"(o[10]), "+f"(o[11])
        : "r"(a0), "r"(a1), "r"(a2), "r"(a3), "l"(db));
}

__device__ __forceinline__ void attn_safe(float (&o)[12], const uint32_t (&q)[4], uint64_t kdesc0, uint64_t vdesc0) {
    float s[32];
    float m0 = -INFINITY, m1 = -INFINITY;
#pragma unroll
    for (int i = 0; i < 12; i++) o[i] = 0.f;
#pragma unroll 1
    for (int j = 0; j < 32; j++) {
        WG_FENCE();
        qk64(s, q, kdesc0 + (uint64_t)(j * 64));
        WG_COMMIT(); WG_WAIT(0);
        float n0 = m0, n1 = m1;
#pragma unroll
        for (int i = 0; i < 8; i++) { n0 = fmaxf(n0, fmaxf(s[4 * i], s[4 * i + 1])); n1 = fmaxf(n1, fmaxf(s[4 * i + 2], s[4 * i + 3])); }
        n0 = fmaxf(n0, __shfl_xor_sync(~0u, n0, 1)); n0 = fmaxf(n0, __shfl_xor_sync(~0u, n0, 2));
        n1 = fmaxf(n1, __shfl_xor_sync(~0u, n1, 1)); n1 = fmaxf(n1, __shfl_xor_sync(~0u, n1, 2));
        const float c0 = ex2((m0 - n0) * QS), c1 = ex2((m1 - n1) * QS);
        m0 = n0; m1 = n1;
#pragma unroll
        for (int i = 0; i < 3; i++) { o[4 * i] *= c0; o[4 * i + 1] *= c0; o[4 * i + 2] *= c1; o[4 * i + 3] *= c1; }
        uint32_t p[16];
#pragma unroll
        for (int i = 0; i < 8; i++) {
            p[2 * i] = packbf(ex2((s[4 * i] - m0) * QS), ex2((s[4 * i + 1] - m0) * QS));
            p[2 * i + 1] = packbf(ex2((s[4 * i + 2] - m1) * QS), ex2((s[4 * i + 3] - m1) * QS));
        }
        WG_FENCE();
#pragma unroll
        for (int kk = 0; kk < 4; kk++) pv24(o, p[4 * kk], p[4 * kk + 1], p[4 * kk + 2], p[4 * kk + 3], vdesc0 + (uint64_t)(j * 64 + kk * 16));
        WG_COMMIT(); WG_WAIT(0);
    }
}

__device__ __forceinline__ void attn_store(const float (&o)[12], int head, int m64, int warp, int lane) {
    const int g = lane >> 2, t = lane & 3;
    const int row = m64 * 64 + warp * 16 + g;
    const float i0 = 1.f / o[8], i1 = 1.f / o[10];
    uint32_t* p0 = reinterpret_cast<uint32_t*>(g_o + (size_t)row * DM + head * 16 + t * 2);
    uint32_t* p1 = reinterpret_cast<uint32_t*>(g_o + (size_t)(row + 8) * DM + head * 16 + t * 2);
    p0[0] = packbf(o[0] * i0, o[1] * i0); p0[4] = packbf(o[4] * i0, o[5] * i0);
    p1[0] = packbf(o[2] * i1, o[3] * i1); p1[4] = packbf(o[6] * i1, o[7] * i1);
}

constexpr int FS_N = 4;
constexpr int FS_BYTES = 32768;
__device__ __forceinline__ void ldsm4t(uint32_t& r0, uint32_t& r1, uint32_t& r2, uint32_t& r3, uint32_t addr) {
    asm volatile("ldmatrix.sync.aligned.m8n8.x4.trans.shared.b16 {%0,%1,%2,%3}, [%4];" : "=r"(r0), "=r"(r1), "=r"(r2), "=r"(r3) : "r"(addr) : "memory");
}
__device__ __forceinline__ void mma16816(float (&d)[4], uint32_t a0, uint32_t a2, uint32_t b0, uint32_t b1) {
    asm volatile("mma.sync.aligned.m16n8k16.row.col.f32.bf16.bf16.f32 {%0,%1,%2,%3}, {%4,%5,%6,%5}, {%7,%8}, {%0,%1,%2,%3};"
                 : "+f"(d[0]), "+f"(d[1]), "+f"(d[2]), "+f"(d[3]) : "r"(a0), "r"(0u), "r"(a2), "r"(b0), "r"(b1));
}
__device__ void ffn_block(int c, uint8_t* smem, uint32_t sbase, const CUtensorMap* mapG, const CUtensorMap* mapU, const CUtensorMap* mapD) {
    const int tid = threadIdx.x, warp = tid >> 5, lane = tid & 31;
    uint32_t* sx = reinterpret_cast<uint32_t*>(smem + FS_N * FS_BYTES);
    __nv_bfloat16* sh = reinterpret_cast<__nv_bfloat16*>(sx + 512);
    const uint32_t bars = sbase + FS_N * FS_BYTES + 8192;
    __shared__ float tv[32]; __shared__ int ti[32];
    __shared__ int ssel[2];
    auto issue = [&](int item) {
        const int slot = item % FS_N;
        const uint32_t dst = sbase + slot * FS_BYTES, bar = bars + 8 * slot;
        mbar_expect_tx(bar, item < 32 ? 28672 : 32768);
        if (item < 32) {
            tma3d(dst, mapG, bar, item * 16, c * 7);
            tma3d(dst + 14336, mapU, bar, item * 16, c * 7);
        } else {
            tma3d(dst, mapD, bar, c * 448 + (item - 32) * 32, 0);
        }
    };
    if (tid == 0) {
        for (int i = 0; i < FS_N; i++) mbar_init(bars + 8 * i, 1);
        fence_barrier_init();
        for (int i = 0; i < FS_N; i++) issue(i);
    }
    float b1 = -INFINITY, b2 = -INFINITY; int i1 = 0x7fffffff, i2 = 0x7fffffff;
    auto push = [&](float v, int i) {
        if (v > b1 || (v == b1 && i < i1)) { b2 = b1; i2 = i1; b1 = v; i1 = i; }
        else if (v > b2 || (v == b2 && i < i2)) { b2 = v; i2 = i; }
    };
    {
        const float4 rv = reinterpret_cast<const float4*>(g_r)[tid];
        push(rv.x, 4 * tid); push(rv.y, 4 * tid + 1); push(rv.z, 4 * tid + 2); push(rv.w, 4 * tid + 3);
    }
#pragma unroll
    for (int o = 16; o > 0; o >>= 1) {
        float v1 = __shfl_xor_sync(~0u, b1, o), v2 = __shfl_xor_sync(~0u, b2, o);
        int j1 = __shfl_xor_sync(~0u, i1, o), j2 = __shfl_xor_sync(~0u, i2, o);
        push(v1, j1); push(v2, j2);
    }
    if (lane == 0) { tv[2 * warp] = b1; ti[2 * warp] = i1; tv[2 * warp + 1] = b2; ti[2 * warp + 1] = i2; }
    __syncthreads();
    if (warp == 1) {
        b1 = tv[lane]; i1 = ti[lane]; b2 = -INFINITY; i2 = 0x7fffffff;
#pragma unroll
        for (int o = 16; o > 0; o >>= 1) {
            float v1 = __shfl_xor_sync(~0u, b1, o), v2 = __shfl_xor_sync(~0u, b2, o);
            int j1 = __shfl_xor_sync(~0u, i1, o), j2 = __shfl_xor_sync(~0u, i2, o);
            push(v1, j1); push(v2, j2);
        }
        if (lane == 0) {
            i1 = min(max(i1, 0), S_LEN - 1); i2 = min(max(i2, 0), S_LEN - 1);
            ssel[0] = i1; ssel[1] = i2;
            if (c == 0) {
                g_sel[0] = i1; g_sel[1] = i2;
                g_gate[0] = bfr(1.f / (1.f + __expf(-bfr(b1))));
                g_gate[1] = bfr(1.f / (1.f + __expf(-bfr(b2))));
            }
        }
    }
    __syncthreads();
    sx[tid] = *reinterpret_cast<const uint32_t*>(g_xn + (size_t)ssel[tid >> 8] * DM + (tid & 255) * 2);
    __syncthreads();
    const int g = lane >> 2, t = lane & 3;
    const int lrow = lane & 15, lsel = lane >> 4;
    {
        float ag[4][4], au[4][4];
#pragma unroll
        for (int j = 0; j < 4; j++) { ag[j][0] = ag[j][1] = ag[j][2] = ag[j][3] = 0.f; au[j][0] = au[j][1] = au[j][2] = au[j][3] = 0.f; }
#pragma unroll 1
        for (int it = 0; it < 32; it++) {
            const int slot = it % FS_N;
            const uint32_t a0 = g < 2 ? sx[g * 256 + it * 8 + t] : 0u, a2 = g < 2 ? sx[g * 256 + it * 8 + 4 + t] : 0u;
            mbar_wait(bars + 8 * slot, (it / FS_N) & 1);
            const uint32_t base = sbase + slot * FS_BYTES + lsel * 14336 + lrow * 128;
#pragma unroll
            for (int j = 0; j < 4; j++) {
                const int nt = warp + j * 16;
                if (nt < 56) {
                    uint32_t b0, b1, b2, b3;
                    ldsm4t(b0, b1, b2, b3, base + (nt >> 3) * 2048 + (((nt & 7) ^ (lrow & 7)) << 4));
                    mma16816(ag[j], a0, a2, b0, b1);
                    mma16816(au[j], a0, a2, b2, b3);
                }
            }
            __syncthreads();
            if (tid == 480) issue(it + FS_N);
        }
        if (g < 2) {
#pragma unroll
            for (int j = 0; j < 4; j++) {
                const int nt = warp + j * 16;
                if (nt < 56) {
#pragma unroll
                    for (int e = 0; e < 2; e++) {
                        const float gs = bfr(ag[j][e]), us = bfr(au[j][e]);
                        const float sg = bfr(gs / (1.f + __expf(-gs)));
                        sh[g * 448 + nt * 8 + t * 2 + e] = __float2bfloat16_rn(sg * us);
                    }
                }
            }
        }
        __syncthreads();
    }
    {
        const uint32_t* shw = reinterpret_cast<const uint32_t*>(sh);
        float a[4][4];
#pragma unroll
        for (int j = 0; j < 4; j++) a[j][0] = a[j][1] = a[j][2] = a[j][3] = 0.f;
#pragma unroll 1
        for (int it = 32; it < 46; it++) {
            const int slot = it % FS_N;
            uint32_t af[4];
#pragma unroll
            for (int q = 0; q < 4; q++) af[q] = g < 2 ? shw[g * 224 + (it - 32) * 16 + q * 4 + t] : 0u;
            mbar_wait(bars + 8 * slot, (it / FS_N) & 1);
            const uint32_t base = sbase + slot * FS_BYTES + (warp >> 1) * 4096 + lane * 128;
#pragma unroll
            for (int j = 0; j < 4; j++) {
                const int u = (warp & 1) * 4 + j;
                uint32_t b0, b1, b2, b3;
                ldsm4t(b0, b1, b2, b3, base + ((u ^ (lane & 7)) << 4));
                mma16816(a[j], af[0], af[1], b0, b1);
                mma16816(a[j], af[2], af[3], b2, b3);
            }
            __syncthreads();
            if (tid == 480 && it + FS_N < 46) issue(it + FS_N);
        }
        if (g < 2) {
#pragma unroll
            for (int j = 0; j < 4; j++)
                *reinterpret_cast<float2*>(&g_ypart[c * 1024 + g * 512 + (warp * 4 + j) * 8 + t * 2]) = make_float2(a[j][0], a[j][1]);
        }
    }
}

__global__ void __launch_bounds__(512, 1) attn_kernel(const __grid_constant__ CUtensorMap mapG, const __grid_constant__ CUtensorMap mapU,
                                                      const __grid_constant__ CUtensorMap mapD, float sc) {
    extern __shared__ uint8_t smem_raw[];
    const uint32_t sraw = smem_u32(smem_raw);
    const uint32_t sbase = (sraw + 1023u) & ~1023u;
    uint8_t* sptr = smem_raw + (sbase - sraw);
    if (blockIdx.x < 4) {
        pdl_launch();
        ffn_block(blockIdx.x, sptr, sbase, &mapG, &mapU, &mapD);
        return;
    }
    const uint32_t bars = sbase + 163840;
    const int head = (blockIdx.x - 4) >> 2, quarter = blockIdx.x & 3;
    const int wg = threadIdx.x >> 7, warp = (threadIdx.x >> 5) & 3, lane = threadIdx.x & 31;
    if (threadIdx.x == 0) {
        for (int c = 0; c < 8; c++) mbar_init(bars + 8 * c, 1);
        fence_barrier_init();
        for (int c = 0; c < 8; c++) mbar_expect_tx(bars + 8 * c, 16384);
    }
    {
        uint4* ones = reinterpret_cast<uint4*>(sptr + 131072);
        for (int i = threadIdx.x; i < 2048; i += 512) ones[i] = make_uint4(0x3f803f80u, 0x3f803f80u, 0x3f803f80u, 0x3f803f80u);
        fence_proxy_async();
    }
    __syncthreads();
    pdl_wait();
    pdl_launch();
    if (threadIdx.x == 0) {
        const uint8_t* kp = reinterpret_cast<const uint8_t*>(g_k + head * 4096);
        const uint8_t* vp = reinterpret_cast<const uint8_t*>(g_v + head * 4096);
        for (int c = 0; c < 8; c++) {
            bulk_g2s(sbase + c * 4096, kp + c * 4096, 4096, bars + 8 * c);
            bulk_g2s(sbase + 32768 + c * 4096, kp + 32768 + c * 4096, 4096, bars + 8 * c);
            bulk_g2s(sbase + 65536 + c * 4096, vp + c * 4096, 4096, bars + 8 * c);
            bulk_g2s(sbase + 98304 + c * 4096, vp + 32768 + c * 4096, 4096, bars + 8 * c);
        }
    }
    const uint64_t kdesc0 = mkdesc(sbase, 32768, 128, 0);
    const uint64_t vdesc0 = mkdesc(sbase + 65536, 128, 32768, 0);
    uint32_t badmask = 0;
    uint32_t q[4];
    { const uint4 qq = g_q[(head * 128 + (quarter * 8 + wg) * 4 + warp) * 32 + lane]; q[0] = qq.x; q[1] = qq.y; q[2] = qq.z; q[3] = qq.w; }
#pragma unroll 1
    for (int mt = 0; mt < 2; mt++) {
        const int m64 = quarter * 8 + mt * 4 + wg;
        float s[32], s2[32], o[12];
#pragma unroll
        for (int i = 0; i < 12; i++) o[i] = 0.f;
        mbar_wait(bars, 0);
        WG_FENCE();
        qk64(s, q, kdesc0);
        WG_COMMIT(); WG_WAIT(0);
        float mx0 = -INFINITY, mx1 = -INFINITY;
#pragma unroll
        for (int i = 0; i < 8; i++) { mx0 = fmaxf(mx0, fmaxf(s[4 * i], s[4 * i + 1])); mx1 = fmaxf(mx1, fmaxf(s[4 * i + 2], s[4 * i + 3])); }
        mx0 = fmaxf(mx0, __shfl_xor_sync(~0u, mx0, 1)); mx0 = fmaxf(mx0, __shfl_xor_sync(~0u, mx0, 2));
        mx1 = fmaxf(mx1, __shfl_xor_sync(~0u, mx1, 1)); mx1 = fmaxf(mx1, __shfl_xor_sync(~0u, mx1, 2));
        float cm0 = -(ceilf(mx0 * QS) + SHIFT), cm1 = -(ceilf(mx1 * QS) + SHIFT);
        float cp0 = (cm0 + 127.f) * sc, cp1 = (cm1 + 127.f) * sc;
        asm volatile("" : "+f"(cm0), "+f"(cm1), "+f"(cp0), "+f"(cp1));
        uint64_t kd = kdesc0, vd = vdesc0;
        auto step = [&](float (&sc_)[32], float (&sn)[32]) {
            kd += 64;
            WG_FENCE();
            qk64(sn, q, kd);
            WG_COMMIT();
#pragma unroll
            for (int kk = 0; kk < 4; kk++) {
                uint32_t p[4];
#pragma unroll
                for (int e = 0; e < 4; e++) {
                    const int r = kk * 8 + e * 2;
                    const float cmx = (e & 1) ? cm1 : cm0, cpx = (e & 1) ? cp1 : cp0;
                    if ((PAT >> (kk * 4 + e)) & 1) p[e] = polyexp(fmaf(sc_[r], scq, cpx), fmaf(sc_[r + 1], scq, cpx));
                    else p[e] = packbf(ex2(fmaf(sc_[r], QS, cmx)), ex2(fmaf(sc_[r + 1], QS, cmx)));
                }
                WG_FENCE();
                pv24(o, p[0], p[1], p[2], p[3], vd);
                vd += 16;
            }
            WG_COMMIT();
            WG_WAIT(1);
        };
#pragma unroll 1
        for (int c = 0; c < 16; c++) {
            if (mt == 0 && (c & 1) == 0 && c < 14) mbar_wait(bars + 4 * c + 8, 0);
            step(s, s2); step(s2, s);
        }
        WG_WAIT(0);
        {
            const uint4 qq = g_q[(head * 128 + (quarter * 8 + 4 + wg) * 4 + warp) * 32 + lane]; q[0] = qq.x; q[1] = qq.y; q[2] = qq.z; q[3] = qq.w;
        }
        bool bad = !(o[8] > 0.f) || !(o[10] > 0.f);
#pragma unroll
        for (int i = 0; i < 12; i++) bad = bad || !(fabsf(o[i]) <= 3.0e38f);
        uint32_t anybad;
        asm volatile("{\n.reg .pred p, q;\nsetp.ne.u32 p, %1, 0;\nbarrier.cta.red.or.pred q, %2, 128, p;\nselp.u32 %0, 1, 0, q;\n}"
                     : "=r"(anybad) : "r"((uint32_t)bad), "r"(wg + 1) : "memory");
        badmask |= anybad << mt;
        attn_store(o, head, m64, warp, lane);
    }
#pragma unroll 1
    for (int mt = 0; mt < 2; mt++) {
        if (!((badmask >> mt) & 1)) continue;
        const int m64 = quarter * 8 + mt * 4 + wg;
        { const uint4 qq = g_q[(head * 128 + m64 * 4 + warp) * 32 + lane]; q[0] = qq.x; q[1] = qq.y; q[2] = qq.z; q[3] = qq.w; }
        float o[12];
        attn_safe(o, q, mkdesc(sbase, 32768, 128, 0), mkdesc(sbase + 65536, 128, 32768, 0));
        attn_store(o, head, m64, warp, lane);
    }
}

constexpr int K3_SMEM = 8 * 8192 + 8 * 16384 + 1024 + 128;

__device__ __forceinline__ void wgmma_n32(float (&d)[16], uint64_t da, uint64_t db, int scale_d) {
    asm volatile("{\n.reg .pred p;\nsetp.ne.b32 p, %18, 0;\n"
        "wgmma.mma_async.sync.aligned.m64n32k16.f32.bf16.bf16 "
        "{%0,%1,%2,%3,%4,%5,%6,%7,%8,%9,%10,%11,%12,%13,%14,%15}, "
        "%16, %17, p, 1, 1, 0, 1;\n}"
        : "+f"(d[0]), "+f"(d[1]), "+f"(d[2]), "+f"(d[3]), "+f"(d[4]), "+f"(d[5]), "+f"(d[6]), "+f"(d[7]),
          "+f"(d[8]), "+f"(d[9]), "+f"(d[10]), "+f"(d[11]), "+f"(d[12]), "+f"(d[13]), "+f"(d[14]), "+f"(d[15])
        : "l"(da), "l"(db), "r"(scale_d));
}

__global__ void __launch_bounds__(512, 1) oproj_kernel(const __grid_constant__ CUtensorMap mapA, const __grid_constant__ CUtensorMap mapB,
                                                       const __nv_bfloat16* __restrict__ x, __nv_bfloat16* __restrict__ out) {
    extern __shared__ uint8_t smem_raw[];
    const uint32_t sbase = (smem_u32(smem_raw) + 1023u) & ~1023u;
    const uint32_t sA = sbase, sB = sbase + 8 * 8192, bars = sbase + 8 * 8192 + 8 * 16384;
    const int warp = threadIdx.x >> 5, lane = threadIdx.x & 31, wg = warp >> 2;
    const int nb = blockIdx.x & 3, mb = blockIdx.x >> 2;
    if (threadIdx.x == 0) {
        for (int c = 0; c < 8; c++) mbar_init(bars + 8 * c, 1);
        fence_barrier_init();
        map_prefetch(&mapA);
        for (int h = 0; h < 2; h++) {
            mbar_expect_tx(bars + 8 * (4 + h), 65536);
            tma3d(sB + h * 65536, &mapB, bars + 8 * (4 + h), h * 256, nb * 2);
        }
    }
    const int g = lane >> 2, t = lane & 3;
    const int row0 = mb * 64 + (warp & 3) * 16 + g;
    const int col0 = nb * 128 + wg * 32 + t * 2;
    uint32_t xv[8], nv[8];
#pragma unroll
    for (int i = 0; i < 4; i++) {
        xv[2 * i] = *reinterpret_cast<const uint32_t*>(x + (size_t)row0 * DM + col0 + i * 8);
        xv[2 * i + 1] = *reinterpret_cast<const uint32_t*>(x + (size_t)(row0 + 8) * DM + col0 + i * 8);
        nv[2 * i] = *reinterpret_cast<const uint32_t*>(g_xn + (size_t)row0 * DM + col0 + i * 8);
        nv[2 * i + 1] = *reinterpret_cast<const uint32_t*>(g_xn + (size_t)(row0 + 8) * DM + col0 + i * 8);
    }
    __syncthreads();
    pdl_wait();
    if (threadIdx.x == 0) {
        for (int c = 0; c < 4; c++) {
            mbar_expect_tx(bars + 8 * c, 16384);
            tma3d(sA + c * 16384, &mapA, bars + 8 * c, mb * 64, c * 2);
        }
    }
    __shared__ float supd[2][128];
    const int sel0 = g_sel[0], sel1 = g_sel[1];
    if (threadIdx.x >= 256) {
        const int which = (threadIdx.x >> 7) & 1, col = nb * 128 + (threadIdx.x & 127);
        const float y = g_ypart[which * 512 + col] + g_ypart[1024 + which * 512 + col] + g_ypart[2048 + which * 512 + col] + g_ypart[3072 + which * 512 + col];
        supd[which][threadIdx.x & 127] = bfr(bfr(y) * g_gate[which]);
    }
    float acc[16];
#pragma unroll
    for (int i = 0; i < 16; i++) acc[i] = 0.f;
#pragma unroll 1
    for (int c = 0; c < 8; c++) {
        if ((c & 3) == 0) mbar_wait(bars + 8 * (4 + (c >> 2)), 0);
        if ((c & 1) == 0) mbar_wait(bars + 8 * (c >> 1), 0);
        const uint64_t da = mkdesc(sA + c * 8192, 16, 1024, 1);
        const uint64_t db = mkdesc(sB + (c >> 2) * 65536 + (wg >> 1) * 32768 + (c & 3) * 8192 + (wg & 1) * 64, 8192, 1024, 1);
        WG_FENCE();
#pragma unroll
        for (int k = 0; k < 4; k++) wgmma_n32(acc, da + k * 2, db + k * 128, (c | k) != 0);
        WG_COMMIT();
    }
    __syncthreads();
    WG_WAIT(0);
#pragma unroll
    for (int h = 0; h < 2; h++) {
        const int row = row0 + h * 8;
        const int which = row == sel0 ? 0 : (row == sel1 ? 1 : -1);
#pragma unroll
        for (int i = 0; i < 4; i++) {
            const int col = col0 + i * 8;
            float b0 = bf_lo(nv[2 * i + h]), b1 = bf_hi(nv[2 * i + h]);
            if (which >= 0) {
                b0 = bfr(b0 + supd[which][col - nb * 128]); b1 = bfr(b1 + supd[which][col + 1 - nb * 128]);
            }
            const float t0 = bfr(bf_lo(xv[2 * i + h]) + bfr(acc[4 * i + 2 * h]));
            const float t1 = bfr(bf_hi(xv[2 * i + h]) + bfr(acc[4 * i + 2 * h + 1]));
            *reinterpret_cast<uint32_t*>(out + (size_t)row * DM + col) = packbf(t0 + b0, t1 + b1);
        }
    }
}

typedef CUresult (*EncodeFn)(CUtensorMap*, CUtensorMapDataType, cuuint32_t, void*, const cuuint64_t*, const cuuint64_t*,
                             const cuuint32_t*, const cuuint32_t*, CUtensorMapInterleave, CUtensorMapSwizzle,
                             CUtensorMapL2promotion, CUtensorMapFloatOOBfill);

void make_map(EncodeFn fn, CUtensorMap* m, const void* ptr, uint64_t cols, uint64_t rows, uint32_t box_rows, uint32_t box_chunks) {
    cuuint64_t dims[3] = {64, rows, cols / 64};
    cuuint64_t strides[2] = {cols * 2, 128};
    cuuint32_t box[3] = {64, box_rows, box_chunks};
    cuuint32_t es[3] = {1, 1, 1};
    fn(m, CU_TENSOR_MAP_DATA_TYPE_BFLOAT16, 3, const_cast<void*>(ptr), dims, strides, box, es, CU_TENSOR_MAP_INTERLEAVE_NONE,
       CU_TENSOR_MAP_SWIZZLE_128B, CU_TENSOR_MAP_L2_PROMOTION_L2_256B, CU_TENSOR_MAP_FLOAT_OOB_FILL_NONE);
}

template <typename... KArgs, typename... Args>
void launch(void (*kern)(KArgs...), int grid, int block, int smem, bool pdl, Args... args) {
    cudaLaunchConfig_t cfg = {};
    cfg.gridDim = dim3(grid); cfg.blockDim = dim3(block); cfg.dynamicSmemBytes = smem; cfg.stream = cudaStreamPerThread;
    cudaLaunchAttribute at[1];
    at[0].id = cudaLaunchAttributeProgrammaticStreamSerialization;
    at[0].val.programmaticStreamSerializationAllowed = 1;
    cfg.attrs = at; cfg.numAttrs = pdl ? 1 : 0;
    cudaLaunchKernelEx(&cfg, kern, KArgs(args)...);
}

}

extern "C" void kernel_launch(void* const* d_in, const int* in_sizes, int n_in, void* d_out, int out_size) {
    const __nv_bfloat16* x = (const __nv_bfloat16*)d_in[0];
    const __nv_bfloat16* wqkv = (const __nv_bfloat16*)d_in[1];
    const __nv_bfloat16* wo = (const __nv_bfloat16*)d_in[2];
    const __nv_bfloat16* wr = (const __nv_bfloat16*)d_in[4];
    const __nv_bfloat16* wgate = (const __nv_bfloat16*)d_in[5];
    const __nv_bfloat16* wup = (const __nv_bfloat16*)d_in[6];
    const __nv_bfloat16* wdown = (const __nv_bfloat16*)d_in[7];
    __nv_bfloat16* out = (__nv_bfloat16*)d_out;

    static EncodeFn enc = nullptr;
    static void* p_xn = nullptr; static void* p_o = nullptr;
    if (!enc) {
        void* fn = nullptr; cudaDriverEntryPointQueryResult qr;
        cudaGetDriverEntryPoint("cuTensorMapEncodeTiled", &fn, cudaEnableDefault, &qr);
        enc = (EncodeFn)fn;
        cudaGetSymbolAddress(&p_xn, g_xn);
        cudaGetSymbolAddress(&p_o, g_o);
        cudaFuncSetAttribute(qkv_kernel, cudaFuncAttributeMaxDynamicSharedMemorySize, K1_SMEM);
        cudaFuncSetAttribute(attn_kernel, cudaFuncAttributeMaxDynamicSharedMemorySize, K2_SMEM);
        cudaFuncSetAttribute(oproj_kernel, cudaFuncAttributeMaxDynamicSharedMemorySize, K3_SMEM);
    }
    CUtensorMap mXn, mWqkv, mO, mWo, mG, mU, mD;
    make_map(enc, &mG, wgate, FF, DM, 16, 7);
    make_map(enc, &mU, wup, FF, DM, 16, 7);
    make_map(enc, &mD, wdown, DM, FF, 32, 8);
    make_map(enc, &mXn, p_xn, DM, S_LEN, 128, 1);
    make_map(enc, &mWqkv, wqkv, 3 * DM, DM, 64, 3);
    make_map(enc, &mO, p_o, DM, S_LEN, 64, 2);
    make_map(enc, &mWo, wo, DM, DM, 256, 2);

    union { uint32_t u; float f; } scu; scu.u = 128u;

    launch(ln_kernel, S_LEN / 8, 256, 0, false, x, wr, (const uint8_t*)wqkv);
    launch(qkv_kernel, 128, 320, K1_SMEM, true, mXn, mWqkv, (const uint8_t*)wgate, (const uint8_t*)wup, (const uint8_t*)wdown, (const uint8_t*)wo);
    launch(attn_kernel, 132, 512, K2_SMEM, true, mG, mU, mD, scu.f);
    launch(oproj_kernel, 128, 512, K3_SMEM, true, mO, mWo, x, out);
}
```

```cpp
#include <cuda_runtime.h>
#include <cuda_bf16.h>
#include <cuda.h>
#include <stdint.h>

namespace {

constexpr int S_LEN = 2048;
constexpr int DM = 512;
constexpr int NH = 32;
constexpr int FF = 1792;

__device__ __align__(1024) __nv_bfloat16 g_xn[S_LEN * DM];
__device__ __align__(16) float g_r[S_LEN];
__device__ __align__(1024) uint4 g_q[NH * 128 * 32];
__device__ __align__(1024) uint4 g_k[NH * 4096];
__device__ __align__(1024) uint4 g_v[NH * 4096];
__device__ __align__(1024) __nv_bfloat16 g_o[S_LEN * DM];
__device__ __align__(16) float g_ypart[4 * 2 * DM];
__device__ int g_sel[2];
__device__ float g_gate[2];


__device__ __forceinline__ uint32_t smem_u32(const void* p) { return (uint32_t)__cvta_generic_to_shared(p); }
__device__ __forceinline__ void pdl_wait() { asm volatile("griddepcontrol.wait;" ::: "memory"); }
__device__ __forceinline__ void pdl_launch() { asm volatile("griddepcontrol.launch_dependents;" ::: "memory"); }
__device__ __forceinline__ void mbar_init(uint32_t bar, uint32_t cnt) {
    asm volatile("mbarrier.init.shared::cta.b64 [%0], %1;" :: "r"(bar), "r"(cnt) : "memory");
}
__device__ __forceinline__ void mbar_expect_tx(uint32_t bar, uint32_t bytes) {
    asm volatile("mbarrier.arrive.expect_tx.shared::cta.b64 _, [%0], %1;" :: "r"(bar), "r"(bytes) : "memory");
}
__device__ __forceinline__ void mbar_arrive(uint32_t bar) {
    asm volatile("mbarrier.arrive.shared::cta.b64 _, [%0];" :: "r"(bar) : "memory");
}
__device__ __forceinline__ void mbar_wait(uint32_t bar, uint32_t parity) {
    asm volatile("{\n.reg .pred p;\n.reg .u32 n;\nmov.u32 n, 0;\n"
                 "WAIT_%=:\n"
                 "mbarrier.try_wait.parity.shared::cta.b64 p, [%0], %1;\n"
                 "@p bra DONE_%=;\n"
                 "add.u32 n, n, 1;\n"
                 "setp.lt.u32 p, n, 4000000;\n"
                 "@p bra WAIT_%=;\n"
                 "trap;\n"
                 "DONE_%=:\n}"
                 :: "r"(bar), "r"(parity) : "memory");
}
__device__ __forceinline__ void fence_barrier_init() { asm volatile("fence.mbarrier_init.release.cluster;" ::: "memory"); }
__device__ __forceinline__ void fence_proxy_async() { asm volatile("fence.proxy.async.shared::cta;" ::: "memory"); }
__device__ __forceinline__ void tma3d(uint32_t dst, const CUtensorMap* map, uint32_t bar, int row, int chunk) {
    asm volatile("cp.async.bulk.tensor.3d.shared::cluster.global.mbarrier::complete_tx::bytes [%0], [%1, {%3, %4, %5}], [%2];"
                 :: "r"(dst), "l"((uint64_t)map), "r"(bar), "r"(0), "r"(row), "r"(chunk) : "memory");
}
__device__ __forceinline__ void bulk_g2s(uint32_t dst, const void* src, uint32_t bytes, uint32_t bar) {
    asm volatile("cp.async.bulk.shared::cluster.global.mbarrier::complete_tx::bytes [%0], [%1], %2, [%3];"
                 :: "r"(dst), "l"((uint64_t)src), "r"(bytes), "r"(bar) : "memory");
}
__device__ __forceinline__ void l2_prefetch(const void* src, uint32_t bytes) {
    asm volatile("cp.async.bulk.prefetch.L2.global [%0], %1;" :: "l"((uint64_t)src), "r"(bytes) : "memory");
}
__device__ __forceinline__ void map_prefetch(const CUtensorMap* m) {
    asm volatile("prefetch.tensormap [%0];" :: "l"((uint64_t)m) : "memory");
}
__device__ __forceinline__ uint64_t mkdesc(uint32_t addr, uint32_t lbo, uint32_t sbo, uint32_t swz) {
    return (uint64_t)((addr & 0x3FFFF) >> 4) | ((uint64_t)(lbo >> 4) << 16) | ((uint64_t)(sbo >> 4) << 32) | ((uint64_t)swz << 62);
}
#define WG_FENCE() asm volatile("wgmma.fence.sync.aligned;" ::: "memory")
#define WG_COMMIT() asm volatile("wgmma.commit_group.sync.aligned;" ::: "memory")
#define WG_WAIT(n) asm volatile("wgmma.wait_group.sync.aligned %0;" :: "n"(n) : "memory")

__device__ __forceinline__ float ex2(float x) { float y; asm("ex2.approx.ftz.f32 %0, %1;" : "=f"(y) : "f"(x)); return y; }
__device__ __forceinline__ uint32_t packbf(float lo, float hi) {
    uint32_t r; asm("cvt.rn.bf16x2.f32 %0, %1, %2;" : "=r"(r) : "f"(hi), "f"(lo)); return r;
}
__device__ __forceinline__ float bf_lo(uint32_t v) { return __uint_as_float(v << 16); }
__device__ __forceinline__ float bf_hi(uint32_t v) { return __uint_as_float(v & 0xffff0000u); }
__device__ __forceinline__ float bfr(float x) { return __bfloat162float(__float2bfloat16_rn(x)); }

__global__ void __launch_bounds__(256) ln_kernel(const __nv_bfloat16* __restrict__ x, const __nv_bfloat16* __restrict__ wr,
                                                 const uint8_t* __restrict__ wqkv) {
    pdl_launch();
    const int warp = threadIdx.x >> 5, lane = threadIdx.x & 31;
    const int row = blockIdx.x * 8 + warp;
    const uint4* xr = reinterpret_cast<const uint4*>(x + (size_t)row * DM);
    uint4 a = xr[lane], b = xr[32 + lane];
    const uint4* wp = reinterpret_cast<const uint4*>(wr);
    uint4 wa = wp[lane], wb = wp[32 + lane];
    if (threadIdx.x == 0) l2_prefetch(wqkv + blockIdx.x * 6144, 6144);
    uint32_t u[8] = {a.x, a.y, a.z, a.w, b.x, b.y, b.z, b.w};
    uint32_t w[8] = {wa.x, wa.y, wa.z, wa.w, wb.x, wb.y, wb.z, wb.w};
    float f[16];
    float sum = 0.f;
#pragma unroll
    for (int i = 0; i < 8; i++) { f[2 * i] = bf_lo(u[i]); f[2 * i + 1] = bf_hi(u[i]); sum += f[2 * i] + f[2 * i + 1]; }
#pragma unroll
    for (int o = 16; o > 0; o >>= 1) sum += __shfl_xor_sync(~0u, sum, o);
    const float mean = sum * (1.f / DM);
    float sq = 0.f;
#pragma unroll
    for (int i = 0; i < 16; i++) { float d = f[i] - mean; sq = fmaf(d, d, sq); }
#pragma unroll
    for (int o = 16; o > 0; o >>= 1) sq += __shfl_xor_sync(~0u, sq, o);
    const float mb = bfr(mean);
    const float vb = bfr(sq * (1.f / DM));
    const float den = bfr(sqrtf(bfr(vb + 1e-5f)));
    const float rinv = 1.f / den;
    uint32_t o[8];
    float r = 0.f;
#pragma unroll
    for (int i = 0; i < 8; i++) {
        float d0 = bfr(f[2 * i] - mb), d1 = bfr(f[2 * i + 1] - mb);
        o[i] = packbf(d0 * rinv, d1 * rinv);
        r = fmaf(bf_lo(o[i]), bf_lo(w[i]), r);
        r = fmaf(bf_hi(o[i]), bf_hi(w[i]), r);
    }
#pragma unroll
    for (int of = 16; of > 0; of >>= 1) r += __shfl_xor_sync(~0u, r, of);
    uint4* xo = reinterpret_cast<uint4*>(g_xn + (size_t)row * DM);
    xo[lane] = make_uint4(o[0], o[1], o[2], o[3]);
    xo[32 + lane] = make_uint4(o[4], o[5], o[6], o[7]);
    if (lane == 0) g_r[row] = r;
}

constexpr int K1_ST = 5;
constexpr int K1_STAGE = 16384 + 24576;
constexpr int K1_SMEM = K1_ST * K1_STAGE + 1024 + 128;

__device__ __forceinline__ void wgmma_n192(float (&d)[96], uint64_t da, uint64_t db, int scale_d) {
    asm volatile("{\n.reg .pred p;\nsetp.ne.b32 p, %98, 0;\n"
        "wgmma.mma_async.sync.aligned.m64n192k16.f32.bf16.bf16 "
        "{%0,%1,%2,%3,%4,%5,%6,%7,%8,%9,%10,%11,%12,%13,%14,%15,%16,%17,%18,%19,%20,%21,%22,%23,"
        "%24,%25,%26,%27,%28,%29,%30,%31,%32,%33,%34,%35,%36,%37,%38,%39,%40,%41,%42,%43,%44,%45,%46,%47,"
        "%48,%49,%50,%51,%52,%53,%54,%55,%56,%57,%58,%59,%60,%61,%62,%63,%64,%65,%66,%67,%68,%69,%70,%71,"
        "%72,%73,%74,%75,%76,%77,%78,%79,%80,%81,%82,%83,%84,%85,%86,%87,%88,%89,%90,%91,%92,%93,%94,%95}, "
        "%96, %97, p, 1, 1, 0, 1;\n}"
        : "+f"(d[0]), "+f"(d[1]), "+f"(d[2]), "+f"(d[3]), "+f"(d[4]), "+f"(d[5]), "+f"(d[6]), "+f"(d[7]),
          "+f"(d[8]), "+f"(d[9]), "+f"(d[10]), "+f"(d[11]), "+f"(d[12]), "+f"(d[13]), "+f"(d[14]), "+f"(d[15]),
          "+f"(d[16]), "+f"(d[17]), "+f"(d[18]), "+f"(d[19]), "+f"(d[20]), "+f"(d[21]), "+f"(d[22]), "+f"(d[23]),
          "+f"(d[24]), "+f"(d[25]), "+f"(d[26]), "+f"(d[27]), "+f"(d[28]), "+f"(d[29]), "+f"(d[30]), "+f"(d[31]),
          "+f"(d[32]), "+f"(d[33]), "+f"(d[34]), "+f"(d[35]), "+f"(d[36]), "+f"(d[37]), "+f"(d[38]), "+f"(d[39]),
          "+f"(d[40]), "+f"(d[41]), "+f"(d[42]), "+f"(d[43]), "+f"(d[44]), "+f"(d[45]), "+f"(d[46]), "+f"(d[47]),
          "+f"(d[48]), "+f"(d[49]), "+f"(d[50]), "+f"(d[51]), "+f"(d[52]), "+f"(d[53]), "+f"(d[54]), "+f"(d[55]),
          "+f"(d[56]), "+f"(d[57]), "+f"(d[58]), "+f"(d[59]), "+f"(d[60]), "+f"(d[61]), "+f"(d[62]), "+f"(d[63]),
          "+f"(d[64]), "+f"(d[65]), "+f"(d[66]), "+f"(d[67]), "+f"(d[68]), "+f"(d[69]), "+f"(d[70]), "+f"(d[71]),
          "+f"(d[72]), "+f"(d[73]), "+f"(d[74]), "+f"(d[75]), "+f"(d[76]), "+f"(d[77]), "+f"(d[78]), "+f"(d[79]),
          "+f"(d[80]), "+f"(d[81]), "+f"(d[82]), "+f"(d[83]), "+f"(d[84]), "+f"(d[85]), "+f"(d[86]), "+f"(d[87]),
          "+f"(d[88]), "+f"(d[89]), "+f"(d[90]), "+f"(d[91]), "+f"(d[92]), "+f"(d[93]), "+f"(d[94]), "+f"(d[95])
        : "l"(da), "l"(db), "r"(scale_d));
}

__global__ void __launch_bounds__(320, 1) qkv_kernel(const __grid_constant__ CUtensorMap mapA, const __grid_constant__ CUtensorMap mapB,
                                                     const uint8_t* __restrict__ pwg, const uint8_t* __restrict__ pwu, const uint8_t* __restrict__ pwd,
                                                     const uint8_t* __restrict__ pwo) {
    extern __shared__ uint8_t smem_raw[];
    const uint32_t sbase = (smem_u32(smem_raw) + 1023u) & ~1023u;
    const uint32_t bars = sbase + K1_ST * K1_STAGE;
    const int warp = threadIdx.x >> 5, lane = threadIdx.x & 31;
    const int nb = blockIdx.x & 7, mb = blockIdx.x >> 3;
    if (threadIdx.x == 0) {
        for (int s = 0; s < K1_ST; s++) { mbar_init(bars + 8 * s, 2); mbar_init(bars + 8 * (K1_ST + s), 2); }
        fence_barrier_init();
    }
    __syncthreads();
    if (warp == 8) {
        if (lane == 0) {
            for (int c = 0; c < 8; c++) {
                const int s = c < K1_ST ? c : c - K1_ST;
                if (c >= K1_ST) mbar_wait(bars + 8 * (K1_ST + s), 0);
                mbar_expect_tx(bars + 8 * s, 24576);
                tma3d(sbase + s * K1_STAGE + 16384, &mapB, bars + 8 * s, c * 64, nb * 3);
            }
        }
        return;
    }
    if (warp == 9) {
        if (lane == 0) {
            map_prefetch(&mapA);
            pdl_wait();
            pdl_launch();
            for (int c = 0; c < 8; c++) {
                const int s = c < K1_ST ? c : c - K1_ST;
                if (c == K1_ST) {
                    l2_prefetch(pwg + blockIdx.x * 14336, 14336);
                    l2_prefetch(pwu + blockIdx.x * 14336, 14336);
                    l2_prefetch(pwd + blockIdx.x * 14336, 14336);
                    l2_prefetch(pwo + blockIdx.x * 4096, 4096);
                }
                if (c >= K1_ST) mbar_wait(bars + 8 * (K1_ST + s), 0);
                mbar_expect_tx(bars + 8 * s, 16384);
                tma3d(sbase + s * K1_STAGE, &mapA, bars + 8 * s, mb * 128, c);
            }
        }
        return;
    }
    const int wg = warp >> 2;
    float acc[96];
#pragma unroll
    for (int i = 0; i < 96; i++) acc[i] = 0.f;
#pragma unroll 1
    for (int c = 0; c < 8; c++) {
        const int s = c < K1_ST ? c : c - K1_ST;
        const uint32_t st = sbase + s * K1_STAGE;
        mbar_wait(bars + 8 * s, c < K1_ST ? 0 : 1);
        const uint64_t da = mkdesc(st + wg * 8192, 16, 1024, 1);
        const uint64_t db = mkdesc(st + 16384, 8192, 1024, 1);
        WG_FENCE();
#pragma unroll
        for (int k = 0; k < 4; k++) wgmma_n192(acc, da + k * 2, db + k * 128, (c | k) != 0);
        WG_COMMIT();
        if (c + K1_ST < 8 + 1) {
            WG_WAIT(1);
            if (c >= 1 && (threadIdx.x & 127) == 0) mbar_arrive(bars + 8 * (K1_ST + c - 1));
        }
    }
    WG_WAIT(0);
    const int g = lane >> 2, t = lane & 3;
    const int mt = mb * 8 + warp;
#pragma unroll
    for (int hh = 0; hh < 12; hh++) {
        const int gh = nb * 12 + hh;
        const float* a = &acc[hh * 8];
        if (gh < 32) {
            uint4 v;
            v.x = packbf(a[0], a[1]); v.y = packbf(a[2], a[3]);
            v.z = packbf(a[4], a[5]); v.w = packbf(a[6], a[7]);
            g_q[(gh * 128 + mt) * 32 + lane] = v;
        } else {
            uint32_t* dst = reinterpret_cast<uint32_t*>(gh < 64 ? g_k + (gh - 32) * 4096 : g_v + (gh - 64) * 4096);
            const float ks = gh < 64 ? 5.421010862427522e-20f : 1.0f;
            const int off = (mt * 16 + g) * 4 + t;
            dst[off] = packbf(a[0] * ks, a[1] * ks);
            dst[off + 32] = packbf(a[2] * ks, a[3] * ks);
            dst[8192 + off] = packbf(a[4] * ks, a[5] * ks);
            dst[8192 + off + 32] = packbf(a[6] * ks, a[7] * ks);
        }
    }
}

constexpr float SHIFT = 90.0f;
constexpr int PAT = 0xCECC;
constexpr float QS = 0.25f * 1.4426950408889634f * 18446744073709551616.0f;
constexpr float scq = 0.25f * 1.4426950408889634f * 3.3087224502121107e-24f;
constexpr int K2_SMEM = 163840 + 1024 + 128;

__device__ __forceinline__ uint32_t polyexp(float lo, float hi) {
    uint32_t w, g, q, h;
    asm("cvt.pack.sat.s16.s32 %0, %1, %2;" : "=r"(w) : "r"(__float_as_uint(hi)), "r"(__float_as_uint(lo)));
    g = w & 0x007F007Fu;
    asm("fma.rn.f16x2 %0, %1, %2, %3;" : "=r"(q) : "r"(g), "r"(0xf940f940u), "r"(0x35513551u));
    asm("mul.rn.f16x2 %0, %1, %2;" : "=r"(h) : "r"(q), "r"(g));
    return w - h;
}
__device__ __forceinline__ void qk64(float (&s)[32], const uint32_t (&q)[4], uint64_t db) {
    asm volatile("wgmma.mma_async.sync.aligned.m64n64k16.f32.bf16.bf16 "
        "{%0,%1,%2,%3,%4,%5,%6,%7,%8,%9,%10,%11,%12,%13,%14,%15,%16,%17,%18,%19,%20,%21,%22,%23,%24,%25,%26,%27,%28,%29,%30,%31}, "
        "{%32,%33,%34,%35}, %36, 0, 1, 1, 0;"
        : "=f"(s[0]), "=f"(s[1]), "=f"(s[2]), "=f"(s[3]), "=f"(s[4]), "=f"(s[5]), "=f"(s[6]), "=f"(s[7]),
          "=f"(s[8]), "=f"(s[9]), "=f"(s[10]), "=f"(s[11]), "=f"(s[12]), "=f"(s[13]), "=f"(s[14]), "=f"(s[15]),
          "=f"(s[16]), "=f"(s[17]), "=f"(s[18]), "=f"(s[19]), "=f"(s[20]), "=f"(s[21]), "=f"(s[22]), "=f"(s[23]),
          "=f"(s[24]), "=f"(s[25]), "=f"(s[26]), "=f"(s[27]), "=f"(s[28]), "=f"(s[29]), "=f"(s[30]), "=f"(s[31])
        : "r"(q[0]), "r"(q[1]), "r"(q[2]), "r"(q[3]), "l"(db));
}
__device__ __forceinline__ void pv24(float (&o)[12], uint32_t a0, uint32_t a1, uint32_t a2, uint32_t a3, uint64_t db) {
    asm volatile("wgmma.mma_async.sync.aligned.m64n24k16.f32.bf16.bf16 "
        "{%0,%1,%2,%3,%4,%5,%6,%7,%8,%9,%10,%11}, {%12,%13,%14,%15}, %16, 1, 1, 1, 1;"
        : "+f"(o[0]), "+f"(o[1]), "+f"(o[2]), "+f"(o[3]), "+f"(o[4]), "+f"(o[5]), "+f"(o[6]), "+f"(o[7]),
          "+f"(o[8]), "+f"(o[9]), "+f"(o[10]), "+f"(o[11])
        : "r"(a0), "r"(a1), "r"(a2), "r"(a3), "l"(db));
}

__device__ __forceinline__ void attn_safe(float (&o)[12], const uint32_t (&q)[4], uint64_t kdesc0, uint64_t vdesc0) {
    float s[32];
    float m0 = -INFINITY, m1 = -INFINITY;
#pragma unroll
    for (int i = 0; i < 12; i++) o[i] = 0.f;
#pragma unroll 1
    for (int j = 0; j < 32; j++) {
        WG_FENCE();
        qk64(s, q, kdesc0 + (uint64_t)(j * 64));
        WG_COMMIT(); WG_WAIT(0);
        float n0 = m0, n1 = m1;
#pragma unroll
        for (int i = 0; i < 8; i++) { n0 = fmaxf(n0, fmaxf(s[4 * i], s[4 * i + 1])); n1 = fmaxf(n1, fmaxf(s[4 * i + 2], s[4 * i + 3])); }
        n0 = fmaxf(n0, __shfl_xor_sync(~0u, n0, 1)); n0 = fmaxf(n0, __shfl_xor_sync(~0u, n0, 2));
        n1 = fmaxf(n1, __shfl_xor_sync(~0u, n1, 1)); n1 = fmaxf(n1, __shfl_xor_sync(~0u, n1, 2));
        const float c0 = ex2((m0 - n0) * QS), c1 = ex2((m1 - n1) * QS);
        m0 = n0; m1 = n1;
#pragma unroll
        for (int i = 0; i < 3; i++) { o[4 * i] *= c0; o[4 * i + 1] *= c0; o[4 * i + 2] *= c1; o[4 * i + 3] *= c1; }
        uint32_t p[16];
#pragma unroll
        for (int i = 0; i < 8; i++) {
            p[2 * i] = packbf(ex2((s[4 * i] - m0) * QS), ex2((s[4 * i + 1] - m0) * QS));
            p[2 * i + 1] = packbf(ex2((s[4 * i + 2] - m1) * QS), ex2((s[4 * i + 3] - m1) * QS));
        }
        WG_FENCE();
#pragma unroll
        for (int kk = 0; kk < 4; kk++) pv24(o, p[4 * kk], p[4 * kk + 1], p[4 * kk + 2], p[4 * kk + 3], vdesc0 + (uint64_t)(j * 64 + kk * 16));
        WG_COMMIT(); WG_WAIT(0);
    }
}

__device__ __forceinline__ void attn_store(const float (&o)[12], int head, int m64, int warp, int lane) {
    const int g = lane >> 2, t = lane & 3;
    const int row = m64 * 64 + warp * 16 + g;
    const float i0 = 1.f / o[8], i1 = 1.f / o[10];
    uint32_t* p0 = reinterpret_cast<uint32_t*>(g_o + (size_t)row * DM + head * 16 + t * 2);
    uint32_t* p1 = reinterpret_cast<uint32_t*>(g_o + (size_t)(row + 8) * DM + head * 16 + t * 2);
    p0[0] = packbf(o[0] * i0, o[1] * i0); p0[4] = packbf(o[4] * i0, o[5] * i0);
    p1[0] = packbf(o[2] * i1, o[3] * i1); p1[4] = packbf(o[6] * i1, o[7] * i1);
}

constexpr int FS_N = 4;
constexpr int FS_BYTES = 32768;
__device__ __forceinline__ void ldsm4t(uint32_t& r0, uint32_t& r1, uint32_t& r2, uint32_t& r3, uint32_t addr) {
    asm volatile("ldmatrix.sync.aligned.m8n8.x4.trans.shared.b16 {%0,%1,%2,%3}, [%4];" : "=r"(r0), "=r"(r1), "=r"(r2), "=r"(r3) : "r"(addr) : "memory");
}
__device__ __forceinline__ void mma16816(float (&d)[4], uint32_t a0, uint32_t a2, uint32_t b0, uint32_t b1) {
    asm volatile("mma.sync.aligned.m16n8k16.row.col.f32.bf16.bf16.f32 {%0,%1,%2,%3}, {%4,%5,%6,%5}, {%7,%8}, {%0,%1,%2,%3};"
                 : "+f"(d[0]), "+f"(d[1]), "+f"(d[2]), "+f"(d[3]) : "r"(a0), "r"(0u), "r"(a2), "r"(b0), "r"(b1));
}
__device__ void ffn_block(int c, uint8_t* smem, uint32_t sbase, const CUtensorMap* mapG, const CUtensorMap* mapU, const CUtensorMap* mapD) {
    const int tid = threadIdx.x, warp = tid >> 5, lane = tid & 31;
    uint32_t* sx = reinterpret_cast<uint32_t*>(smem + FS_N * FS_BYTES);
    __nv_bfloat16* sh = reinterpret_cast<__nv_bfloat16*>(sx + 512);
    const uint32_t bars = sbase + FS_N * FS_BYTES + 8192;
    __shared__ float tv[32]; __shared__ int ti[32];
    __shared__ int ssel[2];
    auto issue = [&](int item) {
        const int slot = item % FS_N;
        const uint32_t dst = sbase + slot * FS_BYTES, bar = bars + 8 * slot;
        mbar_expect_tx(bar, item < 32 ? 28672 : 32768);
        if (item < 32) {
            tma3d(dst, mapG, bar, item * 16, c * 7);
            tma3d(dst + 14336, mapU, bar, item * 16, c * 7);
        } else {
            tma3d(dst, mapD, bar, c * 448 + (item - 32) * 32, 0);
        }
    };
    if (tid == 0) {
        for (int i = 0; i < FS_N; i++) mbar_init(bars + 8 * i, 1);
        fence_barrier_init();
        for (int i = 0; i < FS_N; i++) issue(i);
    }
    float b1 = -INFINITY, b2 = -INFINITY; int i1 = 0x7fffffff, i2 = 0x7fffffff;
    auto push = [&](float v, int i) {
        if (v > b1 || (v == b1 && i < i1)) { b2 = b1; i2 = i1; b1 = v; i1 = i; }
        else if (v > b2 || (v == b2 && i < i2)) { b2 = v; i2 = i; }
    };
    {
        const float4 rv = reinterpret_cast<const float4*>(g_r)[tid];
        push(rv.x, 4 * tid); push(rv.y, 4 * tid + 1); push(rv.z, 4 * tid + 2); push(rv.w, 4 * tid + 3);
    }
#pragma unroll
    for (int o = 16; o > 0; o >>= 1) {
        float v1 = __shfl_xor_sync(~0u, b1, o), v2 = __shfl_xor_sync(~0u, b2, o);
        int j1 = __shfl_xor_sync(~0u, i1, o), j2 = __shfl_xor_sync(~0u, i2, o);
        push(v1, j1); push(v2, j2);
    }
    if (lane == 0) { tv[2 * warp] = b1; ti[2 * warp] = i1; tv[2 * warp + 1] = b2; ti[2 * warp + 1] = i2; }
    __syncthreads();
    if (warp == 1) {
        b1 = tv[lane]; i1 = ti[lane]; b2 = -INFINITY; i2 = 0x7fffffff;
#pragma unroll
        for (int o = 16; o > 0; o >>= 1) {
            float v1 = __shfl_xor_sync(~0u, b1, o), v2 = __shfl_xor_sync(~0u, b2, o);
            int j1 = __shfl_xor_sync(~0u, i1, o), j2 = __shfl_xor_sync(~0u, i2, o);
            push(v1, j1); push(v2, j2);
        }
        if (lane == 0) {
            i1 = min(max(i1, 0), S_LEN - 1); i2 = min(max(i2, 0), S_LEN - 1);
            ssel[0] = i1; ssel[1] = i2;
            if (c == 0) {
                g_sel[0] = i1; g_sel[1] = i2;
                g_gate[0] = bfr(1.f / (1.f + __expf(-bfr(b1))));
                g_gate[1] = bfr(1.f / (1.f + __expf(-bfr(b2))));
            }
        }
    }
    __syncthreads();
    sx[tid] = *reinterpret_cast<const uint32_t*>(g_xn + (size_t)ssel[tid >> 8] * DM + (tid & 255) * 2);
    __syncthreads();
    const int g = lane >> 2, t = lane & 3;
    const int lrow = lane & 15, lsel = lane >> 4;
    {
        float ag[4][4], au[4][4];
#pragma unroll
        for (int j = 0; j < 4; j++) { ag[j][0] = ag[j][1] = ag[j][2] = ag[j][3] = 0.f; au[j][0] = au[j][1] = au[j][2] = au[j][3] = 0.f; }
#pragma unroll 1
        for (int it = 0; it < 32; it++) {
            const int slot = it % FS_N;
            const uint32_t a0 = g < 2 ? sx[g * 256 + it * 8 + t] : 0u, a2 = g < 2 ? sx[g * 256 + it * 8 + 4 + t] : 0u;
            mbar_wait(bars + 8 * slot, (it / FS_N) & 1);
            const uint32_t base = sbase + slot * FS_BYTES + lsel * 14336 + lrow * 128;
#pragma unroll
            for (int j = 0; j < 4; j++) {
                const int nt = warp + j * 16;
                if (nt < 56) {
                    uint32_t b0, b1, b2, b3;
                    ldsm4t(b0, b1, b2, b3, base + (nt >> 3) * 2048 + (((nt & 7) ^ (lrow & 7)) << 4));
                    mma16816(ag[j], a0, a2, b0, b1);
                    mma16816(au[j], a0, a2, b2, b3);
                }
            }
            __syncthreads();
            if (tid == 480) issue(it + FS_N);
        }
        if (g < 2) {
#pragma unroll
            for (int j = 0; j < 4; j++) {
                const int nt = warp + j * 16;
                if (nt < 56) {
#pragma unroll
                    for (int e = 0; e < 2; e++) {
                        const float gs = bfr(ag[j][e]), us = bfr(au[j][e]);
                        const float sg = bfr(gs / (1.f + __expf(-gs)));
                        sh[g * 448 + nt * 8 + t * 2 + e] = __float2bfloat16_rn(sg * us);
                    }
                }
            }
        }
        __syncthreads();
    }
    {
        const uint32_t* shw = reinterpret_cast<const uint32_t*>(sh);
        float a[4][4];
#pragma unroll
        for (int j = 0; j < 4; j++) a[j][0] = a[j][1] = a[j][2] = a[j][3] = 0.f;
#pragma unroll 1
        for (int it = 32; it < 46; it++) {
            const int slot = it % FS_N;
            uint32_t af[4];
#pragma unroll
            for (int q = 0; q < 4; q++) af[q] = g < 2 ? shw[g * 224 + (it - 32) * 16 + q * 4 + t] : 0u;
            mbar_wait(bars + 8 * slot, (it / FS_N) & 1);
            const uint32_t base = sbase + slot * FS_BYTES + (warp >> 1) * 4096 + lane * 128;
#pragma unroll
            for (int j = 0; j < 4; j++) {
                const int u = (warp & 1) * 4 + j;
                uint32_t b0, b1, b2, b3;
                ldsm4t(b0, b1, b2, b3, base + ((u ^ (lane & 7)) << 4));
                mma16816(a[j], af[0], af[1], b0, b1);
                mma16816(a[j], af[2], af[3], b2, b3);
            }
            __syncthreads();
            if (tid == 480 && it + FS_N < 46) issue(it + FS_N);
        }
        if (g < 2) {
#pragma unroll
            for (int j = 0; j < 4; j++)
                *reinterpret_cast<float2*>(&g_ypart[c * 1024 + g * 512 + (warp * 4 + j) * 8 + t * 2]) = make_float2(a[j][0], a[j][1]);
        }
    }
}

__global__ void __launch_bounds__(512, 1) attn_kernel(const __grid_constant__ CUtensorMap mapG, const __grid_constant__ CUtensorMap mapU,
                                                      const __grid_constant__ CUtensorMap mapD, float sc) {
    extern __shared__ uint8_t smem_raw[];
    const uint32_t sraw = smem_u32(smem_raw);
    const uint32_t sbase = (sraw + 1023u) & ~1023u;
    uint8_t* sptr = smem_raw + (sbase - sraw);
    if (blockIdx.x < 4) {
        pdl_launch();
        ffn_block(blockIdx.x, sptr, sbase, &mapG, &mapU, &mapD);
        return;
    }
    const uint32_t bars = sbase + 163840;
    const int head = (blockIdx.x - 4) >> 2, quarter = blockIdx.x & 3;
    const int wg = threadIdx.x >> 7, warp = (threadIdx.x >> 5) & 3, lane = threadIdx.x & 31;
    if (threadIdx.x == 0) {
        for (int c = 0; c < 8; c++) mbar_init(bars + 8 * c, 1);
        fence_barrier_init();
        for (int c = 0; c < 8; c++) mbar_expect_tx(bars + 8 * c, 16384);
    }
    {
        uint4* ones = reinterpret_cast<uint4*>(sptr + 131072);
        for (int i = threadIdx.x; i < 2048; i += 512) ones[i] = make_uint4(0x3f803f80u, 0x3f803f80u, 0x3f803f80u, 0x3f803f80u);
        fence_proxy_async();
    }
    __syncthreads();
    pdl_wait();
    pdl_launch();
    if (threadIdx.x == 0) {
        const uint8_t* kp = reinterpret_cast<const uint8_t*>(g_k + head * 4096);
        const uint8_t* vp = reinterpret_cast<const uint8_t*>(g_v + head * 4096);
        for (int c = 0; c < 8; c++) {
            bulk_g2s(sbase + c * 4096, kp + c * 4096, 4096, bars + 8 * c);
            bulk_g2s(sbase + 32768 + c * 4096, kp + 32768 + c * 4096, 4096, bars + 8 * c);
            bulk_g2s(sbase + 65536 + c * 4096, vp + c * 4096, 4096, bars + 8 * c);
            bulk_g2s(sbase + 98304 + c * 4096, vp + 32768 + c * 4096, 4096, bars + 8 * c);
        }
    }
    const uint64_t kdesc0 = mkdesc(sbase, 32768, 128, 0);
    const uint64_t vdesc0 = mkdesc(sbase + 65536, 128, 32768, 0);
    uint32_t badmask = 0;
    uint32_t q[4];
    { const uint4 qq = g_q[(head * 128 + (quarter * 8 + wg) * 4 + warp) * 32 + lane]; q[0] = qq.x; q[1] = qq.y; q[2] = qq.z; q[3] = qq.w; }
#pragma unroll 1
    for (int mt = 0; mt < 2; mt++) {
        const int m64 = quarter * 8 + mt * 4 + wg;
        float s[32], s2[32], o[12];
#pragma unroll
        for (int i = 0; i < 12; i++) o[i] = 0.f;
        mbar_wait(bars, 0);
        WG_FENCE();
        qk64(s, q, kdesc0);
        WG_COMMIT(); WG_WAIT(0);
        float mx0 = -INFINITY, mx1 = -INFINITY;
#pragma unroll
        for (int i = 0; i < 8; i++) { mx0 = fmaxf(mx0, fmaxf(s[4 * i], s[4 * i + 1])); mx1 = fmaxf(mx1, fmaxf(s[4 * i + 2], s[4 * i + 3])); }
        mx0 = fmaxf(mx0, __shfl_xor_sync(~0u, mx0, 1)); mx0 = fmaxf(mx0, __shfl_xor_sync(~0u, mx0, 2));
        mx1 = fmaxf(mx1, __shfl_xor_sync(~0u, mx1, 1)); mx1 = fmaxf(mx1, __shfl_xor_sync(~0u, mx1, 2));
        float cm0 = -(ceilf(mx0 * QS) + SHIFT), cm1 = -(ceilf(mx1 * QS) + SHIFT);
        float cp0 = (cm0 + 127.f) * sc, cp1 = (cm1 + 127.f) * sc;
        asm volatile("" : "+f"(cm0), "+f"(cm1), "+f"(cp0), "+f"(cp1));
        uint64_t kd = kdesc0, vd = vdesc0;
        auto step = [&](float (&sc_)[32], float (&sn)[32]) {
            kd += 64;
            WG_FENCE();
            qk64(sn, q, kd);
            WG_COMMIT();
#pragma unroll
            for (int kk = 0; kk < 4; kk++) {
                uint32_t p[4];
#pragma unroll
                for (int e = 0; e < 4; e++) {
                    const int r = kk * 8 + e * 2;
                    const float cmx = (e & 1) ? cm1 : cm0, cpx = (e & 1) ? cp1 : cp0;
                    if ((PAT >> (kk * 4 + e)) & 1) p[e] = polyexp(fmaf(sc_[r], scq, cpx), fmaf(sc_[r + 1], scq, cpx));
                    else p[e] = packbf(ex2(fmaf(sc_[r], QS, cmx)), ex2(fmaf(sc_[r + 1], QS, cmx)));
                }
                WG_FENCE();
                pv24(o, p[0], p[1], p[2], p[3], vd);
                vd += 16;
            }
            WG_COMMIT();
            WG_WAIT(1);
        };
#pragma unroll 1
        for (int c = 0; c < 16; c++) {
            if (mt == 0 && (c & 1) == 0 && c < 14) mbar_wait(bars + 4 * c + 8, 0);
            step(s, s2); step(s2, s);
        }
        WG_WAIT(0);
        {
            const uint4 qq = g_q[(head * 128 + (quarter * 8 + 4 + wg) * 4 + warp) * 32 + lane]; q[0] = qq.x; q[1] = qq.y; q[2] = qq.z; q[3] = qq.w;
        }
        bool bad = !(o[8] > 0.f) || !(o[10] > 0.f);
#pragma unroll
        for (int i = 0; i < 12; i++) bad = bad || !(fabsf(o[i]) <= 3.0e38f);
        uint32_t anybad;
        asm volatile("{\n.reg .pred p, q;\nsetp.ne.u32 p, %1, 0;\nbarrier.cta.red.or.pred q, %2, 128, p;\nselp.u32 %0, 1, 0, q;\n}"
                     : "=r"(anybad) : "r"((uint32_t)bad), "r"(wg + 1) : "memory");
        badmask |= anybad << mt;
        attn_store(o, head, m64, warp, lane);
    }
#pragma unroll 1
    for (int mt = 0; mt < 2; mt++) {
        if (!((badmask >> mt) & 1)) continue;
        const int m64 = quarter * 8 + mt * 4 + wg;
        { const uint4 qq = g_q[(head * 128 + m64 * 4 + warp) * 32 + lane]; q[0] = qq.x; q[1] = qq.y; q[2] = qq.z; q[3] = qq.w; }
        float o[12];
        attn_safe(o, q, mkdesc(sbase, 32768, 128, 0), mkdesc(sbase + 65536, 128, 32768, 0));
        attn_store(o, head, m64, warp, lane);
    }
}

constexpr int K3_SMEM = 8 * 8192 + 8 * 16384 + 1024 + 128;

__device__ __forceinline__ void wgmma_n64(float (&d)[32], uint64_t da, uint64_t db, int scale_d) {
    asm volatile("{\n.reg .pred p;\nsetp.ne.b32 p, %34, 0;\n"
        "wgmma.mma_async.sync.aligned.m64n64k16.f32.bf16.bf16 "
        "{%0,%1,%2,%3,%4,%5,%6,%7,%8,%9,%10,%11,%12,%13,%14,%15,%16,%17,%18,%19,%20,%21,%22,%23,%24,%25,%26,%27,%28,%29,%30,%31}, "
        "%32, %33, p, 1, 1, 0, 1;\n}"
        : "+f"(d[0]), "+f"(d[1]), "+f"(d[2]), "+f"(d[3]), "+f"(d[4]), "+f"(d[5]), "+f"(d[6]), "+f"(d[7]),
          "+f"(d[8]), "+f"(d[9]), "+f"(d[10]), "+f"(d[11]), "+f"(d[12]), "+f"(d[13]), "+f"(d[14]), "+f"(d[15]),
          "+f"(d[16]), "+f"(d[17]), "+f"(d[18]), "+f"(d[19]), "+f"(d[20]), "+f"(d[21]), "+f"(d[22]), "+f"(d[23]),
          "+f"(d[24]), "+f"(d[25]), "+f"(d[26]), "+f"(d[27]), "+f"(d[28]), "+f"(d[29]), "+f"(d[30]), "+f"(d[31])
        : "l"(da), "l"(db), "r"(scale_d));
}

__global__ void __launch_bounds__(256, 1) oproj_kernel(const __grid_constant__ CUtensorMap mapA, const __grid_constant__ CUtensorMap mapB,
                                                       const __nv_bfloat16* __restrict__ x, __nv_bfloat16* __restrict__ out) {
    extern __shared__ uint8_t smem_raw[];
    const uint32_t sbase = (smem_u32(smem_raw) + 1023u) & ~1023u;
    const uint32_t sA = sbase, sB = sbase + 8 * 8192, bars = sbase + 8 * 8192 + 8 * 16384;
    const int warp = threadIdx.x >> 5, lane = threadIdx.x & 31, wg = warp >> 2;
    const int nb = blockIdx.x & 3, mb = blockIdx.x >> 2;
    if (threadIdx.x == 0) {
        for (int c = 0; c < 8; c++) mbar_init(bars + 8 * c, 1);
        fence_barrier_init();
        map_prefetch(&mapA);
        for (int h = 0; h < 2; h++) {
            mbar_expect_tx(bars + 8 * (4 + h), 65536);
            tma3d(sB + h * 65536, &mapB, bars + 8 * (4 + h), h * 256, nb * 2);
        }
    }
    const int g = lane >> 2, t = lane & 3;
    const int row0 = mb * 64 + (warp & 3) * 16 + g;
    const int col0 = nb * 128 + wg * 64 + t * 2;
    uint32_t xv[16], nv[16];
#pragma unroll
    for (int i = 0; i < 8; i++) {
        xv[2 * i] = *reinterpret_cast<const uint32_t*>(x + (size_t)row0 * DM + col0 + i * 8);
        xv[2 * i + 1] = *reinterpret_cast<const uint32_t*>(x + (size_t)(row0 + 8) * DM + col0 + i * 8);
        nv[2 * i] = *reinterpret_cast<const uint32_t*>(g_xn + (size_t)row0 * DM + col0 + i * 8);
        nv[2 * i + 1] = *reinterpret_cast<const uint32_t*>(g_xn + (size_t)(row0 + 8) * DM + col0 + i * 8);
    }
    __syncthreads();
    pdl_wait();
    if (threadIdx.x == 0) {
        for (int c = 0; c < 4; c++) {
            mbar_expect_tx(bars + 8 * c, 16384);
            tma3d(sA + c * 16384, &mapA, bars + 8 * c, mb * 64, c * 2);
        }
    }
    __shared__ float supd[2][128];
    const int sel0 = g_sel[0], sel1 = g_sel[1];
    {
        const int which = threadIdx.x >> 7, col = nb * 128 + (threadIdx.x & 127);
        const float y = g_ypart[which * 512 + col] + g_ypart[1024 + which * 512 + col] + g_ypart[2048 + which * 512 + col] + g_ypart[3072 + which * 512 + col];
        supd[which][threadIdx.x & 127] = bfr(bfr(y) * g_gate[which]);
    }
    __syncthreads();
    float acc[32];
#pragma unroll
    for (int i = 0; i < 32; i++) acc[i] = 0.f;
#pragma unroll 1
    for (int c = 0; c < 8; c++) {
        if ((c & 3) == 0) mbar_wait(bars + 8 * (4 + (c >> 2)), 0);
        if ((c & 1) == 0) mbar_wait(bars + 8 * (c >> 1), 0);
        const uint64_t da = mkdesc(sA + c * 8192, 16, 1024, 1);
        const uint64_t db = mkdesc(sB + (c >> 2) * 65536 + wg * 32768 + (c & 3) * 8192, 8192, 1024, 1);
        WG_FENCE();
#pragma unroll
        for (int k = 0; k < 4; k++) wgmma_n64(acc, da + k * 2, db + k * 128, (c | k) != 0);
        WG_COMMIT();
    }
    WG_WAIT(0);
#pragma unroll
    for (int h = 0; h < 2; h++) {
        const int row = row0 + h * 8;
        const int which = row == sel0 ? 0 : (row == sel1 ? 1 : -1);
#pragma unroll
        for (int i = 0; i < 8; i++) {
            const int col = col0 + i * 8;
            float b0 = bf_lo(nv[2 * i + h]), b1 = bf_hi(nv[2 * i + h]);
            if (which >= 0) {
                b0 = bfr(b0 + supd[which][col - nb * 128]); b1 = bfr(b1 + supd[which][col + 1 - nb * 128]);
            }
            const float t0 = bfr(bf_lo(xv[2 * i + h]) + bfr(acc[4 * i + 2 * h]));
            const float t1 = bfr(bf_hi(xv[2 * i + h]) + bfr(acc[4 * i + 2 * h + 1]));
            *reinterpret_cast<uint32_t*>(out + (size_t)row * DM + col) = packbf(t0 + b0, t1 + b1);
        }
    }
}

typedef CUresult (*EncodeFn)(CUtensorMap*, CUtensorMapDataType, cuuint32_t, void*, const cuuint64_t*, const cuuint64_t*,
                             const cuuint32_t*, const cuuint32_t*, CUtensorMapInterleave, CUtensorMapSwizzle,
                             CUtensorMapL2promotion, CUtensorMapFloatOOBfill);

void make_map(EncodeFn fn, CUtensorMap* m, const void* ptr, uint64_t cols, uint64_t rows, uint32_t box_rows, uint32_t box_chunks) {
    cuuint64_t dims[3] = {64, rows, cols / 64};
    cuuint64_t strides[2] = {cols * 2, 128};
    cuuint32_t box[3] = {64, box_rows, box_chunks};
    cuuint32_t es[3] = {1, 1, 1};
    fn(m, CU_TENSOR_MAP_DATA_TYPE_BFLOAT16, 3, const_cast<void*>(ptr), dims, strides, box, es, CU_TENSOR_MAP_INTERLEAVE_NONE,
       CU_TENSOR_MAP_SWIZZLE_128B, CU_TENSOR_MAP_L2_PROMOTION_L2_256B, CU_TENSOR_MAP_FLOAT_OOB_FILL_NONE);
}

template <typename... KArgs, typename... Args>
void launch(void (*kern)(KArgs...), int grid, int block, int smem, bool pdl, Args... args) {
    cudaLaunchConfig_t cfg = {};
    cfg.gridDim = dim3(grid); cfg.blockDim = dim3(block); cfg.dynamicSmemBytes = smem; cfg.stream = cudaStreamPerThread;
    cudaLaunchAttribute at[1];
    at[0].id = cudaLaunchAttributeProgrammaticStreamSerialization;
    at[0].val.programmaticStreamSerializationAllowed = 1;
    cfg.attrs = at; cfg.numAttrs = pdl ? 1 : 0;
    cudaLaunchKernelEx(&cfg, kern, KArgs(args)...);
}

}

extern "C" void kernel_launch(void* const* d_in, const int* in_sizes, int n_in, void* d_out, int out_size) {
    const __nv_bfloat16* x = (const __nv_bfloat16*)d_in[0];
    const __nv_bfloat16* wqkv = (const __nv_bfloat16*)d_in[1];
    const __nv_bfloat16* wo = (const __nv_bfloat16*)d_in[2];
    const __nv_bfloat16* wr = (const __nv_bfloat16*)d_in[4];
    const __nv_bfloat16* wgate = (const __nv_bfloat16*)d_in[5];
    const __nv_bfloat16* wup = (const __nv_bfloat16*)d_in[6];
    const __nv_bfloat16* wdown = (const __nv_bfloat16*)d_in[7];
    __nv_bfloat16* out = (__nv_bfloat16*)d_out;

    static EncodeFn enc = nullptr;
    static void* p_xn = nullptr; static void* p_o = nullptr;
    if (!enc) {
        void* fn = nullptr; cudaDriverEntryPointQueryResult qr;
        cudaGetDriverEntryPoint("cuTensorMapEncodeTiled", &fn, cudaEnableDefault, &qr);
        enc = (EncodeFn)fn;
        cudaGetSymbolAddress(&p_xn, g_xn);
        cudaGetSymbolAddress(&p_o, g_o);
        cudaFuncSetAttribute(qkv_kernel, cudaFuncAttributeMaxDynamicSharedMemorySize, K1_SMEM);
        cudaFuncSetAttribute(attn_kernel, cudaFuncAttributeMaxDynamicSharedMemorySize, K2_SMEM);
        cudaFuncSetAttribute(oproj_kernel, cudaFuncAttributeMaxDynamicSharedMemorySize, K3_SMEM);
    }
    CUtensorMap mXn, mWqkv, mO, mWo, mG, mU, mD;
    make_map(enc, &mG, wgate, FF, DM, 16, 7);
    make_map(enc, &mU, wup, FF, DM, 16, 7);
    make_map(enc, &mD, wdown, DM, FF, 32, 8);
    make_map(enc, &mXn, p_xn, DM, S_LEN, 128, 1);
    make_map(enc, &mWqkv, wqkv, 3 * DM, DM, 64, 3);
    make_map(enc, &mO, p_o, DM, S_LEN, 64, 2);
    make_map(enc, &mWo, wo, DM, DM, 256, 2);

    union { uint32_t u; float f; } scu; scu.u = 128u;

    launch(ln_kernel, S_LEN / 8, 256, 0, false, x, wr, (const uint8_t*)wqkv);
    launch(qkv_kernel, 128, 320, K1_SMEM, true, mXn, mWqkv, (const uint8_t*)wgate, (const uint8_t*)wup, (const uint8_t*)wdown, (const uint8_t*)wo);
    launch(attn_kernel, 132, 512, K2_SMEM, true, mG, mU, mD, scu.f);
    launch(oproj_kernel, 128, 256, K3_SMEM, true, mO, mWo, x, out);
}
```
